```python
import torch

def _softmax(x, axis=-1):
    return torch.softmax(x, dim=axis)
def _gelu(x):
    return torch.nn.functional.gelu(x, approximate="tanh")
def _silu(x):
    return torch.nn.functional.silu(x)
def _sigmoid(x):
    return torch.sigmoid(x)
def _layernorm(x, axis=-1, eps=1e-5):
    m = x.mean(dim=axis, keepdim=True)
    v = x.var(dim=axis, keepdim=True, unbiased=False)
    return (x - m) / torch.sqrt(v + eps)
def _scatter_add(tgt, idx, src, axis=0):
    return tgt.clone().index_add_(axis, idx, src)
def _segment_sum(src, seg, n):
    out = torch.zeros((n,) + src.shape[1:], dtype=src.dtype)
    return out.index_add_(0, seg, src)
def _pad(x, pw):
    flat = tuple(v for pair in reversed(pw) for v in pair)
    return torch.nn.functional.pad(x, flat)

kernel_name = 'standalone__normalfloat_lut_af4__prompt'

def setup_inputs():

    _w = (lambda a: (lambda t: t.to(torch.bfloat16) if t.is_floating_point() else t)(torch.as_tensor(a)))
    B, S, D, F = 1, 2048, 1024, 3584
    G = -1 if -1 > 0 else D
    D = (D // G) * G
    ng = D // G
    nf4 = torch.tensor([
        -1.0, -0.6961928009986877, -0.5250730514526367, -0.39491748809814453,
        -0.28444138169288635, -0.18477343022823334, -0.09105003625154495, 0.0,
        0.07958029955625534, 0.16093020141124725, 0.24611230194568634,
        0.33791524171829224, 0.44070982933044434, 0.5626170039176941,
        0.7229568362236023, 1.0,
    ], dtype=float)
    qw = torch.randint(0, 16, (D, F)).to(torch.int64)
    return {
        "x": _w((lambda *s: torch.randn(*s, dtype=torch.bfloat16) * 0.05)(B, S, D)),
        "qw": _w(qw),
        "lut": _w(nf4),
        "scales": _w(torch.abs((lambda *s: torch.randn(*s, dtype=torch.bfloat16) * 0.05)(ng, F)).to(float) + 0.01),
    }

def reference(x, qw, lut, scales):
    B, S, D = x.shape
    ng, F = scales.shape
    G = D // ng
    deq = lut[qw]
    s = (lambda x, n, axis: torch.repeat_interleave(x, n, dim=axis))(scales, G, axis=0)
    w = (lambda x, dt: x.to(dt))(deq, x.dtype) * (lambda x, dt: x.to(dt))(s, x.dtype)
    return torch.einsum("bsd,df->bsf", x, w)
```

```cpp
#include <cuda_runtime.h>
#include <cuda_bf16.h>
#include <cuda.h>
#include <stdint.h>

namespace {

constexpr int S_DIM = 2048, D_DIM = 1024, F_DIM = 3584;
constexpr int BM = 256, BN = 224, BK = 64;
constexpr int NKB = D_DIM / BK;
constexpr int NJ = F_DIM / BN;
constexpr int NI = S_DIM / BM;
constexpr int WS = 5;
constexpr int XS = 5;
constexpr int ENDK = 4;
constexpr int NR = NKB - ENDK;
constexpr int X_SLICE = 64 * BK * 2;
constexpr int W_STAGE = BN * BK * 2;
constexpr int W_KC = BN * 16;

__device__ uint4 g_w[NJ * NKB * 8 * BN];
__device__ unsigned g_flag[NJ][32];

__device__ __forceinline__ uint32_t smem_u32(const void* p) { return (uint32_t)__cvta_generic_to_shared(p); }
__device__ __forceinline__ void mbar_init(uint32_t bar, uint32_t cnt) {
  asm volatile("mbarrier.init.shared::cta.b64 [%0], %1;" ::"r"(bar), "r"(cnt) : "memory");
}
__device__ __forceinline__ void mbar_expect_tx(uint32_t bar, uint32_t bytes) {
  asm volatile("mbarrier.arrive.expect_tx.shared::cta.b64 _, [%0], %1;" ::"r"(bar), "r"(bytes) : "memory");
}
__device__ __forceinline__ void mbar_arrive(uint32_t bar) {
  asm volatile("mbarrier.arrive.shared::cta.b64 _, [%0];" ::"r"(bar) : "memory");
}
__device__ __forceinline__ void mbar_wait(uint32_t bar, uint32_t parity) {
  asm volatile(
      "{\n.reg .pred p;\n"
      "LAB_WAIT:\n"
      "mbarrier.try_wait.parity.shared::cta.b64 p, [%0], %1;\n"
      "@p bra LAB_DONE;\n"
      "bra LAB_WAIT;\n"
      "LAB_DONE:\n}\n" ::"r"(bar), "r"(parity) : "memory");
}
__device__ __forceinline__ void tma_load_2d(uint32_t dst, const CUtensorMap* tm, int c0, int c1, uint32_t bar) {
  asm volatile(
      "cp.async.bulk.tensor.2d.shared::cluster.global.mbarrier::complete_tx::bytes [%0], [%1, {%3, %4}], [%2];"
      ::"r"(dst), "l"(tm), "r"(bar), "r"(c0), "r"(c1) : "memory");
}
__device__ __forceinline__ void bulk_load(uint32_t dst, const void* src, uint32_t bytes, uint32_t bar) {
  asm volatile(
      "cp.async.bulk.shared::cluster.global.mbarrier::complete_tx::bytes [%0], [%1], %2, [%3];"
      ::"r"(dst), "l"(src), "r"(bytes), "r"(bar) : "memory");
}
__device__ __forceinline__ void l2_prefetch(const void* src, uint32_t bytes) {
  asm volatile("cp.async.bulk.prefetch.L2.global [%0], %1;" ::"l"(src), "r"(bytes) : "memory");
}
__device__ __forceinline__ int ldg_stream(const int* p) {
  int v;
  asm volatile("ld.global.nc.L1::no_allocate.b32 %0, [%1];" : "=r"(v) : "l"(p));
  return v;
}
__device__ __forceinline__ unsigned ld_acquire(const unsigned* p) {
  unsigned v;
  asm volatile("ld.acquire.gpu.global.u32 %0, [%1];" : "=r"(v) : "l"(p) : "memory");
  return v;
}
__device__ __forceinline__ void wgmma_fence() { asm volatile("wgmma.fence.sync.aligned;" ::: "memory"); }
__device__ __forceinline__ void wgmma_commit() { asm volatile("wgmma.commit_group.sync.aligned;" ::: "memory"); }
template <int N>
__device__ __forceinline__ void wgmma_wait() { asm volatile("wgmma.wait_group.sync.aligned %0;" ::"n"(N) : "memory"); }
__device__ __forceinline__ void bar_sync(int id, int n) { asm volatile("bar.sync %0, %1;" ::"r"(id), "r"(n) : "memory"); }
__device__ __forceinline__ void bar_arrive(int id, int n) { asm volatile("bar.arrive %0, %1;" ::"r"(id), "r"(n) : "memory"); }

__device__ __forceinline__ void wgmma_m64n224k16(float (&d)[112], uint64_t da, uint64_t db, int scale_d) {
  asm volatile(
    "{\n.reg .pred p;\nsetp.ne.b32 p, %114, 0;\n"
    "wgmma.mma_async.sync.aligned.m64n224k16.f32.bf16.bf16 "
    "{%0, %1, %2, %3, %4, %5, %6, %7, %8, %9, %10, %11, %12, %13, %14, %15, "
    "%16, %17, %18, %19, %20, %21, %22, %23, %24, %25, %26, %27, %28, %29, %30, %31, "
    "%32, %33, %34, %35, %36, %37, %38, %39, %40, %41, %42, %43, %44, %45, %46, %47, "
    "%48, %49, %50, %51, %52, %53, %54, %55, %56, %57, %58, %59, %60, %61, %62, %63, "
    "%64, %65, %66, %67, %68, %69, %70, %71, %72, %73, %74, %75, %76, %77, %78, %79, "
    "%80, %81, %82, %83, %84, %85, %86, %87, %88, %89, %90, %91, %92, %93, %94, %95, "
    "%96, %97, %98, %99, %100, %101, %102, %103, %104, %105, %106, %107, %108, %109, %110, %111}, "
    "%112, %113, p, 1, 1, 0, 0;\n}\n"
    : "+f"(d[0]), "+f"(d[1]), "+f"(d[2]), "+f"(d[3]), "+f"(d[4]), "+f"(d[5]), "+f"(d[6]), "+f"(d[7]),
      "+f"(d[8]), "+f"(d[9]), "+f"(d[10]), "+f"(d[11]), "+f"(d[12]), "+f"(d[13]), "+f"(d[14]), "+f"(d[15]),
      "+f"(d[16]), "+f"(d[17]), "+f"(d[18]), "+f"(d[19]), "+f"(d[20]), "+f"(d[21]), "+f"(d[22]), "+f"(d[23]),
      "+f"(d[24]), "+f"(d[25]), "+f"(d[26]), "+f"(d[27]), "+f"(d[28]), "+f"(d[29]), "+f"(d[30]), "+f"(d[31]),
      "+f"(d[32]), "+f"(d[33]), "+f"(d[34]), "+f"(d[35]), "+f"(d[36]), "+f"(d[37]), "+f"(d[38]), "+f"(d[39]),
      "+f"(d[40]), "+f"(d[41]), "+f"(d[42]), "+f"(d[43]), "+f"(d[44]), "+f"(d[45]), "+f"(d[46]), "+f"(d[47]),
      "+f"(d[48]), "+f"(d[49]), "+f"(d[50]), "+f"(d[51]), "+f"(d[52]), "+f"(d[53]), "+f"(d[54]), "+f"(d[55]),
      "+f"(d[56]), "+f"(d[57]), "+f"(d[58]), "+f"(d[59]), "+f"(d[60]), "+f"(d[61]), "+f"(d[62]), "+f"(d[63]),
      "+f"(d[64]), "+f"(d[65]), "+f"(d[66]), "+f"(d[67]), "+f"(d[68]), "+f"(d[69]), "+f"(d[70]), "+f"(d[71]),
      "+f"(d[72]), "+f"(d[73]), "+f"(d[74]), "+f"(d[75]), "+f"(d[76]), "+f"(d[77]), "+f"(d[78]), "+f"(d[79]),
      "+f"(d[80]), "+f"(d[81]), "+f"(d[82]), "+f"(d[83]), "+f"(d[84]), "+f"(d[85]), "+f"(d[86]), "+f"(d[87]),
      "+f"(d[88]), "+f"(d[89]), "+f"(d[90]), "+f"(d[91]), "+f"(d[92]), "+f"(d[93]), "+f"(d[94]), "+f"(d[95]),
      "+f"(d[96]), "+f"(d[97]), "+f"(d[98]), "+f"(d[99]), "+f"(d[100]), "+f"(d[101]), "+f"(d[102]), "+f"(d[103]),
      "+f"(d[104]), "+f"(d[105]), "+f"(d[106]), "+f"(d[107]), "+f"(d[108]), "+f"(d[109]), "+f"(d[110]), "+f"(d[111])
    : "l"(da), "l"(db), "r"(scale_d));
}

__device__ __forceinline__ uint32_t pack_bf16(float lo, float hi) {
  uint32_t r;
  asm("cvt.rn.bf16x2.f32 %0, %1, %2;" : "=r"(r) : "f"(hi), "f"(lo));
  return r;
}

__device__ __forceinline__ int perm32(int n) { return (n & ~30) | ((n & 6) << 2) | ((n >> 2) & 6); }

constexpr int SMEM_X = 0;
constexpr int SMEM_W = 2 * XS * X_SLICE;
constexpr int SMEM_BAR = SMEM_W + WS * W_STAGE;
constexpr int B_FULLW = 0, B_EMPTYW = B_FULLW + WS, B_FULLX = B_EMPTYW + WS, B_EMPTYX = B_FULLX + 2 * XS,
              B_DQ = B_EMPTYX + 2 * XS, B_COUNT = B_DQ + 16;
constexpr int SMEM_TL = SMEM_BAR + 512;
constexpr int SMEM_TOTAL = SMEM_TL + 2048;

#define TL(i)
#define TLG(i)

__device__ __forceinline__ void store_acc(const float (&a)[112], __nv_bfloat16* p) {
#pragma unroll
  for (int J = 0; J < 7; J++) {
    uint4 v0, v1;
    v0.x = pack_bf16(a[16 * J + 0], a[16 * J + 1]);
    v0.y = pack_bf16(a[16 * J + 4], a[16 * J + 5]);
    v0.z = pack_bf16(a[16 * J + 8], a[16 * J + 9]);
    v0.w = pack_bf16(a[16 * J + 12], a[16 * J + 13]);
    v1.x = pack_bf16(a[16 * J + 2], a[16 * J + 3]);
    v1.y = pack_bf16(a[16 * J + 6], a[16 * J + 7]);
    v1.z = pack_bf16(a[16 * J + 10], a[16 * J + 11]);
    v1.w = pack_bf16(a[16 * J + 14], a[16 * J + 15]);
    *reinterpret_cast<uint4*>(p + 32 * J) = v0;
    *reinterpret_cast<uint4*>(p + 8 * F_DIM + 32 * J) = v1;
  }
}

__device__ __forceinline__ void load_unit(int (&q)[8], const int* p) {
#pragma unroll
  for (int i = 0; i < 8; i++) q[i] = ldg_stream(p + i * F_DIM);
}
__device__ __forceinline__ uint4 convert_unit(const int (&q)[8], float lutv, float sc) {
  float v[8];
#pragma unroll
  for (int i = 0; i < 8; i++) v[i] = __shfl_sync(0xffffffffu, lutv, q[i]) * sc;
  uint4 o;
  o.x = pack_bf16(v[0], v[1]);
  o.y = pack_bf16(v[2], v[3]);
  o.z = pack_bf16(v[4], v[5]);
  o.w = pack_bf16(v[6], v[7]);
  return o;
}

constexpr int PU = 3;

__global__ void __launch_bounds__(256, 1)
fused_kernel(const __grid_constant__ CUtensorMap tm_x, const int* __restrict__ qw,
             const __nv_bfloat16* __restrict__ lut, const __nv_bfloat16* __restrict__ scales,
             __nv_bfloat16* __restrict__ out) {
  extern __shared__ __align__(1024) uint8_t smem_raw[];
  const uint32_t sbase = smem_u32(smem_raw);
  const uint32_t bars = sbase + SMEM_BAR;
  const int j = blockIdx.x >> 3, it = blockIdx.x & 7;
  const int warp = __shfl_sync(0xffffffffu, threadIdx.x >> 5, 0);
  const int wg = warp >> 2;
  const int lane = threadIdx.x & 31;
  TL(0); TLG(1);

  const int fcol = j * BN + (warp < 7 ? warp : 0) * 32 + lane;
  const int* qp = qw + (size_t)(it * 8) * F_DIM + fcol;
  uint4* wp = g_w + (j * (NKB * 8) + it) * BN + perm32(warp * 32 + lane);
  int q[8];
  float lutv, sc;
  unsigned* flags = g_flag[j];
  const uint8_t* wsrc = reinterpret_cast<const uint8_t*>(g_w) + (size_t)j * NKB * W_STAGE;
  const int xrow = it * BM + wg * 128;

  if (warp < 7) {
    int qa[PU][8];
#pragma unroll
    for (int u = 0; u < PU; u++) load_unit(qa[u], qp + u * BK * F_DIM);
    lutv = __bfloat162float(lut[lane & 15]);
    sc = __bfloat162float(scales[fcol]);
    load_unit(q, qp + PU * BK * F_DIM);
    bar_sync(0, 256);
    if (warp == 0 && lane == 0) {
#pragma unroll
      for (int n = 0; n < XS; n++) {
        mbar_expect_tx(bars + 8 * (B_FULLX + n), X_SLICE);
        tma_load_2d(sbase + SMEM_X + n * X_SLICE, &tm_x, (n >> 1) * BK, xrow + (n & 1) * 64, bars + 8 * (B_FULLX + n));
      }
    }
#pragma unroll
    for (int u = 0; u < PU; u++) {
      wp[u * 8 * BN] = convert_unit(qa[u], lutv, sc);
      __syncwarp();
      if (lane == 0) mbar_arrive(bars + 8 * (B_DQ + u));
      TL(2 + u);
    }
  } else {
    if (lane == 0) {
#pragma unroll
      for (int s = 0; s < WS; s++) {
        mbar_init(bars + 8 * (B_FULLW + s), 1);
        mbar_init(bars + 8 * (B_EMPTYW + s), 8);
      }
#pragma unroll
      for (int s = 0; s < 2 * XS; s++) {
        mbar_init(bars + 8 * (B_FULLX + s), 1);
        mbar_init(bars + 8 * (B_EMPTYX + s), 4);
      }
#pragma unroll
      for (int s = 0; s < 16; s++) mbar_init(bars + 8 * (B_DQ + s), 7);
      asm volatile("fence.mbarrier_init.release.cluster;" ::: "memory");
      asm volatile("fence.proxy.async.shared::cta;" ::: "memory");
    }
    bar_sync(0, 256);
    if (lane == 0) {
#pragma unroll
      for (int n = 0; n < XS; n++) {
        mbar_expect_tx(bars + 8 * (B_FULLX + XS + n), X_SLICE);
        tma_load_2d(sbase + SMEM_X + (XS + n) * X_SLICE, &tm_x, (n >> 1) * BK, xrow + (n & 1) * 64,
                    bars + 8 * (B_FULLX + XS + n));
      }
    }
    for (int u = PU + 1 + (lane >> 3); u < NKB; u += 4)
      l2_prefetch(qw + (size_t)(u * BK + it * 8 + (lane & 7)) * F_DIM + j * BN, BN * 4);
    lutv = 0.f;
    sc = 0.f;
#pragma unroll
    for (int i = 0; i < 8; i++) q[i] = 0;
  }

  int next_pub = 0;
  int next_w = 0;
  unsigned ready = 0;
  int w_slot = 0;
  uint32_t w_ph = 1;

  auto publish = [&](int upto) {
    if (next_pub < upto) {
      mbar_wait(bars + 8 * (B_DQ + upto - 1), 0);
      if (lane == 0) asm volatile("fence.acq_rel.gpu;" ::: "memory");
      if (lane == 0)
        for (int u = next_pub; u < upto; u++)
          asm volatile("red.relaxed.gpu.global.add.u32 [%0], 1;" ::"l"(flags + u) : "memory");
      next_pub = upto;
    }
  };
  auto poll = [&]() {
    unsigned v = ld_acquire(flags + (lane & 15));
    ready = __ballot_sync(0xffffffffu, v >= NI);
  };
  auto issue_w = [&]() {
    mbar_wait(bars + 8 * (B_EMPTYW + w_slot), w_ph);
    if (lane == 0) {
      asm volatile("fence.proxy.async.global;" ::: "memory");
      mbar_expect_tx(bars + 8 * (B_FULLW + w_slot), W_STAGE);
      bulk_load(sbase + SMEM_W + w_slot * W_STAGE, wsrc + (size_t)next_w * W_STAGE, W_STAGE, bars + 8 * (B_FULLW + w_slot));
    }
    next_w++;
    if (++w_slot == WS) { w_slot = 0; w_ph ^= 1; }
  };
  auto load_w = [&](int must, int may) {
    int spins = 0;
    while (next_w < may) {
      if (!((ready >> next_w) & 1)) {
        if (spins > 0 && next_w >= must) break;
        poll();
        if (++spins > (1 << 22)) __trap();
        continue;
      }
      issue_w();
    }
  };

  if (warp == 7) {
    publish(1);
    TL(2);
    publish(2);
    TL(3);
    load_w(1, 1);
    TL(4);
    publish(PU);
    load_w(1, PU);
    TL(5);
  }

  float acc0[112], acc1[112];
  const uint64_t da_base = ((uint64_t)1 << 62) | ((uint64_t)(1024 >> 4) << 32) | ((uint64_t)1 << 16) |
                           (uint64_t)((sbase + SMEM_X + wg * (XS * X_SLICE)) >> 4);
  const uint64_t db_base = ((uint64_t)(128 >> 4) << 32) | ((uint64_t)(W_KC >> 4) << 16) |
                           (uint64_t)((sbase + SMEM_W) >> 4);
  const uint32_t fullx = bars + 8 * (B_FULLX + wg * XS), emptyx = bars + 8 * (B_EMPTYX + wg * XS);
  const bool x_issuer = (warp & 3) == 0;

  int xs = 0, ws = 0;
  uint32_t xph = 0, wph = 0;
  int xn = 0;
  int unit = PU;

  auto mma4 = [&](float (&acc)[112], int wslot, int first) {
    mbar_wait(fullx + 8 * xs, xph);
    const uint64_t da = da_base + (uint64_t)(xs * (X_SLICE >> 4));
    const uint64_t db = db_base + (uint64_t)(wslot * (W_STAGE >> 4));
    wgmma_fence();
#pragma unroll
    for (int k = 0; k < 4; k++) wgmma_m64n224k16(acc, da + k * 2, db + k * (2 * W_KC >> 4), (k != 0) | (first == 0));
    wgmma_commit();
  };
  auto refill_x = [&]() {
    const int n = xn - 1 + XS;
    if (xn > 0 && n < 2 * NKB) {
      const int sp = xs == 0 ? XS - 1 : xs - 1;
      if (lane == 0) mbar_arrive(emptyx + 8 * sp);
      if (x_issuer) {
        mbar_wait(emptyx + 8 * sp, xs == 0 ? xph ^ 1 : xph);
        if (lane == 0) {
          const int kb = n < 2 * NR ? (n >> 1) : NR + ((n - 2 * NR) & (ENDK - 1));
          const int half = n < 2 * NR ? (n & 1) : ((n - 2 * NR) / ENDK);
          mbar_expect_tx(fullx + 8 * sp, X_SLICE);
          tma_load_2d(sbase + SMEM_X + (wg * XS + sp) * X_SLICE, &tm_x, kb * BK, xrow + half * 64, fullx + 8 * sp);
        }
      }
    }
  };
  auto next_x = [&]() {
    xn++;
    if (++xs == XS) { xs = 0; xph ^= 1; }
  };
  auto dequant_step = [&]() {
    if (warp < 7 && unit < NKB) {
      wp[unit * 8 * BN] = convert_unit(q, lutv, sc);
      __syncwarp();
      if (lane == 0) mbar_arrive(bars + 8 * (B_DQ + unit));
      if (unit + 1 < NKB) load_unit(q, qp + (unit + 1) * BK * F_DIM);
    }
    unit++;
  };

#pragma unroll 1
  for (int r = 0; r < NR; r++) {
    if (warp == 7) load_w(r + 1, r + 1);
    mbar_wait(bars + 8 * (B_FULLW + ws), wph);
    TL(8 + 2 * r);
    mma4(acc0, ws, r == 0);
    wgmma_wait<1>();
    if (r > 0 && lane == 0) mbar_arrive(bars + 8 * (B_EMPTYW + (ws == 0 ? WS - 1 : ws - 1)));
    refill_x();
    next_x();
    if (warp == 7) publish(unit < NKB ? unit : NKB);
    dequant_step();
    TL(9 + 2 * r);
    mma4(acc1, ws, r == 0);
    wgmma_wait<1>();
    refill_x();
    next_x();
    if (warp == 7) load_w(0, r + WS < NKB ? r + WS : NKB);
    dequant_step();
    if (++ws == WS) { ws = 0; wph ^= 1; }
  }
  if (warp == 7) load_w(NKB, NKB);

  __nv_bfloat16* op = out + (size_t)(xrow + (warp & 3) * 16 + (lane >> 2)) * F_DIM + j * BN + (lane & 3) * 8;
  TL(40);
  if (wg == 1) bar_sync(1, 256);
  {
    int s = ws;
    uint32_t p = wph;
#pragma unroll 1
    for (int e = 0; e < ENDK; e++) {
      mbar_wait(bars + 8 * (B_FULLW + s), p);
      mma4(acc0, s, 0);
      if (e == ENDK - 1) bar_arrive(1 + wg, 256);
      wgmma_wait<1>();
      refill_x();
      next_x();
      if (++s == WS) { s = 0; p ^= 1; }
    }
  }
  wgmma_wait<0>();
  TL(41);
  store_acc(acc0, op);
  TL(42);
  bar_sync(2 + wg, 256);
  {
    int s = ws;
#pragma unroll 1
    for (int e = 0; e < ENDK; e++) {
      mma4(acc1, s, 0);
      next_x();
      if (++s == WS) s = 0;
    }
  }
  if (wg == 0) bar_arrive(3, 256);
  wgmma_wait<0>();
  TL(43);
  store_acc(acc1, op + 64 * F_DIM);
  TL(44);
  if (threadIdx.x == 0) {
    if (atomicAdd(flags + 16, 1u) == NI - 1) {
#pragma unroll
      for (int u = 0; u <= 16; u++) flags[u] = 0;
    }
  }
}

typedef CUresult (*EncodeTiledFn)(CUtensorMap*, CUtensorMapDataType, cuuint32_t, void*, const cuuint64_t*,
                                  const cuuint64_t*, const cuuint32_t*, const cuuint32_t*, CUtensorMapInterleave,
                                  CUtensorMapSwizzle, CUtensorMapL2promotion, CUtensorMapFloatOOBfill);

}

extern "C" void kernel_launch(void* const* d_in, const int* in_sizes, int n_in, void* d_out, int out_size) {
  const __nv_bfloat16* x = (const __nv_bfloat16*)d_in[0];
  const int* qw = (const int*)d_in[1];
  const __nv_bfloat16* lut = (const __nv_bfloat16*)d_in[2];
  const __nv_bfloat16* scales = (const __nv_bfloat16*)d_in[3];
  __nv_bfloat16* out = (__nv_bfloat16*)d_out;

  static EncodeTiledFn enc = nullptr;
  if (!enc) {
    void* fn = nullptr;
    cudaDriverEntryPointQueryResult qr;
    cudaGetDriverEntryPoint("cuTensorMapEncodeTiled", &fn, cudaEnableDefault, &qr);
    enc = (EncodeTiledFn)fn;
    cudaFuncSetAttribute(fused_kernel, cudaFuncAttributeMaxDynamicSharedMemorySize, SMEM_TOTAL);
  }
  CUtensorMap tm_x;
  cuuint64_t gdim[2] = {(cuuint64_t)D_DIM, (cuuint64_t)S_DIM};
  cuuint64_t gstr[1] = {(cuuint64_t)D_DIM * 2};
  cuuint32_t box[2] = {(cuuint32_t)BK, 64};
  cuuint32_t estr[2] = {1, 1};
  enc(&tm_x, CU_TENSOR_MAP_DATA_TYPE_BFLOAT16, 2, (void*)x, gdim, gstr, box, estr, CU_TENSOR_MAP_INTERLEAVE_NONE,
      CU_TENSOR_MAP_SWIZZLE_128B, CU_TENSOR_MAP_L2_PROMOTION_L2_256B, CU_TENSOR_MAP_FLOAT_OOB_FILL_NONE);

  fused_kernel<<<NI * NJ, 256, SMEM_TOTAL, cudaStreamPerThread>>>(tm_x, qw, lut, scales, out);
}
```

```cpp
#include <cuda_runtime.h>
#include <cuda_bf16.h>
#include <cuda.h>
#include <stdint.h>

namespace {

constexpr int S_DIM = 2048, D_DIM = 1024, F_DIM = 3584;
constexpr int BM = 256, BN = 224, BK = 64;
constexpr int NKB = D_DIM / BK;
constexpr int NJ = F_DIM / BN;
constexpr int NI = S_DIM / BM;
constexpr int WS = 5;
constexpr int XS = 5;
constexpr int ENDK = 4;
constexpr int NR = NKB - ENDK;
constexpr int X_SLICE = 64 * BK * 2;
constexpr int W_STAGE = BN * BK * 2;
constexpr int W_KC = BN * 16;

__device__ uint4 g_w[NJ * NKB * 8 * BN];
__device__ unsigned g_flag[NJ * 32];

__device__ __forceinline__ uint32_t smem_u32(const void* p) { return (uint32_t)__cvta_generic_to_shared(p); }
__device__ __forceinline__ unsigned clk32() {
  unsigned c;
  asm volatile("mov.u32 %0, %%clock;" : "=r"(c)::"memory");
  return c;
}
__device__ __forceinline__ bool elect_one() {
  uint32_t p;
  asm volatile("{\n.reg .pred P;\nelect.sync _|P, 0xffffffff;\nselp.b32 %0, 1, 0, P;\n}" : "=r"(p));
  return p != 0;
}
__device__ __forceinline__ void mbar_init(uint32_t bar, uint32_t cnt) {
  asm volatile("mbarrier.init.shared::cta.b64 [%0], %1;" ::"r"(bar), "r"(cnt) : "memory");
}
__device__ __forceinline__ void mbar_expect_tx(uint32_t bar, uint32_t bytes) {
  asm volatile("mbarrier.arrive.expect_tx.shared::cta.b64 _, [%0], %1;" ::"r"(bar), "r"(bytes) : "memory");
}
__device__ __forceinline__ void mbar_arrive(uint32_t bar) {
  asm volatile("mbarrier.arrive.shared::cta.b64 _, [%0];" ::"r"(bar) : "memory");
}
__device__ __forceinline__ bool mbar_test(uint32_t bar, uint32_t parity) {
  uint32_t ok;
  asm volatile(
      "{\n.reg .pred p;\nmbarrier.test_wait.parity.shared::cta.b64 p, [%1], %2;\nselp.b32 %0, 1, 0, p;\n}\n"
      : "=r"(ok) : "r"(bar), "r"(parity) : "memory");
  return ok != 0;
}
__device__ __forceinline__ void mbar_wait(uint32_t bar, uint32_t parity) {
  asm volatile(
      "{\n.reg .pred p;\n"
      "LAB_WAIT:\n"
      "mbarrier.try_wait.parity.shared::cta.b64 p, [%0], %1;\n"
      "@p bra LAB_DONE;\n"
      "bra LAB_WAIT;\n"
      "LAB_DONE:\n}\n" ::"r"(bar), "r"(parity) : "memory");
}
__device__ __forceinline__ void tma_load_2d(uint32_t dst, const CUtensorMap* tm, int c0, int c1, uint32_t bar) {
  asm volatile(
      "cp.async.bulk.tensor.2d.shared::cluster.global.mbarrier::complete_tx::bytes [%0], [%1, {%3, %4}], [%2];"
      ::"r"(dst), "l"(tm), "r"(bar), "r"(c0), "r"(c1) : "memory");
}
__device__ __forceinline__ void tma_prefetch_2d(const CUtensorMap* tm, int c0, int c1) {
  asm volatile("cp.async.bulk.prefetch.tensor.2d.L2.global [%0, {%1, %2}];" ::"l"(tm), "r"(c0), "r"(c1) : "memory");
}
__device__ __forceinline__ void bulk_load(uint32_t dst, const void* src, uint32_t bytes, uint32_t bar) {
  asm volatile(
      "cp.async.bulk.shared::cluster.global.mbarrier::complete_tx::bytes [%0], [%1], %2, [%3];"
      ::"r"(dst), "l"(src), "r"(bytes), "r"(bar) : "memory");
}
__device__ __forceinline__ int ldg_stream(const int* p) {
  int v;
  asm volatile("ld.global.L1::no_allocate.b32 %0, [%1];" : "=r"(v) : "l"(p) : "memory");
  return v;
}
__device__ __forceinline__ unsigned ld_strong(const void* p) {
  unsigned v;
  asm volatile("ld.relaxed.gpu.global.u32 %0, [%1];" : "=r"(v) : "l"(p) : "memory");
  return v;
}
__device__ __forceinline__ void st_strong128(void* p, uint4 v) {
  asm volatile("st.relaxed.gpu.global.v4.u32 [%0], {%1, %2, %3, %4};" ::"l"(p), "r"(v.x), "r"(v.y), "r"(v.z), "r"(v.w)
               : "memory");
}
__device__ __forceinline__ void wgmma_fence() { asm volatile("wgmma.fence.sync.aligned;" ::: "memory"); }
__device__ __forceinline__ void wgmma_commit() { asm volatile("wgmma.commit_group.sync.aligned;" ::: "memory"); }
template <int N>
__device__ __forceinline__ void wgmma_wait() { asm volatile("wgmma.wait_group.sync.aligned %0;" ::"n"(N) : "memory"); }
__device__ __forceinline__ void bar_sync(int id, int n) { asm volatile("bar.sync %0, %1;" ::"r"(id), "r"(n) : "memory"); }
__device__ __forceinline__ void bar_arrive(int id, int n) { asm volatile("bar.arrive %0, %1;" ::"r"(id), "r"(n) : "memory"); }

__device__ __forceinline__ void wgmma_m64n224k16(float (&d)[112], uint64_t da, uint64_t db, int scale_d) {
  asm volatile(
    "{\n.reg .pred p;\nsetp.ne.b32 p, %114, 0;\n"
    "wgmma.mma_async.sync.aligned.m64n224k16.f32.bf16.bf16 "
    "{%0, %1, %2, %3, %4, %5, %6, %7, %8, %9, %10, %11, %12, %13, %14, %15, "
    "%16, %17, %18, %19, %20, %21, %22, %23, %24, %25, %26, %27, %28, %29, %30, %31, "
    "%32, %33, %34, %35, %36, %37, %38, %39, %40, %41, %42, %43, %44, %45, %46, %47, "
    "%48, %49, %50, %51, %52, %53, %54, %55, %56, %57, %58, %59, %60, %61, %62, %63, "
    "%64, %65, %66, %67, %68, %69, %70, %71, %72, %73, %74, %75, %76, %77, %78, %79, "
    "%80, %81, %82, %83, %84, %85, %86, %87, %88, %89, %90, %91, %92, %93, %94, %95, "
    "%96, %97, %98, %99, %100, %101, %102, %103, %104, %105, %106, %107, %108, %109, %110, %111}, "
    "%112, %113, p, 1, 1, 0, 0;\n}\n"
    : "+f"(d[0]), "+f"(d[1]), "+f"(d[2]), "+f"(d[3]), "+f"(d[4]), "+f"(d[5]), "+f"(d[6]), "+f"(d[7]),
      "+f"(d[8]), "+f"(d[9]), "+f"(d[10]), "+f"(d[11]), "+f"(d[12]), "+f"(d[13]), "+f"(d[14]), "+f"(d[15]),
      "+f"(d[16]), "+f"(d[17]), "+f"(d[18]), "+f"(d[19]), "+f"(d[20]), "+f"(d[21]), "+f"(d[22]), "+f"(d[23]),
      "+f"(d[24]), "+f"(d[25]), "+f"(d[26]), "+f"(d[27]), "+f"(d[28]), "+f"(d[29]), "+f"(d[30]), "+f"(d[31]),
      "+f"(d[32]), "+f"(d[33]), "+f"(d[34]), "+f"(d[35]), "+f"(d[36]), "+f"(d[37]), "+f"(d[38]), "+f"(d[39]),
      "+f"(d[40]), "+f"(d[41]), "+f"(d[42]), "+f"(d[43]), "+f"(d[44]), "+f"(d[45]), "+f"(d[46]), "+f"(d[47]),
      "+f"(d[48]), "+f"(d[49]), "+f"(d[50]), "+f"(d[51]), "+f"(d[52]), "+f"(d[53]), "+f"(d[54]), "+f"(d[55]),
      "+f"(d[56]), "+f"(d[57]), "+f"(d[58]), "+f"(d[59]), "+f"(d[60]), "+f"(d[61]), "+f"(d[62]), "+f"(d[63]),
      "+f"(d[64]), "+f"(d[65]), "+f"(d[66]), "+f"(d[67]), "+f"(d[68]), "+f"(d[69]), "+f"(d[70]), "+f"(d[71]),
      "+f"(d[72]), "+f"(d[73]), "+f"(d[74]), "+f"(d[75]), "+f"(d[76]), "+f"(d[77]), "+f"(d[78]), "+f"(d[79]),
      "+f"(d[80]), "+f"(d[81]), "+f"(d[82]), "+f"(d[83]), "+f"(d[84]), "+f"(d[85]), "+f"(d[86]), "+f"(d[87]),
      "+f"(d[88]), "+f"(d[89]), "+f"(d[90]), "+f"(d[91]), "+f"(d[92]), "+f"(d[93]), "+f"(d[94]), "+f"(d[95]),
      "+f"(d[96]), "+f"(d[97]), "+f"(d[98]), "+f"(d[99]), "+f"(d[100]), "+f"(d[101]), "+f"(d[102]), "+f"(d[103]),
      "+f"(d[104]), "+f"(d[105]), "+f"(d[106]), "+f"(d[107]), "+f"(d[108]), "+f"(d[109]), "+f"(d[110]), "+f"(d[111])
    : "l"(da), "l"(db), "r"(scale_d));
}

__device__ __forceinline__ uint32_t pack_bf16(float lo, float hi) {
  uint32_t r;
  asm("cvt.rn.bf16x2.f32 %0, %1, %2;" : "=r"(r) : "f"(hi), "f"(lo));
  return r;
}

__device__ __forceinline__ int perm32(int n) { return (n & ~30) | ((n & 6) << 2) | ((n >> 2) & 6); }

constexpr int SMEM_X = 0;
constexpr int SMEM_W = 2 * XS * X_SLICE;
constexpr int SMEM_BAR = SMEM_W + WS * W_STAGE;
constexpr int B_FULLW = 0, B_EMPTYW = B_FULLW + WS, B_FULLX = B_EMPTYW + WS, B_EMPTYX = B_FULLX + 2 * XS;
constexpr int SMEM_TL = SMEM_BAR + 512;
constexpr int SMEM_TOTAL = SMEM_TL + 2048;
constexpr unsigned FLAG_FULL = NI * 7;

#define TL(i)
#define TLG(i)

__device__ __forceinline__ void store_acc(const float (&a)[112], __nv_bfloat16* p) {
#pragma unroll
  for (int J = 0; J < 7; J++) {
    uint4 v0, v1;
    v0.x = pack_bf16(a[16 * J + 0], a[16 * J + 1]);
    v0.y = pack_bf16(a[16 * J + 4], a[16 * J + 5]);
    v0.z = pack_bf16(a[16 * J + 8], a[16 * J + 9]);
    v0.w = pack_bf16(a[16 * J + 12], a[16 * J + 13]);
    v1.x = pack_bf16(a[16 * J + 2], a[16 * J + 3]);
    v1.y = pack_bf16(a[16 * J + 6], a[16 * J + 7]);
    v1.z = pack_bf16(a[16 * J + 10], a[16 * J + 11]);
    v1.w = pack_bf16(a[16 * J + 14], a[16 * J + 15]);
    *reinterpret_cast<uint4*>(p + 32 * J) = v0;
    *reinterpret_cast<uint4*>(p + 8 * F_DIM + 32 * J) = v1;
  }
}

__device__ __forceinline__ void load_unit(int (&q)[8], const int* p) {
#pragma unroll
  for (int i = 0; i < 8; i++) q[i] = ldg_stream(p + i * F_DIM);
}
__device__ __forceinline__ uint4 convert_unit(const int (&q)[8], float lutv, float sc) {
  float v[8];
#pragma unroll
  for (int i = 0; i < 8; i++) v[i] = __shfl_sync(0xffffffffu, lutv, q[i]) * sc;
  uint4 o;
  o.x = pack_bf16(v[0], v[1]);
  o.y = pack_bf16(v[2], v[3]);
  o.z = pack_bf16(v[4], v[5]);
  o.w = pack_bf16(v[6], v[7]);
  return o;
}

constexpr int PU = 3;
constexpr int PFD = 3;
#define PACE 650

__global__ void __launch_bounds__(256, 1)
fused_kernel(const __grid_constant__ CUtensorMap tm_x, const __grid_constant__ CUtensorMap tm_q,
             const int* __restrict__ qw, const __nv_bfloat16* __restrict__ lut,
             const __nv_bfloat16* __restrict__ scales, __nv_bfloat16* __restrict__ out, uint4* wscr,
             unsigned* flag_base) {
  extern __shared__ __align__(1024) uint8_t smem_raw[];
  const uint32_t sbase = smem_u32(smem_raw);
  const uint32_t bars = sbase + SMEM_BAR;
  const int j = blockIdx.x >> 3, it = blockIdx.x & 7;
  const int warp = __shfl_sync(0xffffffffu, threadIdx.x >> 5, 0);
  const int wg = warp >> 2;
  const int lane = threadIdx.x & 31;
  const unsigned t_start = clk32();
  TL(0); TLG(1);

  const int fcol = j * BN + (warp < 7 ? warp : 0) * 32 + lane;
  const int* qp = qw + (size_t)(it * 8) * F_DIM + fcol;
  uint4* wp = wscr + (j * (NKB * 8) + it) * BN + perm32(warp * 32 + lane);
  int q[8];
  float lutv, sc;
  unsigned rb;
  unsigned* flags = flag_base + j * 32;
  const uint8_t* wsrc = reinterpret_cast<const uint8_t*>(wscr) + (size_t)j * NKB * W_STAGE;
  const int xrow = it * BM + wg * 128;

  auto emit_unit = [&](const int (&qq)[8], int u) {
    st_strong128(wp + u * 8 * BN, convert_unit(qq, lutv, sc));
    rb = ld_strong(wp + u * 8 * BN);
  };
  auto publish_unit = [&](int u) {
    const unsigned inc = __all_sync(0xffffffffu, rb != 0xffffffffu) ? 1u : 0u;
    if (elect_one()) asm volatile("red.relaxed.gpu.global.add.u32 [%0], %1;" ::"l"(flags + u), "r"(inc) : "memory");
  };
  auto load_x0 = [&](int g, int n) {
    mbar_expect_tx(bars + 8 * (B_FULLX + g * XS + n), X_SLICE);
    tma_load_2d(sbase + SMEM_X + (g * XS + n) * X_SLICE, &tm_x, (n >> 1) * BK, it * BM + g * 128 + (n & 1) * 64,
                bars + 8 * (B_FULLX + g * XS + n));
  };
  auto prefetch_unit = [&](int u) {
    if (u < NKB && elect_one()) tma_prefetch_2d(&tm_q, j * BN, u * BK + it * 8);
  };

  int next_w = 0;
  unsigned ready = 0;
  int w_slot = 0;
  uint32_t w_ph = 1;

  auto issue_w = [&]() {
    mbar_wait(bars + 8 * (B_EMPTYW + w_slot), w_ph);
    if (elect_one()) {
      asm volatile("fence.proxy.async.global;" ::: "memory");
      mbar_expect_tx(bars + 8 * (B_FULLW + w_slot), W_STAGE);
      bulk_load(sbase + SMEM_W + w_slot * W_STAGE, wsrc + (size_t)next_w * W_STAGE, W_STAGE, bars + 8 * (B_FULLW + w_slot));
    }
    next_w++;
    if (++w_slot == WS) { w_slot = 0; w_ph ^= 1; }
  };
  auto load_w_must = [&](int must) {
    int spins = 0;
    while (next_w < must) {
      if (!((ready >> next_w) & 1)) {
        ready = __ballot_sync(0xffffffffu, ld_strong(flags + (lane & 15)) >= FLAG_FULL);
        if (++spins > (1 << 22)) __trap();
        continue;
      }
      issue_w();
    }
  };
  auto load_w_may = [&](int may) {
    if (next_w < NKB) {
      ready |= __ballot_sync(0xffffffffu, rb >= FLAG_FULL);
      while (next_w < may && ((ready >> next_w) & 1)) issue_w();
      rb = ld_strong(flags + (lane & 15));
    }
  };

  if (warp < 7) {
    int qa[8], qb[8];
    load_unit(qa, qp);
    lutv = __bfloat162float(lut[lane & 15]);
    sc = __bfloat162float(scales[fcol]);
    while (clk32() - t_start < PACE) {}
    load_unit(qb, qp + 1 * BK * F_DIM);
    emit_unit(qa, 0);
    load_unit(qa, qp + 2 * BK * F_DIM);
    TL(2);
    publish_unit(0);
    TL(3);
    emit_unit(qb, 1);
    load_unit(q, qp + 3 * BK * F_DIM);
    publish_unit(1);
    TL(4);
    emit_unit(qa, 2);
    publish_unit(2);
    TL(5);
    bar_sync(0, 256);
  } else {
    if (elect_one()) {
#pragma unroll
      for (int s = 0; s < WS; s++) {
        mbar_init(bars + 8 * (B_FULLW + s), 1);
        mbar_init(bars + 8 * (B_EMPTYW + s), 8);
      }
#pragma unroll
      for (int s = 0; s < 2 * XS; s++) {
        mbar_init(bars + 8 * (B_FULLX + s), 1);
        mbar_init(bars + 8 * (B_EMPTYX + s), 4);
      }
      asm volatile("fence.mbarrier_init.release.cluster;" ::: "memory");
      asm volatile("fence.proxy.async.shared::cta;" ::: "memory");
      load_x0(0, 0); load_x0(0, 1); load_x0(1, 0); load_x0(1, 1);
    }
    bar_arrive(0, 256);
    lutv = 0.f;
    sc = 0.f;
#pragma unroll
    for (int i = 0; i < 8; i++) q[i] = 0;
    while (clk32() - t_start < 2 * PACE) {}
    if (elect_one()) {
      load_x0(0, 2); load_x0(0, 3); load_x0(1, 2); load_x0(1, 3); load_x0(0, 4); load_x0(1, 4);
    }
    load_w_must(1);
    TL(2);
    prefetch_unit(PU + 1);
    rb = 0;
    do {
      load_w_may(PU);
    } while (next_w < 2 && !mbar_test(bars + 8 * B_FULLW, 0));
    TL(3);
    prefetch_unit(PU + 2);
  }

  float acc0[112], acc1[112];
  const uint64_t da_base = ((uint64_t)1 << 62) | ((uint64_t)(1024 >> 4) << 32) | ((uint64_t)1 << 16) |
                           (uint64_t)((sbase + SMEM_X + wg * (XS * X_SLICE)) >> 4);
  const uint64_t db_base = ((uint64_t)(128 >> 4) << 32) | ((uint64_t)(W_KC >> 4) << 16) |
                           (uint64_t)((sbase + SMEM_W) >> 4);
  const uint32_t fullx = bars + 8 * (B_FULLX + wg * XS), emptyx = bars + 8 * (B_EMPTYX + wg * XS);
  const bool x_issuer = (warp & 3) == 3;

  int xs = 0, ws = 0;
  uint32_t xph = 0, wph = 0;
  int xn = 0;
  int unit = PU;

  auto mma4 = [&](float (&acc)[112], int wslot, int first) {
    mbar_wait(fullx + 8 * xs, xph);
    const uint64_t da = da_base + (uint64_t)(xs * (X_SLICE >> 4));
    const uint64_t db = db_base + (uint64_t)(wslot * (W_STAGE >> 4));
    wgmma_fence();
#pragma unroll
    for (int k = 0; k < 4; k++) wgmma_m64n224k16(acc, da + k * 2, db + k * (2 * W_KC >> 4), (k != 0) | (first == 0));
    wgmma_commit();
  };
  auto refill_x = [&]() {
    const int n = xn - 1 + XS;
    if (xn > 0 && n < 2 * NKB) {
      const int sp = xs == 0 ? XS - 1 : xs - 1;
      if (elect_one()) mbar_arrive(emptyx + 8 * sp);
      if (x_issuer) {
        mbar_wait(emptyx + 8 * sp, xs == 0 ? xph ^ 1 : xph);
        if (elect_one()) {
          const int kb = n < 2 * NR ? (n >> 1) : NR + ((n - 2 * NR) & (ENDK - 1));
          const int half = n < 2 * NR ? (n & 1) : ((n - 2 * NR) / ENDK);
          mbar_expect_tx(fullx + 8 * sp, X_SLICE);
          tma_load_2d(sbase + SMEM_X + (wg * XS + sp) * X_SLICE, &tm_x, kb * BK, xrow + half * 64, fullx + 8 * sp);
        }
      }
    }
  };
  auto next_x = [&]() {
    xn++;
    if (++xs == XS) { xs = 0; xph ^= 1; }
  };
  auto dequant_step = [&]() {
    if (warp < 7) {
      if (unit > PU && unit <= NKB) publish_unit(unit - 1);
      if (unit < NKB) {
        emit_unit(q, unit);
        if (unit + 1 < NKB) load_unit(q, qp + (unit + 1) * BK * F_DIM);
      }
    } else {
      prefetch_unit(unit + PFD);
    }
    unit++;
  };

#pragma unroll 1
  for (int r = 0; r < NR; r++) {
    if (warp == 7) load_w_must(r + 1);
    mbar_wait(bars + 8 * (B_FULLW + ws), wph);
    TL(8 + 2 * r);
    mma4(acc0, ws, r == 0);
    dequant_step();
    wgmma_wait<1>();
    if (r > 0 && elect_one()) mbar_arrive(bars + 8 * (B_EMPTYW + (ws == 0 ? WS - 1 : ws - 1)));
    refill_x();
    next_x();
    if (warp == 7) load_w_may(r + WS - 1);
    TL(9 + 2 * r);
    mma4(acc1, ws, r == 0);
    dequant_step();
    wgmma_wait<1>();
    refill_x();
    next_x();
    if (warp == 7) load_w_may(r + WS);
    if (++ws == WS) { ws = 0; wph ^= 1; }
  }
  if (warp == 7) load_w_must(NKB);

  __nv_bfloat16* op = out + (size_t)(xrow + (warp & 3) * 16 + (lane >> 2)) * F_DIM + j * BN + (lane & 3) * 8;
  TL(40);
  if (wg == 1) bar_sync(1, 256);
  {
    int s = ws;
    uint32_t p = wph;
#pragma unroll 1
    for (int e = 0; e < ENDK; e++) {
      mbar_wait(bars + 8 * (B_FULLW + s), p);
      mma4(acc0, s, 0);
      if (e == ENDK - 1) bar_arrive(1 + wg, 256);
      wgmma_wait<1>();
      refill_x();
      next_x();
      if (++s == WS) { s = 0; p ^= 1; }
    }
  }
  wgmma_wait<0>();
  TL(41);
  store_acc(acc0, op);
  TL(42);
  bar_sync(2 + wg, 256);
  {
    int s = ws;
#pragma unroll 1
    for (int e = 0; e < ENDK; e++) {
      mma4(acc1, s, 0);
      next_x();
      if (++s == WS) s = 0;
    }
  }
  if (wg == 0) bar_arrive(3, 256);
  wgmma_wait<0>();
  TL(43);
  store_acc(acc1, op + 64 * F_DIM);
  TL(44);
  if (threadIdx.x == 0) {
    if (atomicAdd(flags + 16, 1u) == NI - 1) {
#pragma unroll
      for (int u = 0; u <= 16; u++) flags[u] = 0;
    }
  }
}

typedef CUresult (*EncodeTiledFn)(CUtensorMap*, CUtensorMapDataType, cuuint32_t, void*, const cuuint64_t*,
                                  const cuuint64_t*, const cuuint32_t*, const cuuint32_t*, CUtensorMapInterleave,
                                  CUtensorMapSwizzle, CUtensorMapL2promotion, CUtensorMapFloatOOBfill);

}

extern "C" void kernel_launch(void* const* d_in, const int* in_sizes, int n_in, void* d_out, int out_size) {
  const __nv_bfloat16* x = (const __nv_bfloat16*)d_in[0];
  const int* qw = (const int*)d_in[1];
  const __nv_bfloat16* lut = (const __nv_bfloat16*)d_in[2];
  const __nv_bfloat16* scales = (const __nv_bfloat16*)d_in[3];
  __nv_bfloat16* out = (__nv_bfloat16*)d_out;

  static EncodeTiledFn enc = nullptr;
  static void* p_w = nullptr;
  static void* p_flag = nullptr;
  if (!enc) {
    void* fn = nullptr;
    cudaDriverEntryPointQueryResult qr;
    cudaGetDriverEntryPoint("cuTensorMapEncodeTiled", &fn, cudaEnableDefault, &qr);
    enc = (EncodeTiledFn)fn;
    cudaGetSymbolAddress(&p_w, g_w);
    cudaGetSymbolAddress(&p_flag, g_flag);
    cudaFuncSetAttribute(fused_kernel, cudaFuncAttributeMaxDynamicSharedMemorySize, SMEM_TOTAL);
  }
  CUtensorMap tm_x, tm_q;
  cuuint32_t estr[2] = {1, 1};
  {
    cuuint64_t gdim[2] = {(cuuint64_t)D_DIM, (cuuint64_t)S_DIM};
    cuuint64_t gstr[1] = {(cuuint64_t)D_DIM * 2};
    cuuint32_t box[2] = {(cuuint32_t)BK, 64};
    enc(&tm_x, CU_TENSOR_MAP_DATA_TYPE_BFLOAT16, 2, (void*)x, gdim, gstr, box, estr, CU_TENSOR_MAP_INTERLEAVE_NONE,
        CU_TENSOR_MAP_SWIZZLE_128B, CU_TENSOR_MAP_L2_PROMOTION_L2_256B, CU_TENSOR_MAP_FLOAT_OOB_FILL_NONE);
  }
  {
    cuuint64_t gdim[2] = {(cuuint64_t)F_DIM, (cuuint64_t)D_DIM};
    cuuint64_t gstr[1] = {(cuuint64_t)F_DIM * 4};
    cuuint32_t box[2] = {(cuuint32_t)BN, 8};
    enc(&tm_q, CU_TENSOR_MAP_DATA_TYPE_INT32, 2, (void*)qw, gdim, gstr, box, estr, CU_TENSOR_MAP_INTERLEAVE_NONE,
        CU_TENSOR_MAP_SWIZZLE_NONE, CU_TENSOR_MAP_L2_PROMOTION_NONE, CU_TENSOR_MAP_FLOAT_OOB_FILL_NONE);
  }
  fused_kernel<<<NI * NJ, 256, SMEM_TOTAL, cudaStreamPerThread>>>(tm_x, tm_q, qw, lut, scales, out, (uint4*)p_w,
                                                                  (unsigned*)p_flag);
}
```

```cpp
#include <cuda_runtime.h>
#include <cuda_bf16.h>
#include <cuda.h>
#include <stdint.h>

namespace {

constexpr int S_DIM = 2048, D_DIM = 1024, F_DIM = 3584;
constexpr int BM = 256, BN = 224, BK = 64;
constexpr int NKB = D_DIM / BK;
constexpr int NJ = F_DIM / BN;
constexpr int NI = S_DIM / BM;
constexpr int WS = 4;
constexpr int XS = 5;
constexpr int ENDK = 4;
constexpr int NR = NKB - ENDK;
constexpr int X_SLICE = 64 * BK * 2;
constexpr int W_STAGE = BN * BK * 2;
constexpr int W_KC = BN * 16;

__device__ uint4 g_w[NJ * NKB * 8 * BN];
__device__ unsigned g_flag[NJ * 32];

__device__ __forceinline__ uint32_t smem_u32(const void* p) { return (uint32_t)__cvta_generic_to_shared(p); }
__device__ __forceinline__ unsigned clk32() {
  unsigned c;
  asm volatile("mov.u32 %0, %%clock;" : "=r"(c)::"memory");
  return c;
}
__device__ __forceinline__ bool elect_one() {
  uint32_t p;
  asm volatile("{\n.reg .pred P;\nelect.sync _|P, 0xffffffff;\nselp.b32 %0, 1, 0, P;\n}" : "=r"(p));
  return p != 0;
}
__device__ __forceinline__ void mbar_init(uint32_t bar, uint32_t cnt) {
  asm volatile("mbarrier.init.shared::cta.b64 [%0], %1;" ::"r"(bar), "r"(cnt) : "memory");
}
__device__ __forceinline__ void mbar_expect_tx(uint32_t bar, uint32_t bytes) {
  asm volatile("mbarrier.arrive.expect_tx.shared::cta.b64 _, [%0], %1;" ::"r"(bar), "r"(bytes) : "memory");
}
__device__ __forceinline__ void mbar_arrive(uint32_t bar) {
  asm volatile("mbarrier.arrive.shared::cta.b64 _, [%0];" ::"r"(bar) : "memory");
}
__device__ __forceinline__ bool mbar_test(uint32_t bar, uint32_t parity) {
  uint32_t ok;
  asm volatile(
      "{\n.reg .pred p;\nmbarrier.test_wait.parity.shared::cta.b64 p, [%1], %2;\nselp.b32 %0, 1, 0, p;\n}\n"
      : "=r"(ok) : "r"(bar), "r"(parity) : "memory");
  return ok != 0;
}
__device__ __forceinline__ void mbar_wait(uint32_t bar, uint32_t parity) {
  asm volatile(
      "{\n.reg .pred p;\n"
      "LAB_WAIT:\n"
      "mbarrier.try_wait.parity.shared::cta.b64 p, [%0], %1;\n"
      "@p bra LAB_DONE;\n"
      "bra LAB_WAIT;\n"
      "LAB_DONE:\n}\n" ::"r"(bar), "r"(parity) : "memory");
}
__device__ __forceinline__ void tma_load_2d(uint32_t dst, const CUtensorMap* tm, int c0, int c1, uint32_t bar) {
  asm volatile(
      "cp.async.bulk.tensor.2d.shared::cluster.global.mbarrier::complete_tx::bytes [%0], [%1, {%3, %4}], [%2];"
      ::"r"(dst), "l"(tm), "r"(bar), "r"(c0), "r"(c1) : "memory");
}
__device__ __forceinline__ void bulk_load(uint32_t dst, const void* src, uint32_t bytes, uint32_t bar) {
  asm volatile(
      "cp.async.bulk.shared::cluster.global.mbarrier::complete_tx::bytes [%0], [%1], %2, [%3];"
      ::"r"(dst), "l"(src), "r"(bytes), "r"(bar) : "memory");
}
__device__ __forceinline__ int ldg_stream(const int* p) {
  int v;
  asm volatile("ld.global.L1::no_allocate.b32 %0, [%1];" : "=r"(v) : "l"(p) : "memory");
  return v;
}
__device__ __forceinline__ int lds32(uint32_t addr) {
  int v;
  asm volatile("ld.shared.b32 %0, [%1];" : "=r"(v) : "r"(addr) : "memory");
  return v;
}
__device__ __forceinline__ uint64_t make_desc(uint32_t lo, uint32_t hi) {
  uint64_t d;
  asm("mov.b64 %0, {%1, %2};" : "=l"(d) : "r"(lo), "r"(hi));
  return d;
}
__device__ __forceinline__ unsigned ld_strong(const void* p) {
  unsigned v;
  asm volatile("ld.relaxed.gpu.global.u32 %0, [%1];" : "=r"(v) : "l"(p) : "memory");
  return v;
}
__device__ __forceinline__ void st_strong128(void* p, uint4 v) {
  asm volatile("st.relaxed.gpu.global.v4.u32 [%0], {%1, %2, %3, %4};" ::"l"(p), "r"(v.x), "r"(v.y), "r"(v.z), "r"(v.w)
               : "memory");
}
__device__ __forceinline__ void wgmma_fence() { asm volatile("wgmma.fence.sync.aligned;" ::: "memory"); }
__device__ __forceinline__ void wgmma_commit() { asm volatile("wgmma.commit_group.sync.aligned;" ::: "memory"); }
template <int N>
__device__ __forceinline__ void wgmma_wait() { asm volatile("wgmma.wait_group.sync.aligned %0;" ::"n"(N) : "memory"); }
__device__ __forceinline__ void bar_sync(int id, int n) { asm volatile("bar.sync %0, %1;" ::"r"(id), "r"(n) : "memory"); }
__device__ __forceinline__ void bar_arrive(int id, int n) { asm volatile("bar.arrive %0, %1;" ::"r"(id), "r"(n) : "memory"); }

__device__ __forceinline__ void wgmma_m64n224k16(float (&d)[112], uint64_t da, uint64_t db, int scale_d) {
  asm volatile(
    "{\n.reg .pred p;\nsetp.ne.b32 p, %114, 0;\n"
    "wgmma.mma_async.sync.aligned.m64n224k16.f32.bf16.bf16 "
    "{%0, %1, %2, %3, %4, %5, %6, %7, %8, %9, %10, %11, %12, %13, %14, %15, "
    "%16, %17, %18, %19, %20, %21, %22, %23, %24, %25, %26, %27, %28, %29, %30, %31, "
    "%32, %33, %34, %35, %36, %37, %38, %39, %40, %41, %42, %43, %44, %45, %46, %47, "
    "%48, %49, %50, %51, %52, %53, %54, %55, %56, %57, %58, %59, %60, %61, %62, %63, "
    "%64, %65, %66, %67, %68, %69, %70, %71, %72, %73, %74, %75, %76, %77, %78, %79, "
    "%80, %81, %82, %83, %84, %85, %86, %87, %88, %89, %90, %91, %92, %93, %94, %95, "
    "%96, %97, %98, %99, %100, %101, %102, %103, %104, %105, %106, %107, %108, %109, %110, %111}, "
    "%112, %113, p, 1, 1, 0, 0;\n}\n"
    : "+f"(d[0]), "+f"(d[1]), "+f"(d[2]), "+f"(d[3]), "+f"(d[4]), "+f"(d[5]), "+f"(d[6]), "+f"(d[7]),
      "+f"(d[8]), "+f"(d[9]), "+f"(d[10]), "+f"(d[11]), "+f"(d[12]), "+f"(d[13]), "+f"(d[14]), "+f"(d[15]),
      "+f"(d[16]), "+f"(d[17]), "+f"(d[18]), "+f"(d[19]), "+f"(d[20]), "+f"(d[21]), "+f"(d[22]), "+f"(d[23]),
      "+f"(d[24]), "+f"(d[25]), "+f"(d[26]), "+f"(d[27]), "+f"(d[28]), "+f"(d[29]), "+f"(d[30]), "+f"(d[31]),
      "+f"(d[32]), "+f"(d[33]), "+f"(d[34]), "+f"(d[35]), "+f"(d[36]), "+f"(d[37]), "+f"(d[38]), "+f"(d[39]),
      "+f"(d[40]), "+f"(d[41]), "+f"(d[42]), "+f"(d[43]), "+f"(d[44]), "+f"(d[45]), "+f"(d[46]), "+f"(d[47]),
      "+f"(d[48]), "+f"(d[49]), "+f"(d[50]), "+f"(d[51]), "+f"(d[52]), "+f"(d[53]), "+f"(d[54]), "+f"(d[55]),
      "+f"(d[56]), "+f"(d[57]), "+f"(d[58]), "+f"(d[59]), "+f"(d[60]), "+f"(d[61]), "+f"(d[62]), "+f"(d[63]),
      "+f"(d[64]), "+f"(d[65]), "+f"(d[66]), "+f"(d[67]), "+f"(d[68]), "+f"(d[69]), "+f"(d[70]), "+f"(d[71]),
      "+f"(d[72]), "+f"(d[73]), "+f"(d[74]), "+f"(d[75]), "+f"(d[76]), "+f"(d[77]), "+f"(d[78]), "+f"(d[79]),
      "+f"(d[80]), "+f"(d[81]), "+f"(d[82]), "+f"(d[83]), "+f"(d[84]), "+f"(d[85]), "+f"(d[86]), "+f"(d[87]),
      "+f"(d[88]), "+f"(d[89]), "+f"(d[90]), "+f"(d[91]), "+f"(d[92]), "+f"(d[93]), "+f"(d[94]), "+f"(d[95]),
      "+f"(d[96]), "+f"(d[97]), "+f"(d[98]), "+f"(d[99]), "+f"(d[100]), "+f"(d[101]), "+f"(d[102]), "+f"(d[103]),
      "+f"(d[104]), "+f"(d[105]), "+f"(d[106]), "+f"(d[107]), "+f"(d[108]), "+f"(d[109]), "+f"(d[110]), "+f"(d[111])
    : "l"(da), "l"(db), "r"(scale_d));
}

__device__ __forceinline__ uint32_t pack_bf16(float lo, float hi) {
  uint32_t r;
  asm("cvt.rn.bf16x2.f32 %0, %1, %2;" : "=r"(r) : "f"(hi), "f"(lo));
  return r;
}

__device__ __forceinline__ int perm32(int n) { return (n & ~30) | ((n & 6) << 2) | ((n >> 2) & 6); }

constexpr int SMEM_X = 0;
constexpr int SMEM_W = 2 * XS * X_SLICE;
constexpr int SMEM_Q = SMEM_W + WS * W_STAGE;
constexpr int Q_UNIT = 8 * BN * 4;
constexpr int SMEM_BAR = SMEM_Q + W_STAGE;
constexpr int B_FULLW = 0, B_FULLQ = 16, B_FULLX = 32, B_DONE = 96, B_COUNT = 160;
constexpr int SMEM_TL = SMEM_BAR + B_COUNT * 8;
constexpr int SMEM_TOTAL = SMEM_TL + 2048;
constexpr unsigned FLAG_FULL = NI * 7;

#define TL(i)
#define TLG(i)

__device__ __forceinline__ void store_acc(const float (&a)[112], __nv_bfloat16* p) {
#pragma unroll
  for (int J = 0; J < 7; J++) {
    uint4 v0, v1;
    v0.x = pack_bf16(a[16 * J + 0], a[16 * J + 1]);
    v0.y = pack_bf16(a[16 * J + 4], a[16 * J + 5]);
    v0.z = pack_bf16(a[16 * J + 8], a[16 * J + 9]);
    v0.w = pack_bf16(a[16 * J + 12], a[16 * J + 13]);
    v1.x = pack_bf16(a[16 * J + 2], a[16 * J + 3]);
    v1.y = pack_bf16(a[16 * J + 6], a[16 * J + 7]);
    v1.z = pack_bf16(a[16 * J + 10], a[16 * J + 11]);
    v1.w = pack_bf16(a[16 * J + 14], a[16 * J + 15]);
    *reinterpret_cast<uint4*>(p + 32 * J) = v0;
    *reinterpret_cast<uint4*>(p + 8 * F_DIM + 32 * J) = v1;
  }
}

__device__ __forceinline__ void load_unit(int (&q)[8], const int* p) {
#pragma unroll
  for (int i = 0; i < 8; i++) q[i] = ldg_stream(p + i * F_DIM);
}
__device__ __forceinline__ uint4 convert_unit(const int (&q)[8], float lutv, float sc) {
  float v[8];
#pragma unroll
  for (int i = 0; i < 8; i++) v[i] = __shfl_sync(0xffffffffu, lutv, q[i]) * sc;
  uint4 o;
  o.x = pack_bf16(v[0], v[1]);
  o.y = pack_bf16(v[2], v[3]);
  o.z = pack_bf16(v[4], v[5]);
  o.w = pack_bf16(v[6], v[7]);
  return o;
}

constexpr int PU = 3;
constexpr int R1 = 7;
#define PACE 650

__global__ void __launch_bounds__(256, 1)
fused_kernel(const __grid_constant__ CUtensorMap tm_x, const __grid_constant__ CUtensorMap tm_q,
             const int* __restrict__ qw, const __nv_bfloat16* __restrict__ lut,
             const __nv_bfloat16* __restrict__ scales, __nv_bfloat16* __restrict__ out, uint4* wscr,
             unsigned* flag_base) {
  extern __shared__ __align__(1024) uint8_t smem_raw[];
  const uint32_t sbase = __shfl_sync(0xffffffffu, smem_u32(smem_raw), 0);
  const uint32_t bars = sbase + SMEM_BAR;
  const int j = blockIdx.x >> 3, it = blockIdx.x & 7;
  const int warp = __shfl_sync(0xffffffffu, threadIdx.x >> 5, 0);
  const int wg = warp >> 2;
  const int lane = threadIdx.x & 31;
  const unsigned t_start = clk32();
  TL(0); TLG(1);

  uint4* wp = wscr + (j * (NKB * 8) + it) * BN + perm32(warp * 32 + lane);
  float lutv, sc;
  unsigned rb;
  unsigned* flags = flag_base + j * 32;
  const uint8_t* wsrc = reinterpret_cast<const uint8_t*>(wscr) + (size_t)j * NKB * W_STAGE;
  const int xrow = it * BM + wg * 128;

  auto emit_unit = [&](const int (&qq)[8]) {
    st_strong128(wp, convert_unit(qq, lutv, sc));
    rb = ld_strong(wp);
    wp += 8 * BN;
  };
  auto publish_unit = [&](int u) {
    const unsigned inc = __all_sync(0xffffffffu, rb != 0xffffffffu) ? 1u : 0u;
    asm volatile(
        "{\n.reg .pred P;\nelect.sync _|P, 0xffffffff;\n@P red.relaxed.gpu.global.add.u32 [%0], %1;\n}"
        ::"l"(flags + u), "r"(inc) : "memory");
  };
  auto load_x = [&](int g, int n, int slot, int kb, int half) {
    mbar_expect_tx(bars + 8 * (B_FULLX + g * 32 + n), X_SLICE);
    tma_load_2d(sbase + SMEM_X + (g * XS + slot) * X_SLICE, &tm_x, kb * BK, it * BM + g * 128 + half * 64,
                bars + 8 * (B_FULLX + g * 32 + n));
  };
  auto load_q = [&](int u) {
    mbar_expect_tx(bars + 8 * (B_FULLQ + u), Q_UNIT);
    tma_load_2d(sbase + SMEM_Q + (u & 3) * Q_UNIT, &tm_q, j * BN, u * BK + it * 8, bars + 8 * (B_FULLQ + u));
  };

  int next_w = 0;
  unsigned ready = 0;
  auto issue_w = [&](int kb, int slot) {
    if (elect_one()) {
      asm volatile("fence.proxy.async.global;" ::: "memory");
      mbar_expect_tx(bars + 8 * (B_FULLW + kb), W_STAGE);
      bulk_load(sbase + SMEM_W + slot * W_STAGE, wsrc + (size_t)kb * W_STAGE, W_STAGE, bars + 8 * (B_FULLW + kb));
    }
  };
  auto wait_ready = [&](int kb) {
    int spins = 0;
    while (!((ready >> kb) & 1)) {
      ready = __ballot_sync(0xffffffffu, ld_strong(flags + (lane & 15)) >= FLAG_FULL);
      if (++spins > (1 << 22)) __trap();
    }
  };
  auto load_w_must = [&](int must) {
    while (next_w < must) {
      wait_ready(next_w);
      issue_w(next_w, next_w & 3);
      next_w++;
    }
  };
  auto load_w_may = [&](int may) {
    ready |= __ballot_sync(0xffffffffu, rb >= FLAG_FULL);
    if (next_w < may && ((ready >> next_w) & 1)) {
      issue_w(next_w, next_w & 3);
      next_w++;
    }
    rb = ld_strong(flags + (lane & 15));
  };

  const uint32_t qaddr = sbase + SMEM_Q + threadIdx.x * 4;
  auto lds_unit = [&](int (&q)[8], int u) {
    mbar_wait(bars + 8 * (B_FULLQ + u), 0);
#pragma unroll
    for (int i = 0; i < 8; i++) q[i] = lds32(qaddr + (u & 3) * Q_UNIT + i * (BN * 4));
  };
  auto arrive_one = [&](uint32_t bar) {
    asm volatile("{\n.reg .pred P;\nelect.sync _|P, 0xffffffff;\n@P mbarrier.arrive.shared::cta.b64 _, [%0];\n}"
                 ::"r"(bar) : "memory");
  };
  {
    int q[8];
    const int fcol = j * BN + (warp < 7 ? warp : 0) * 32 + lane;
    if (warp < 7) load_unit(q, qw + (size_t)(it * 8) * F_DIM + fcol);
    lutv = __bfloat162float(lut[lane & 15]);
    sc = __bfloat162float(scales[fcol]);
    if (elect_one()) {
#pragma unroll
      for (int i = 0; i < 12; i++) mbar_init(bars + 8 * (warp * 12 + i), 1);
#pragma unroll
      for (int i = 0; i < 8; i++) mbar_init(bars + 8 * (B_DONE + warp * 8 + i), 4);
      asm volatile("fence.mbarrier_init.release.cluster;" ::: "memory");
    }
    bar_sync(0, 256);
    if (warp < 7) {
      emit_unit(q);
      TL(2);
      publish_unit(0);
      TL(3);
      lds_unit(q, 1);
      emit_unit(q);
      arrive_one(bars + 8 * (B_DONE + wg * 32 + 30));
      publish_unit(1);
      TL(4);
      lds_unit(q, 2);
      emit_unit(q);
      TL(5);
    } else {
      if (elect_one()) {
        load_x(0, 0, 0, 0, 0); load_x(0, 1, 1, 0, 1); load_x(1, 0, 0, 0, 0); load_x(1, 1, 1, 0, 1);
      }
      arrive_one(bars + 8 * (B_DONE + 32 + 30));
      while (clk32() - t_start < PACE) {}
      if (elect_one()) load_q(1);
      while (clk32() - t_start < 2 * PACE) {}
      if (elect_one()) load_q(2);
      while (clk32() - t_start < 3 * PACE) {}
      if (elect_one()) load_q(3);
      load_w_must(1);
      TL(2);
      if (elect_one()) {
        load_q(4);
        load_x(0, 2, 2, 1, 0); load_x(0, 3, 3, 1, 1); load_x(1, 2, 2, 1, 0); load_x(1, 3, 3, 1, 1);
      }
      rb = 0;
      do {
        load_w_may(PU);
      } while (next_w < 2 && !mbar_test(bars + 8 * B_FULLW, 0));
      TL(3);
      mbar_wait(bars + 8 * (B_DONE + 30), 0);
      mbar_wait(bars + 8 * (B_DONE + 32 + 30), 0);
      if (elect_one()) {
        load_q(5);
        load_x(0, 4, 4, 2, 0); load_x(1, 4, 4, 2, 0);
      }
    }
    arrive_one(bars + 8 * (B_DONE + wg * 32 + 31));
  }

  float acc0[112], acc1[112];
  constexpr uint32_t DA_HI = (1u << 30) | (1024 >> 4), DB_HI = (128 >> 4);
  const uint32_t da0 = (1u << 16) | ((sbase + SMEM_X + wg * (XS * X_SLICE)) >> 4);
  const uint32_t db0 = ((W_KC >> 4) << 16) | ((sbase + SMEM_W) >> 4);
  const uint32_t fullx = bars + 8 * (B_FULLX + wg * 32), done = bars + 8 * (B_DONE + wg * 32);
  const bool x_issuer = (warp & 3) == 3;

  int xs = 0, xp = 0;

  auto mma4 = [&](float (&acc)[112], int n, int wslot, int accum) {
    mbar_wait(fullx + 8 * n, 0);
    const uint32_t da = da0 + xs * (X_SLICE >> 4);
    const uint32_t db = db0 + wslot * (W_STAGE >> 4);
    wgmma_fence();
#pragma unroll
    for (int k = 0; k < 4; k++)
      wgmma_m64n224k16(acc, make_desc(da + k * 2, DA_HI), make_desc(db + k * (2 * W_KC >> 4), DB_HI), k != 0 || accum);
    wgmma_commit();
  };
  auto end_slot = [&](int n, int kb, int half) {
    wgmma_wait<1>();
    arrive_one(done + 8 * n);
    if (x_issuer) {
      mbar_wait(done + 8 * n, 0);
      if (n > 0 && elect_one()) load_x(wg, n + 4, xp, kb, half);
    }
    xp = xs;
    xs = xs == XS - 1 ? 0 : xs + 1;
  };
  auto dequant_slot = [&](int n) {
    if (warp < 7) {
      const int u = n + PU;
      if (u < NKB) {
        int q[8];
        lds_unit(q, u);
        publish_unit(u - 1);
        emit_unit(q);
      } else {
        publish_unit(u - 1);
      }
    }
  };
  auto loader_slot = [&](int n) {
    if (warp == 7) {
      mbar_wait(bars + 8 * (B_DONE + ((n - 1) & 31)), 0);
      if (n + 6 < NKB && elect_one()) load_q(n + 6);
      load_w_may(((n - 1) >> 1) + 4);
    }
  };

#pragma unroll 1
  for (int r = 0; r < R1; r++) {
    if (warp == 7) load_w_must(r + 1);
    mbar_wait(bars + 8 * (B_FULLW + r), 0);
    TL(8 + 2 * r);
    mma4(acc0, 2 * r, r & 3, r);
    dequant_slot(2 * r);
    end_slot(2 * r, r + 2, 0);
    loader_slot(2 * r);
    TL(9 + 2 * r);
    mma4(acc1, 2 * r + 1, r & 3, r);
    dequant_slot(2 * r + 1);
    end_slot(2 * r + 1, r + 2, 1);
    loader_slot(2 * r + 1);
  }
#pragma unroll 1
  for (int r = R1; r < NR; r++) {
    if (warp == 7) load_w_must(r + 1);
    mbar_wait(bars + 8 * (B_FULLW + r), 0);
    TL(8 + 2 * r);
    mma4(acc0, 2 * r, r & 3, 1);
    end_slot(2 * r, r == NR - 1 ? 15 : r + 2, 0);
    if (warp == 7 && r == R1 + 1) {
      wait_ready(15);
      issue_w(15, 4);
    }
    TL(9 + 2 * r);
    mma4(acc1, 2 * r + 1, r & 3, 1);
    end_slot(2 * r + 1, r >= NR - 2 ? r + 3 : r + 2, r >= NR - 2 ? 0 : 1);
    if (warp == 7) {
      mbar_wait(bars + 8 * (B_DONE + 2 * r), 0);
      load_w_must(r + 4);
    }
  }

  __nv_bfloat16* op = out + (size_t)(xrow + (warp & 3) * 16 + (lane >> 2)) * F_DIM + j * BN + (lane & 3) * 8;
  TL(40);
  if (wg == 1) bar_sync(1, 256);
#pragma unroll
  for (int e = 0; e < ENDK; e++) {
    const int kb = e < 2 ? NR + e : NR + 5 - e;
    mbar_wait(bars + 8 * (B_FULLW + kb), 0);
    mma4(acc0, 2 * NR + e, kb == 15 ? 4 : (kb & 3), 1);
    if (e == ENDK - 1) bar_arrive(1 + wg, 256);
    end_slot(2 * NR + e, kb, 1);
  }
  wgmma_wait<0>();
  TL(41);
  store_acc(acc0, op);
  TL(42);
  bar_sync(2 + wg, 256);
#pragma unroll
  for (int e = 0; e < ENDK; e++) {
    const int kb = e < 2 ? NR + e : NR + 5 - e;
    mma4(acc1, 2 * NR + ENDK + e, kb == 15 ? 4 : (kb & 3), 1);
    xs = xs == XS - 1 ? 0 : xs + 1;
  }
  if (wg == 0) bar_arrive(3, 256);
  wgmma_wait<0>();
  TL(43);
  store_acc(acc1, op + 64 * F_DIM);
  TL(44);
  if (threadIdx.x == 0) {
    if (atomicAdd(flags + 16, 1u) == NI - 1) {
#pragma unroll
      for (int u = 0; u <= 16; u++) flags[u] = 0;
    }
  }
}

typedef CUresult (*EncodeTiledFn)(CUtensorMap*, CUtensorMapDataType, cuuint32_t, void*, const cuuint64_t*,
                                  const cuuint64_t*, const cuuint32_t*, const cuuint32_t*, CUtensorMapInterleave,
                                  CUtensorMapSwizzle, CUtensorMapL2promotion, CUtensorMapFloatOOBfill);

}

extern "C" void kernel_launch(void* const* d_in, const int* in_sizes, int n_in, void* d_out, int out_size) {
  const __nv_bfloat16* x = (const __nv_bfloat16*)d_in[0];
  const int* qw = (const int*)d_in[1];
  const __nv_bfloat16* lut = (const __nv_bfloat16*)d_in[2];
  const __nv_bfloat16* scales = (const __nv_bfloat16*)d_in[3];
  __nv_bfloat16* out = (__nv_bfloat16*)d_out;

  static EncodeTiledFn enc = nullptr;
  static void* p_w = nullptr;
  static void* p_flag = nullptr;
  if (!enc) {
    void* fn = nullptr;
    cudaDriverEntryPointQueryResult qr;
    cudaGetDriverEntryPoint("cuTensorMapEncodeTiled", &fn, cudaEnableDefault, &qr);
    enc = (EncodeTiledFn)fn;
    cudaGetSymbolAddress(&p_w, g_w);
    cudaGetSymbolAddress(&p_flag, g_flag);
    cudaFuncSetAttribute(fused_kernel, cudaFuncAttributeMaxDynamicSharedMemorySize, SMEM_TOTAL);
  }
  CUtensorMap tm_x, tm_q;
  cuuint32_t estr[2] = {1, 1};
  {
    cuuint64_t gdim[2] = {(cuuint64_t)D_DIM, (cuuint64_t)S_DIM};
    cuuint64_t gstr[1] = {(cuuint64_t)D_DIM * 2};
    cuuint32_t box[2] = {(cuuint32_t)BK, 64};
    enc(&tm_x, CU_TENSOR_MAP_DATA_TYPE_BFLOAT16, 2, (void*)x, gdim, gstr, box, estr, CU_TENSOR_MAP_INTERLEAVE_NONE,
        CU_TENSOR_MAP_SWIZZLE_128B, CU_TENSOR_MAP_L2_PROMOTION_L2_256B, CU_TENSOR_MAP_FLOAT_OOB_FILL_NONE);
  }
  {
    cuuint64_t gdim[2] = {(cuuint64_t)F_DIM, (cuuint64_t)D_DIM};
    cuuint64_t gstr[1] = {(cuuint64_t)F_DIM * 4};
    cuuint32_t box[2] = {(cuuint32_t)BN, 8};
    enc(&tm_q, CU_TENSOR_MAP_DATA_TYPE_INT32, 2, (void*)qw, gdim, gstr, box, estr, CU_TENSOR_MAP_INTERLEAVE_NONE,
        CU_TENSOR_MAP_SWIZZLE_NONE, CU_TENSOR_MAP_L2_PROMOTION_NONE, CU_TENSOR_MAP_FLOAT_OOB_FILL_NONE);
  }
  fused_kernel<<<NI * NJ, 256, SMEM_TOTAL, cudaStreamPerThread>>>(tm_x, tm_q, qw, lut, scales, out, (uint4*)p_w,
                                                                  (unsigned*)p_flag);
}
```

```cpp
#include <cuda_runtime.h>
#include <cuda_bf16.h>
#include <cuda.h>
#include <stdint.h>

namespace {

constexpr int S_DIM = 2048, D_DIM = 1024, F_DIM = 3584;
constexpr int BM = 256, BN = 224, BK = 64;
constexpr int NKB = D_DIM / BK;
constexpr int NJ = F_DIM / BN;
constexpr int NI = S_DIM / BM;
constexpr int WS = 4;
constexpr int XS = 5;
constexpr int ENDK = 4;
constexpr int NR = NKB - ENDK;
constexpr int X_SLICE = 64 * BK * 2;
constexpr int W_STAGE = BN * BK * 2;
constexpr int W_KC = BN * 16;

__device__ uint4 g_w[NJ * NKB * 8 * BN];
__device__ unsigned g_flag[NJ * 32];

__device__ __forceinline__ uint32_t smem_u32(const void* p) { return (uint32_t)__cvta_generic_to_shared(p); }
__device__ __forceinline__ unsigned clk32() {
  unsigned c;
  asm volatile("mov.u32 %0, %%clock;" : "=r"(c)::"memory");
  return c;
}
__device__ __forceinline__ bool elect_one() {
  uint32_t p;
  asm volatile("{\n.reg .pred P;\nelect.sync _|P, 0xffffffff;\nselp.b32 %0, 1, 0, P;\n}" : "=r"(p));
  return p != 0;
}
__device__ __forceinline__ void mbar_init(uint32_t bar, uint32_t cnt) {
  asm volatile("mbarrier.init.shared::cta.b64 [%0], %1;" ::"r"(bar), "r"(cnt) : "memory");
}
__device__ __forceinline__ void mbar_expect_tx(uint32_t bar, uint32_t bytes) {
  asm volatile("mbarrier.arrive.expect_tx.shared::cta.b64 _, [%0], %1;" ::"r"(bar), "r"(bytes) : "memory");
}
__device__ __forceinline__ void mbar_arrive(uint32_t bar) {
  asm volatile("mbarrier.arrive.shared::cta.b64 _, [%0];" ::"r"(bar) : "memory");
}
__device__ __forceinline__ bool mbar_test(uint32_t bar, uint32_t parity) {
  uint32_t ok;
  asm volatile(
      "{\n.reg .pred p;\nmbarrier.test_wait.parity.shared::cta.b64 p, [%1], %2;\nselp.b32 %0, 1, 0, p;\n}\n"
      : "=r"(ok) : "r"(bar), "r"(parity) : "memory");
  return ok != 0;
}
__device__ __forceinline__ void mbar_wait(uint32_t bar, uint32_t parity) {
  asm volatile(
      "{\n.reg .pred p;\n"
      "LAB_WAIT:\n"
      "mbarrier.try_wait.parity.shared::cta.b64 p, [%0], %1;\n"
      "@p bra LAB_DONE;\n"
      "bra LAB_WAIT;\n"
      "LAB_DONE:\n}\n" ::"r"(bar), "r"(parity) : "memory");
}
__device__ __forceinline__ void tma_load_2d(uint32_t dst, const CUtensorMap* tm, int c0, int c1, uint32_t bar) {
  asm volatile(
      "cp.async.bulk.tensor.2d.shared::cluster.global.mbarrier::complete_tx::bytes [%0], [%1, {%3, %4}], [%2];"
      ::"r"(dst), "l"(tm), "r"(bar), "r"(c0), "r"(c1) : "memory");
}
__device__ __forceinline__ void bulk_load(uint32_t dst, const void* src, uint32_t bytes, uint32_t bar) {
  asm volatile(
      "cp.async.bulk.shared::cluster.global.mbarrier::complete_tx::bytes [%0], [%1], %2, [%3];"
      ::"r"(dst), "l"(src), "r"(bytes), "r"(bar) : "memory");
}
__device__ __forceinline__ int ldg_stream(const int* p) {
  int v;
  asm volatile("ld.global.L1::no_allocate.b32 %0, [%1];" : "=r"(v) : "l"(p) : "memory");
  return v;
}
__device__ __forceinline__ int lds32(uint32_t addr) {
  int v;
  asm volatile("ld.shared.b32 %0, [%1];" : "=r"(v) : "r"(addr) : "memory");
  return v;
}
__device__ __forceinline__ uint64_t make_desc(uint32_t lo, uint32_t hi) {
  uint64_t d;
  asm("mov.b64 %0, {%1, %2};" : "=l"(d) : "r"(lo), "r"(hi));
  return d;
}
__device__ __forceinline__ unsigned ld_strong(const void* p) {
  unsigned v;
  asm volatile("ld.relaxed.gpu.global.u32 %0, [%1];" : "=r"(v) : "l"(p) : "memory");
  return v;
}
__device__ __forceinline__ void st_strong128(void* p, uint4 v) {
  asm volatile("st.relaxed.gpu.global.v4.u32 [%0], {%1, %2, %3, %4};" ::"l"(p), "r"(v.x), "r"(v.y), "r"(v.z), "r"(v.w)
               : "memory");
}
__device__ __forceinline__ void wgmma_fence() { asm volatile("wgmma.fence.sync.aligned;" ::: "memory"); }
__device__ __forceinline__ void wgmma_commit() { asm volatile("wgmma.commit_group.sync.aligned;" ::: "memory"); }
template <int N>
__device__ __forceinline__ void wgmma_wait() { asm volatile("wgmma.wait_group.sync.aligned %0;" ::"n"(N) : "memory"); }
__device__ __forceinline__ void bar_sync(int id, int n) { asm volatile("bar.sync %0, %1;" ::"r"(id), "r"(n) : "memory"); }
__device__ __forceinline__ void bar_arrive(int id, int n) { asm volatile("bar.arrive %0, %1;" ::"r"(id), "r"(n) : "memory"); }

__device__ __forceinline__ void wgmma_m64n224k16(float (&d)[112], uint64_t da, uint64_t db, int scale_d) {
  asm volatile(
    "{\n.reg .pred p;\nsetp.ne.b32 p, %114, 0;\n"
    "wgmma.mma_async.sync.aligned.m64n224k16.f32.bf16.bf16 "
    "{%0, %1, %2, %3, %4, %5, %6, %7, %8, %9, %10, %11, %12, %13, %14, %15, "
    "%16, %17, %18, %19, %20, %21, %22, %23, %24, %25, %26, %27, %28, %29, %30, %31, "
    "%32, %33, %34, %35, %36, %37, %38, %39, %40, %41, %42, %43, %44, %45, %46, %47, "
    "%48, %49, %50, %51, %52, %53, %54, %55, %56, %57, %58, %59, %60, %61, %62, %63, "
    "%64, %65, %66, %67, %68, %69, %70, %71, %72, %73, %74, %75, %76, %77, %78, %79, "
    "%80, %81, %82, %83, %84, %85, %86, %87, %88, %89, %90, %91, %92, %93, %94, %95, "
    "%96, %97, %98, %99, %100, %101, %102, %103, %104, %105, %106, %107, %108, %109, %110, %111}, "
    "%112, %113, p, 1, 1, 0, 0;\n}\n"
    : "+f"(d[0]), "+f"(d[1]), "+f"(d[2]), "+f"(d[3]), "+f"(d[4]), "+f"(d[5]), "+f"(d[6]), "+f"(d[7]),
      "+f"(d[8]), "+f"(d[9]), "+f"(d[10]), "+f"(d[11]), "+f"(d[12]), "+f"(d[13]), "+f"(d[14]), "+f"(d[15]),
      "+f"(d[16]), "+f"(d[17]), "+f"(d[18]), "+f"(d[19]), "+f"(d[20]), "+f"(d[21]), "+f"(d[22]), "+f"(d[23]),
      "+f"(d[24]), "+f"(d[25]), "+f"(d[26]), "+f"(d[27]), "+f"(d[28]), "+f"(d[29]), "+f"(d[30]), "+f"(d[31]),
      "+f"(d[32]), "+f"(d[33]), "+f"(d[34]), "+f"(d[35]), "+f"(d[36]), "+f"(d[37]), "+f"(d[38]), "+f"(d[39]),
      "+f"(d[40]), "+f"(d[41]), "+f"(d[42]), "+f"(d[43]), "+f"(d[44]), "+f"(d[45]), "+f"(d[46]), "+f"(d[47]),
      "+f"(d[48]), "+f"(d[49]), "+f"(d[50]), "+f"(d[51]), "+f"(d[52]), "+f"(d[53]), "+f"(d[54]), "+f"(d[55]),
      "+f"(d[56]), "+f"(d[57]), "+f"(d[58]), "+f"(d[59]), "+f"(d[60]), "+f"(d[61]), "+f"(d[62]), "+f"(d[63]),
      "+f"(d[64]), "+f"(d[65]), "+f"(d[66]), "+f"(d[67]), "+f"(d[68]), "+f"(d[69]), "+f"(d[70]), "+f"(d[71]),
      "+f"(d[72]), "+f"(d[73]), "+f"(d[74]), "+f"(d[75]), "+f"(d[76]), "+f"(d[77]), "+f"(d[78]), "+f"(d[79]),
      "+f"(d[80]), "+f"(d[81]), "+f"(d[82]), "+f"(d[83]), "+f"(d[84]), "+f"(d[85]), "+f"(d[86]), "+f"(d[87]),
      "+f"(d[88]), "+f"(d[89]), "+f"(d[90]), "+f"(d[91]), "+f"(d[92]), "+f"(d[93]), "+f"(d[94]), "+f"(d[95]),
      "+f"(d[96]), "+f"(d[97]), "+f"(d[98]), "+f"(d[99]), "+f"(d[100]), "+f"(d[101]), "+f"(d[102]), "+f"(d[103]),
      "+f"(d[104]), "+f"(d[105]), "+f"(d[106]), "+f"(d[107]), "+f"(d[108]), "+f"(d[109]), "+f"(d[110]), "+f"(d[111])
    : "l"(da), "l"(db), "r"(scale_d));
}

__device__ __forceinline__ uint32_t pack_bf16(float lo, float hi) {
  uint32_t r;
  asm("cvt.rn.bf16x2.f32 %0, %1, %2;" : "=r"(r) : "f"(hi), "f"(lo));
  return r;
}

__device__ __forceinline__ int perm32(int n) { return (n & ~30) | ((n & 6) << 2) | ((n >> 2) & 6); }

constexpr int SMEM_X = 0;
constexpr int SMEM_W = 2 * XS * X_SLICE;
constexpr int SMEM_Q = SMEM_W + WS * W_STAGE;
constexpr int Q_UNIT = 8 * BN * 4;
constexpr int SMEM_BAR = SMEM_Q + W_STAGE;
constexpr int B_FULLW = 0, B_FULLQ = 16, B_FULLX = 32, B_DONE = 96, B_COUNT = 160;
constexpr int SMEM_TL = SMEM_BAR + B_COUNT * 8;
constexpr int SMEM_TOTAL = SMEM_TL + 2048;
constexpr unsigned FLAG_FULL = NI * 7;

#define TL(i)
#define TLG(i)

__device__ __forceinline__ void store_acc(const float (&a)[112], __nv_bfloat16* p) {
#pragma unroll
  for (int J = 0; J < 7; J++) {
    uint4 v0, v1;
    v0.x = pack_bf16(a[16 * J + 0], a[16 * J + 1]);
    v0.y = pack_bf16(a[16 * J + 4], a[16 * J + 5]);
    v0.z = pack_bf16(a[16 * J + 8], a[16 * J + 9]);
    v0.w = pack_bf16(a[16 * J + 12], a[16 * J + 13]);
    v1.x = pack_bf16(a[16 * J + 2], a[16 * J + 3]);
    v1.y = pack_bf16(a[16 * J + 6], a[16 * J + 7]);
    v1.z = pack_bf16(a[16 * J + 10], a[16 * J + 11]);
    v1.w = pack_bf16(a[16 * J + 14], a[16 * J + 15]);
    *reinterpret_cast<uint4*>(p + 32 * J) = v0;
    *reinterpret_cast<uint4*>(p + 8 * F_DIM + 32 * J) = v1;
  }
}

__device__ __forceinline__ void load_unit(int (&q)[8], const int* p) {
#pragma unroll
  for (int i = 0; i < 8; i++) q[i] = ldg_stream(p + i * F_DIM);
}
__device__ __forceinline__ uint4 convert_unit(const int (&q)[8], float lutv, float sc) {
  float v[8];
#pragma unroll
  for (int i = 0; i < 8; i++) v[i] = __shfl_sync(0xffffffffu, lutv, q[i]) * sc;
  uint4 o;
  o.x = pack_bf16(v[0], v[1]);
  o.y = pack_bf16(v[2], v[3]);
  o.z = pack_bf16(v[4], v[5]);
  o.w = pack_bf16(v[6], v[7]);
  return o;
}

constexpr int PU = 3;
constexpr int R1 = 7;
#define PACE 650

__global__ void __launch_bounds__(256, 1)
fused_kernel(const __grid_constant__ CUtensorMap tm_x, const __grid_constant__ CUtensorMap tm_q,
             const int* __restrict__ qw, const __nv_bfloat16* __restrict__ lut,
             const __nv_bfloat16* __restrict__ scales, __nv_bfloat16* __restrict__ out, uint4* wscr,
             unsigned* flag_base) {
  extern __shared__ __align__(1024) uint8_t smem_raw[];
  const uint32_t sbase = __shfl_sync(0xffffffffu, smem_u32(smem_raw), 0);
  const uint32_t bars = sbase + SMEM_BAR;
  const int j = blockIdx.x >> 3, it = blockIdx.x & 7;
  const int warp = __shfl_sync(0xffffffffu, threadIdx.x >> 5, 0);
  const int wg = warp >> 2;
  const int lane = threadIdx.x & 31;
  const unsigned t_start = clk32();
  TL(0); TLG(1);

  uint4* wp = wscr + (j * (NKB * 8) + it - 8) * BN + perm32(warp * 32 + lane);
  float lutv, sc;
  unsigned rb;
  unsigned* fl = flag_base + j * 32 + (lane & 15);
  const uint8_t* wsrc = reinterpret_cast<const uint8_t*>(wscr) + (size_t)j * NKB * W_STAGE;
  const int xrow = it * BM + wg * 128;

  auto emit_unit = [&](const int (&qq)[8]) {
    wp += 8 * BN;
    st_strong128(wp, convert_unit(qq, lutv, sc));
    rb = ld_strong(wp);
  };
  auto publish_unit = [&](int u) {
    asm volatile(
        "{\n.reg .pred P, Q;\n"
        "setp.ne.u32 P, %1, 0xffffffff;\n"
        "vote.sync.all.pred P, P, 0xffffffff;\n"
        "setp.eq.and.s32 Q, %2, %3, P;\n"
        "@Q red.relaxed.gpu.global.add.u32 [%0], 1;\n}"
        ::"l"(fl), "r"(rb), "r"(lane), "r"(u) : "memory");
  };
  auto load_x = [&](int g, int n, int slot, int kb, int half) {
    mbar_expect_tx(bars + 8 * (B_FULLX + g * 32 + n), X_SLICE);
    tma_load_2d(sbase + SMEM_X + (g * XS + slot) * X_SLICE, &tm_x, kb * BK, it * BM + g * 128 + half * 64,
                bars + 8 * (B_FULLX + g * 32 + n));
  };
  auto load_q = [&](int u) {
    mbar_expect_tx(bars + 8 * (B_FULLQ + u), Q_UNIT);
    tma_load_2d(sbase + SMEM_Q + (u & 3) * Q_UNIT, &tm_q, j * BN, u * BK + it * 8, bars + 8 * (B_FULLQ + u));
  };

  int next_w = 0;
  unsigned ready = 0;
  auto issue_w = [&](int kb, int slot) {
    if (elect_one()) {
      asm volatile("fence.proxy.async.global;" ::: "memory");
      mbar_expect_tx(bars + 8 * (B_FULLW + kb), W_STAGE);
      bulk_load(sbase + SMEM_W + slot * W_STAGE, wsrc + (size_t)kb * W_STAGE, W_STAGE, bars + 8 * (B_FULLW + kb));
    }
  };
  auto wait_ready = [&](int kb) {
    int spins = 0;
    while (!((ready >> kb) & 1)) {
      ready = __ballot_sync(0xffffffffu, ld_strong(fl) >= FLAG_FULL);
      if (++spins > (1 << 22)) __trap();
    }
  };
  auto load_w_must = [&](int must) {
    while (next_w < must) {
      wait_ready(next_w);
      issue_w(next_w, next_w & 3);
      next_w++;
    }
  };
  auto load_w_may = [&](int may) {
    ready |= __ballot_sync(0xffffffffu, rb >= FLAG_FULL);
    if (next_w < may && ((ready >> next_w) & 1)) {
      issue_w(next_w, next_w & 3);
      next_w++;
    }
    rb = ld_strong(fl);
  };

  const uint32_t qaddr = sbase + SMEM_Q + threadIdx.x * 4;
  auto lds_unit = [&](int (&q)[8], int u) {
    mbar_wait(bars + 8 * (B_FULLQ + u), 0);
#pragma unroll
    for (int i = 0; i < 8; i++) q[i] = lds32(qaddr + (u & 3) * Q_UNIT + i * (BN * 4));
  };
  auto arrive_one = [&](uint32_t bar) {
    asm volatile("{\n.reg .pred P;\nelect.sync _|P, 0xffffffff;\n@P mbarrier.arrive.shared::cta.b64 _, [%0];\n}"
                 ::"r"(bar) : "memory");
  };
  int q[8];
  {
    const int fcol = j * BN + (warp < 7 ? warp : 0) * 32 + lane;
    if (warp < 7) load_unit(q, qw + (size_t)(it * 8) * F_DIM + fcol);
    lutv = __bfloat162float(lut[lane & 15]);
    sc = __bfloat162float(scales[fcol]);
    if (elect_one()) {
#pragma unroll
      for (int i = 0; i < 12; i++) mbar_init(bars + 8 * (warp * 12 + i), 1);
#pragma unroll
      for (int i = 0; i < 8; i++) mbar_init(bars + 8 * (B_DONE + warp * 8 + i), 4);
      asm volatile("fence.mbarrier_init.release.cluster;" ::: "memory");
    }
    bar_sync(0, 256);
    if (warp < 7) {
      emit_unit(q);
      TL(2);
      publish_unit(0);
      TL(3);
      lds_unit(q, 1);
      emit_unit(q);
      arrive_one(bars + 8 * (B_DONE + wg * 32 + 30));
      publish_unit(1);
      TL(4);
      lds_unit(q, 2);
      emit_unit(q);
      TL(5);
      lds_unit(q, 3);
    } else {
      if (elect_one()) {
        load_x(0, 0, 0, 0, 0); load_x(0, 1, 1, 0, 1); load_x(1, 0, 0, 0, 0); load_x(1, 1, 1, 0, 1);
      }
      arrive_one(bars + 8 * (B_DONE + 32 + 30));
      while (clk32() - t_start < PACE) {}
      if (elect_one()) load_q(1);
      while (clk32() - t_start < 2 * PACE) {}
      if (elect_one()) load_q(2);
      while (clk32() - t_start < 3 * PACE) {}
      if (elect_one()) load_q(3);
      load_w_must(1);
      TL(2);
      if (elect_one()) {
        load_q(4);
        load_x(0, 2, 2, 1, 0); load_x(0, 3, 3, 1, 1); load_x(1, 2, 2, 1, 0); load_x(1, 3, 3, 1, 1);
      }
      rb = 0;
      do {
        load_w_may(PU);
      } while (next_w < 2 && !mbar_test(bars + 8 * B_FULLW, 0));
      TL(3);
      mbar_wait(bars + 8 * (B_DONE + 30), 0);
      mbar_wait(bars + 8 * (B_DONE + 32 + 30), 0);
      if (elect_one()) {
        load_q(5);
        load_x(0, 4, 4, 2, 0); load_x(1, 4, 4, 2, 0);
      }
    }
    arrive_one(bars + 8 * (B_DONE + wg * 32 + 31));
  }

  float acc0[112], acc1[112];
  constexpr uint32_t DA_HI = (1u << 30) | (1024 >> 4), DB_HI = (128 >> 4);
  const uint32_t da0 = (1u << 16) | ((sbase + SMEM_X + wg * (XS * X_SLICE)) >> 4);
  const uint32_t db0 = ((W_KC >> 4) << 16) | ((sbase + SMEM_W) >> 4);
  const uint32_t fullx = bars + 8 * (B_FULLX + wg * 32), done = bars + 8 * (B_DONE + wg * 32);
  const bool x_issuer = (warp & 3) == 3;

  int xs = 0, xp = 0;

  auto mma4 = [&](float (&acc)[112], int n, int wslot, int accum) {
    mbar_wait(fullx + 8 * n, 0);
    const uint32_t da = da0 + xs * (X_SLICE >> 4);
    const uint32_t db = db0 + wslot * (W_STAGE >> 4);
    wgmma_fence();
#pragma unroll
    for (int k = 0; k < 4; k++)
      wgmma_m64n224k16(acc, make_desc(da + k * 2, DA_HI), make_desc(db + k * (2 * W_KC >> 4), DB_HI), k != 0 || accum);
    wgmma_commit();
  };
  auto end_slot = [&](int n, int kb, int half) {
    wgmma_wait<1>();
    arrive_one(done + 8 * n);
    if (x_issuer) {
      mbar_wait(done + 8 * n, 0);
      if (n > 0 && elect_one()) load_x(wg, n + 4, xp, kb, half);
    }
    xp = xs;
    xs = xs == XS - 1 ? 0 : xs + 1;
  };
  auto side_slot = [&](int n) {
    if (warp < 7) {
      const int u = n + PU;
      publish_unit(u - 1);
      if (u < NKB) emit_unit(q);
      if (u + 1 < NKB) lds_unit(q, u + 1);
    } else {
      mbar_wait(bars + 8 * (B_DONE + ((n - 1) & 31)), 0);
      if (n + 6 < NKB && elect_one()) load_q(n + 6);
      load_w_may(((n - 1) >> 1) + 4);
    }
  };

#pragma unroll 1
  for (int r = 0; r < R1; r++) {
    if (warp == 7) load_w_must(r + 1);
    mbar_wait(bars + 8 * (B_FULLW + r), 0);
    TL(8 + 2 * r);
    mma4(acc0, 2 * r, r & 3, r);
    end_slot(2 * r, r + 2, 0);
    side_slot(2 * r);
    TL(9 + 2 * r);
    mma4(acc1, 2 * r + 1, r & 3, r);
    end_slot(2 * r + 1, r + 2, 1);
    side_slot(2 * r + 1);
  }
#pragma unroll 1
  for (int r = R1; r < NR; r++) {
    if (warp == 7) load_w_must(r + 1);
    mbar_wait(bars + 8 * (B_FULLW + r), 0);
    TL(8 + 2 * r);
    mma4(acc0, 2 * r, r & 3, 1);
    end_slot(2 * r, r == NR - 1 ? 15 : r + 2, 0);
    if (warp == 7 && r == R1 + 1) {
      wait_ready(15);
      issue_w(15, 4);
    }
    TL(9 + 2 * r);
    mma4(acc1, 2 * r + 1, r & 3, 1);
    end_slot(2 * r + 1, r >= NR - 2 ? r + 3 : r + 2, r >= NR - 2 ? 0 : 1);
    if (warp == 7) {
      mbar_wait(bars + 8 * (B_DONE + 2 * r), 0);
      load_w_must(r + 4);
    }
  }

  __nv_bfloat16* op = out + (size_t)(xrow + (warp & 3) * 16 + (lane >> 2)) * F_DIM + j * BN + (lane & 3) * 8;
  TL(40);
  if (wg == 1) bar_sync(1, 256);
#pragma unroll
  for (int e = 0; e < ENDK; e++) {
    const int kb = e < 2 ? NR + e : NR + 5 - e;
    mbar_wait(bars + 8 * (B_FULLW + kb), 0);
    mma4(acc0, 2 * NR + e, kb == 15 ? 4 : (kb & 3), 1);
    if (e == ENDK - 1) bar_arrive(1 + wg, 256);
    end_slot(2 * NR + e, kb, 1);
  }
  wgmma_wait<0>();
  TL(41);
  store_acc(acc0, op);
  TL(42);
  bar_sync(2 + wg, 256);
#pragma unroll
  for (int e = 0; e < ENDK; e++) {
    const int kb = e < 2 ? NR + e : NR + 5 - e;
    mma4(acc1, 2 * NR + ENDK + e, kb == 15 ? 4 : (kb & 3), 1);
    xs = xs == XS - 1 ? 0 : xs + 1;
  }
  if (wg == 0) bar_arrive(3, 256);
  wgmma_wait<0>();
  TL(43);
  store_acc(acc1, op + 64 * F_DIM);
  TL(44);
  if (threadIdx.x == 0) {
    if (atomicAdd(fl + 16, 1u) == NI - 1) {
#pragma unroll
      for (int u = 0; u <= 16; u++) fl[u] = 0;
    }
  }
}

typedef CUresult (*EncodeTiledFn)(CUtensorMap*, CUtensorMapDataType, cuuint32_t, void*, const cuuint64_t*,
                                  const cuuint64_t*, const cuuint32_t*, const cuuint32_t*, CUtensorMapInterleave,
                                  CUtensorMapSwizzle, CUtensorMapL2promotion, CUtensorMapFloatOOBfill);

}

extern "C" void kernel_launch(void* const* d_in, const int* in_sizes, int n_in, void* d_out, int out_size) {
  const __nv_bfloat16* x = (const __nv_bfloat16*)d_in[0];
  const int* qw = (const int*)d_in[1];
  const __nv_bfloat16* lut = (const __nv_bfloat16*)d_in[2];
  const __nv_bfloat16* scales = (const __nv_bfloat16*)d_in[3];
  __nv_bfloat16* out = (__nv_bfloat16*)d_out;

  static EncodeTiledFn enc = nullptr;
  static void* p_w = nullptr;
  static void* p_flag = nullptr;
  if (!enc) {
    void* fn = nullptr;
    cudaDriverEntryPointQueryResult qr;
    cudaGetDriverEntryPoint("cuTensorMapEncodeTiled", &fn, cudaEnableDefault, &qr);
    enc = (EncodeTiledFn)fn;
    cudaGetSymbolAddress(&p_w, g_w);
    cudaGetSymbolAddress(&p_flag, g_flag);
    cudaFuncSetAttribute(fused_kernel, cudaFuncAttributeMaxDynamicSharedMemorySize, SMEM_TOTAL);
  }
  CUtensorMap tm_x, tm_q;
  cuuint32_t estr[2] = {1, 1};
  {
    cuuint64_t gdim[2] = {(cuuint64_t)D_DIM, (cuuint64_t)S_DIM};
    cuuint64_t gstr[1] = {(cuuint64_t)D_DIM * 2};
    cuuint32_t box[2] = {(cuuint32_t)BK, 64};
    enc(&tm_x, CU_TENSOR_MAP_DATA_TYPE_BFLOAT16, 2, (void*)x, gdim, gstr, box, estr, CU_TENSOR_MAP_INTERLEAVE_NONE,
        CU_TENSOR_MAP_SWIZZLE_128B, CU_TENSOR_MAP_L2_PROMOTION_L2_256B, CU_TENSOR_MAP_FLOAT_OOB_FILL_NONE);
  }
  {
    cuuint64_t gdim[2] = {(cuuint64_t)F_DIM, (cuuint64_t)D_DIM};
    cuuint64_t gstr[1] = {(cuuint64_t)F_DIM * 4};
    cuuint32_t box[2] = {(cuuint32_t)BN, 8};
    enc(&tm_q, CU_TENSOR_MAP_DATA_TYPE_INT32, 2, (void*)qw, gdim, gstr, box, estr, CU_TENSOR_MAP_INTERLEAVE_NONE,
        CU_TENSOR_MAP_SWIZZLE_NONE, CU_TENSOR_MAP_L2_PROMOTION_NONE, CU_TENSOR_MAP_FLOAT_OOB_FILL_NONE);
  }
  fused_kernel<<<NI * NJ, 256, SMEM_TOTAL, cudaStreamPerThread>>>(tm_x, tm_q, qw, lut, scales, out, (uint4*)p_w,
                                                                  (unsigned*)p_flag);
}
```

```cpp
#include <cuda_runtime.h>
#include <cuda_bf16.h>
#include <cuda.h>
#include <stdint.h>

namespace {

constexpr int S_DIM = 2048, D_DIM = 1024, F_DIM = 3584;
constexpr int BM = 256, BN = 224, BK = 64;
constexpr int NKB = D_DIM / BK;
constexpr int NJ = F_DIM / BN;
constexpr int NI = S_DIM / BM;
constexpr int WS = 4;
constexpr int XS = 5;
constexpr int ENDK = 4;
constexpr int NR = NKB - ENDK;
constexpr int X_SLICE = 64 * BK * 2;
constexpr int W_STAGE = BN * BK * 2;
constexpr int W_KC = BN * 16;

constexpr int REGION = 512 * 1024;
__device__ uint4 g_scratch[(NJ + 1) * REGION / 16];

__device__ __forceinline__ uint32_t smem_u32(const void* p) { return (uint32_t)__cvta_generic_to_shared(p); }
__device__ __forceinline__ unsigned clk32() {
  unsigned c;
  asm volatile("mov.u32 %0, %%clock;" : "=r"(c)::"memory");
  return c;
}
__device__ __forceinline__ bool elect_one() {
  uint32_t p;
  asm volatile("{\n.reg .pred P;\nelect.sync _|P, 0xffffffff;\nselp.b32 %0, 1, 0, P;\n}" : "=r"(p));
  return p != 0;
}
__device__ __forceinline__ void mbar_init(uint32_t bar, uint32_t cnt) {
  asm volatile("mbarrier.init.shared::cta.b64 [%0], %1;" ::"r"(bar), "r"(cnt) : "memory");
}
__device__ __forceinline__ void mbar_expect_tx(uint32_t bar, uint32_t bytes) {
  asm volatile("mbarrier.arrive.expect_tx.shared::cta.b64 _, [%0], %1;" ::"r"(bar), "r"(bytes) : "memory");
}
__device__ __forceinline__ void mbar_arrive(uint32_t bar) {
  asm volatile("mbarrier.arrive.shared::cta.b64 _, [%0];" ::"r"(bar) : "memory");
}
__device__ __forceinline__ bool mbar_test(uint32_t bar, uint32_t parity) {
  uint32_t ok;
  asm volatile(
      "{\n.reg .pred p;\nmbarrier.test_wait.parity.shared::cta.b64 p, [%1], %2;\nselp.b32 %0, 1, 0, p;\n}\n"
      : "=r"(ok) : "r"(bar), "r"(parity) : "memory");
  return ok != 0;
}
__device__ __forceinline__ void mbar_wait(uint32_t bar, uint32_t parity) {
  asm volatile(
      "{\n.reg .pred p;\n"
      "LAB_WAIT:\n"
      "mbarrier.try_wait.parity.shared::cta.b64 p, [%0], %1;\n"
      "@p bra LAB_DONE;\n"
      "bra LAB_WAIT;\n"
      "LAB_DONE:\n}\n" ::"r"(bar), "r"(parity) : "memory");
}
__device__ __forceinline__ void tma_load_2d(uint32_t dst, const CUtensorMap* tm, int c0, int c1, uint32_t bar) {
  asm volatile(
      "cp.async.bulk.tensor.2d.shared::cluster.global.mbarrier::complete_tx::bytes [%0], [%1, {%3, %4}], [%2];"
      ::"r"(dst), "l"(tm), "r"(bar), "r"(c0), "r"(c1) : "memory");
}
__device__ __forceinline__ void bulk_load(uint32_t dst, const void* src, uint32_t bytes, uint32_t bar) {
  asm volatile(
      "cp.async.bulk.shared::cluster.global.mbarrier::complete_tx::bytes [%0], [%1], %2, [%3];"
      ::"r"(dst), "l"(src), "r"(bytes), "r"(bar) : "memory");
}
__device__ __forceinline__ int ldg_stream(const int* p) {
  int v;
  asm volatile("ld.global.L1::no_allocate.b32 %0, [%1];" : "=r"(v) : "l"(p) : "memory");
  return v;
}
__device__ __forceinline__ int lds32(uint32_t addr) {
  int v;
  asm volatile("ld.shared.b32 %0, [%1];" : "=r"(v) : "r"(addr) : "memory");
  return v;
}
__device__ __forceinline__ uint64_t make_desc(uint32_t lo, uint32_t hi) {
  uint64_t d;
  asm("mov.b64 %0, {%1, %2};" : "=l"(d) : "r"(lo), "r"(hi));
  return d;
}
__device__ __forceinline__ unsigned ld_strong(const void* p) {
  unsigned v;
  asm volatile("ld.relaxed.gpu.global.u32 %0, [%1];" : "=r"(v) : "l"(p) : "memory");
  return v;
}
__device__ __forceinline__ void st_strong128(void* p, uint4 v) {
  asm volatile("st.relaxed.gpu.global.v4.u32 [%0], {%1, %2, %3, %4};" ::"l"(p), "r"(v.x), "r"(v.y), "r"(v.z), "r"(v.w)
               : "memory");
}
__device__ __forceinline__ void wgmma_fence() { asm volatile("wgmma.fence.sync.aligned;" ::: "memory"); }
__device__ __forceinline__ void wgmma_commit() { asm volatile("wgmma.commit_group.sync.aligned;" ::: "memory"); }
template <int N>
__device__ __forceinline__ void wgmma_wait() { asm volatile("wgmma.wait_group.sync.aligned %0;" ::"n"(N) : "memory"); }
__device__ __forceinline__ void bar_sync(int id, int n) { asm volatile("bar.sync %0, %1;" ::"r"(id), "r"(n) : "memory"); }
__device__ __forceinline__ void bar_arrive(int id, int n) { asm volatile("bar.arrive %0, %1;" ::"r"(id), "r"(n) : "memory"); }

__device__ __forceinline__ void wgmma_m64n224k16(float (&d)[112], uint64_t da, uint64_t db, int scale_d) {
  asm volatile(
    "{\n.reg .pred p;\nsetp.ne.b32 p, %114, 0;\n"
    "wgmma.mma_async.sync.aligned.m64n224k16.f32.bf16.bf16 "
    "{%0, %1, %2, %3, %4, %5, %6, %7, %8, %9, %10, %11, %12, %13, %14, %15, "
    "%16, %17, %18, %19, %20, %21, %22, %23, %24, %25, %26, %27, %28, %29, %30, %31, "
    "%32, %33, %34, %35, %36, %37, %38, %39, %40, %41, %42, %43, %44, %45, %46, %47, "
    "%48, %49, %50, %51, %52, %53, %54, %55, %56, %57, %58, %59, %60, %61, %62, %63, "
    "%64, %65, %66, %67, %68, %69, %70, %71, %72, %73, %74, %75, %76, %77, %78, %79, "
    "%80, %81, %82, %83, %84, %85, %86, %87, %88, %89, %90, %91, %92, %93, %94, %95, "
    "%96, %97, %98, %99, %100, %101, %102, %103, %104, %105, %106, %107, %108, %109, %110, %111}, "
    "%112, %113, p, 1, 1, 0, 0;\n}\n"
    : "+f"(d[0]), "+f"(d[1]), "+f"(d[2]), "+f"(d[3]), "+f"(d[4]), "+f"(d[5]), "+f"(d[6]), "+f"(d[7]),
      "+f"(d[8]), "+f"(d[9]), "+f"(d[10]), "+f"(d[11]), "+f"(d[12]), "+f"(d[13]), "+f"(d[14]), "+f"(d[15]),
      "+f"(d[16]), "+f"(d[17]), "+f"(d[18]), "+f"(d[19]), "+f"(d[20]), "+f"(d[21]), "+f"(d[22]), "+f"(d[23]),
      "+f"(d[24]), "+f"(d[25]), "+f"(d[26]), "+f"(d[27]), "+f"(d[28]), "+f"(d[29]), "+f"(d[30]), "+f"(d[31]),
      "+f"(d[32]), "+f"(d[33]), "+f"(d[34]), "+f"(d[35]), "+f"(d[36]), "+f"(d[37]), "+f"(d[38]), "+f"(d[39]),
      "+f"(d[40]), "+f"(d[41]), "+f"(d[42]), "+f"(d[43]), "+f"(d[44]), "+f"(d[45]), "+f"(d[46]), "+f"(d[47]),
      "+f"(d[48]), "+f"(d[49]), "+f"(d[50]), "+f"(d[51]), "+f"(d[52]), "+f"(d[53]), "+f"(d[54]), "+f"(d[55]),
      "+f"(d[56]), "+f"(d[57]), "+f"(d[58]), "+f"(d[59]), "+f"(d[60]), "+f"(d[61]), "+f"(d[62]), "+f"(d[63]),
      "+f"(d[64]), "+f"(d[65]), "+f"(d[66]), "+f"(d[67]), "+f"(d[68]), "+f"(d[69]), "+f"(d[70]), "+f"(d[71]),
      "+f"(d[72]), "+f"(d[73]), "+f"(d[74]), "+f"(d[75]), "+f"(d[76]), "+f"(d[77]), "+f"(d[78]), "+f"(d[79]),
      "+f"(d[80]), "+f"(d[81]), "+f"(d[82]), "+f"(d[83]), "+f"(d[84]), "+f"(d[85]), "+f"(d[86]), "+f"(d[87]),
      "+f"(d[88]), "+f"(d[89]), "+f"(d[90]), "+f"(d[91]), "+f"(d[92]), "+f"(d[93]), "+f"(d[94]), "+f"(d[95]),
      "+f"(d[96]), "+f"(d[97]), "+f"(d[98]), "+f"(d[99]), "+f"(d[100]), "+f"(d[101]), "+f"(d[102]), "+f"(d[103]),
      "+f"(d[104]), "+f"(d[105]), "+f"(d[106]), "+f"(d[107]), "+f"(d[108]), "+f"(d[109]), "+f"(d[110]), "+f"(d[111])
    : "l"(da), "l"(db), "r"(scale_d));
}

__device__ __forceinline__ uint32_t pack_bf16(float lo, float hi) {
  uint32_t r;
  asm("cvt.rn.bf16x2.f32 %0, %1, %2;" : "=r"(r) : "f"(hi), "f"(lo));
  return r;
}

__device__ __forceinline__ int perm32(int n) { return (n & ~30) | ((n & 6) << 2) | ((n >> 2) & 6); }

constexpr int SMEM_X = 0;
constexpr int SMEM_W = 2 * XS * X_SLICE;
constexpr int SMEM_Q = SMEM_W + WS * W_STAGE;
constexpr int Q_UNIT = 8 * BN * 4;
constexpr int SMEM_BAR = SMEM_Q + W_STAGE;
constexpr int B_FULLW = 0, B_FULLQ = 16, B_FULLX = 32, B_DONE = 96, B_COUNT = 160;
constexpr int SMEM_TL = SMEM_BAR + B_COUNT * 8;
constexpr int SMEM_TOTAL = SMEM_TL + 2048;
constexpr unsigned FLAG_FULL = NI * 7;

#define TL(i)
#define TLG(i)

__device__ __forceinline__ void store_acc(const float (&a)[112], __nv_bfloat16* p) {
#pragma unroll
  for (int J = 0; J < 7; J++) {
    uint4 v0, v1;
    v0.x = pack_bf16(a[16 * J + 0], a[16 * J + 1]);
    v0.y = pack_bf16(a[16 * J + 4], a[16 * J + 5]);
    v0.z = pack_bf16(a[16 * J + 8], a[16 * J + 9]);
    v0.w = pack_bf16(a[16 * J + 12], a[16 * J + 13]);
    v1.x = pack_bf16(a[16 * J + 2], a[16 * J + 3]);
    v1.y = pack_bf16(a[16 * J + 6], a[16 * J + 7]);
    v1.z = pack_bf16(a[16 * J + 10], a[16 * J + 11]);
    v1.w = pack_bf16(a[16 * J + 14], a[16 * J + 15]);
    *reinterpret_cast<uint4*>(p + 32 * J) = v0;
    *reinterpret_cast<uint4*>(p + 8 * F_DIM + 32 * J) = v1;
  }
}

__device__ __forceinline__ void load_unit(int (&q)[8], const int* p) {
#pragma unroll
  for (int i = 0; i < 8; i++) q[i] = ldg_stream(p + i * F_DIM);
}
__device__ __forceinline__ uint4 convert_unit(const int (&q)[8], float lutv, float sc) {
  float v[8];
#pragma unroll
  for (int i = 0; i < 8; i++) v[i] = __shfl_sync(0xffffffffu, lutv, q[i]) * sc;
  uint4 o;
  o.x = pack_bf16(v[0], v[1]);
  o.y = pack_bf16(v[2], v[3]);
  o.z = pack_bf16(v[4], v[5]);
  o.w = pack_bf16(v[6], v[7]);
  return o;
}

__device__ __forceinline__ void dequant_lookup(int (&q)[8], float lutv) {
  asm volatile(
      "shfl.sync.idx.b32 %0, %8, %0, 31, 0xffffffff;\n"
      "shfl.sync.idx.b32 %1, %8, %1, 31, 0xffffffff;\n"
      "shfl.sync.idx.b32 %2, %8, %2, 31, 0xffffffff;\n"
      "shfl.sync.idx.b32 %3, %8, %3, 31, 0xffffffff;\n"
      "shfl.sync.idx.b32 %4, %8, %4, 31, 0xffffffff;\n"
      "shfl.sync.idx.b32 %5, %8, %5, 31, 0xffffffff;\n"
      "shfl.sync.idx.b32 %6, %8, %6, 31, 0xffffffff;\n"
      "shfl.sync.idx.b32 %7, %8, %7, 31, 0xffffffff;\n"
      : "+r"(q[0]), "+r"(q[1]), "+r"(q[2]), "+r"(q[3]), "+r"(q[4]), "+r"(q[5]), "+r"(q[6]), "+r"(q[7])
      : "r"(__float_as_int(lutv)));
}
__device__ __forceinline__ void dequant_finish(int (&q)[8], unsigned& rb, uint4* wp, float sc, uint32_t qbar,
                                               uint32_t qaddr) {
  asm volatile(
      "{\n.reg .pred W;\n.reg .b32 o0, o1, o2, o3;\n"
      "DQ_WAIT:\n"
      "mbarrier.try_wait.parity.shared::cta.b64 W, [%11], 0;\n"
      "@!W bra DQ_WAIT;\n"
      "mul.rn.f32 %0, %0, %10;\nmul.rn.f32 %1, %1, %10;\nmul.rn.f32 %2, %2, %10;\nmul.rn.f32 %3, %3, %10;\n"
      "mul.rn.f32 %4, %4, %10;\nmul.rn.f32 %5, %5, %10;\nmul.rn.f32 %6, %6, %10;\nmul.rn.f32 %7, %7, %10;\n"
      "cvt.rn.bf16x2.f32 o0, %1, %0;\ncvt.rn.bf16x2.f32 o1, %3, %2;\n"
      "cvt.rn.bf16x2.f32 o2, %5, %4;\ncvt.rn.bf16x2.f32 o3, %7, %6;\n"
      "ld.volatile.shared.b32 %0, [%12];\nld.volatile.shared.b32 %1, [%12+896];\n"
      "ld.volatile.shared.b32 %2, [%12+1792];\nld.volatile.shared.b32 %3, [%12+2688];\n"
      "ld.volatile.shared.b32 %4, [%12+3584];\nld.volatile.shared.b32 %5, [%12+4480];\n"
      "ld.volatile.shared.b32 %6, [%12+5376];\nld.volatile.shared.b32 %7, [%12+6272];\n"
      "st.relaxed.gpu.global.v4.u32 [%9], {o0, o1, o2, o3};\n"
      "ld.relaxed.gpu.global.u32 %8, [%9];\n}\n"
      : "+r"(q[0]), "+r"(q[1]), "+r"(q[2]), "+r"(q[3]), "+r"(q[4]), "+r"(q[5]), "+r"(q[6]), "+r"(q[7]), "=r"(rb)
      : "l"(wp), "r"(__float_as_int(sc)), "r"(qbar), "r"(qaddr)
      : "memory");
}

constexpr int PU = 3;
#define HEAVY 0x6DB6Du
#define PACE_X 300
#define PACE_Q1 650
#define PACE_Q2 1400
#define PACE_Q3 2000

__global__ void __launch_bounds__(256, 1)
fused_kernel(const __grid_constant__ CUtensorMap tm_x, const __grid_constant__ CUtensorMap tm_q,
             const int* __restrict__ qw, const __nv_bfloat16* __restrict__ lut,
             const __nv_bfloat16* __restrict__ scales, __nv_bfloat16* __restrict__ out, uint8_t* scratch) {
  extern __shared__ __align__(1024) uint8_t smem_raw[];
  const uint32_t sbase = __shfl_sync(0xffffffffu, smem_u32(smem_raw), 0);
  const uint32_t bars = sbase + SMEM_BAR;
  const int j = blockIdx.x >> 3, it = blockIdx.x & 7;
  const int warp = __shfl_sync(0xffffffffu, threadIdx.x >> 5, 0);
  const int wg = warp >> 2;
  int lane;
  asm volatile("mov.u32 %0, %%laneid;" : "=r"(lane));
  const unsigned t_start = clk32();
  TL(0); TLG(1);

  uint8_t* const region = scratch + (size_t)j * REGION;
  uint8_t* wp = region + 128 + it * W_KC + perm32(warp * 32 + lane) * 16;
  unsigned* const fl = reinterpret_cast<unsigned*>(region) + (lane & 15);
  float lutv, sc;
  unsigned rb;
  const int xrow = it * BM + wg * 128;

  auto w_ptr = [&](int u) { return reinterpret_cast<uint4*>(wp + u * W_STAGE); };
  auto emit_unit = [&](const int (&qq)[8], int u) {
    st_strong128(w_ptr(u), convert_unit(qq, lutv, sc));
    rb = ld_strong(w_ptr(u));
  };
  auto publish_unit = [&](int u) {
    asm volatile(
        "{\n.reg .pred P, Q;\n"
        "setp.ne.u32 P, %1, 0xffffffff;\n"
        "vote.sync.all.pred P, P, 0xffffffff;\n"
        "setp.eq.and.s32 Q, %2, %3, P;\n"
        "@Q red.relaxed.gpu.global.add.u32 [%0], 1;\n}"
        ::"l"(fl), "r"(rb), "r"(lane), "r"(u) : "memory");
  };
  auto load_x = [&](int g, int n, int slot, int kb, int half) {
    mbar_expect_tx(bars + 8 * (B_FULLX + g * 32 + n), X_SLICE);
    tma_load_2d(sbase + SMEM_X + (g * XS + slot) * X_SLICE, &tm_x, kb * BK, it * BM + g * 128 + half * 64,
                bars + 8 * (B_FULLX + g * 32 + n));
  };
  auto load_q = [&](int u) {
    mbar_expect_tx(bars + 8 * (B_FULLQ + u), Q_UNIT);
    tma_load_2d(sbase + SMEM_Q + (u & 3) * Q_UNIT, &tm_q, j * BN, u * BK + it * 8, bars + 8 * (B_FULLQ + u));
  };

  int next_w = 0;
  unsigned ready = 0;
  auto issue_w = [&](int kb, int slot) {
    if (elect_one()) {
      asm volatile("fence.proxy.async.global;" ::: "memory");
      mbar_expect_tx(bars + 8 * (B_FULLW + kb), W_STAGE);
      bulk_load(sbase + SMEM_W + slot * W_STAGE, region + 128 + kb * W_STAGE, W_STAGE, bars + 8 * (B_FULLW + kb));
    }
  };
  auto wait_ready = [&](int kb) {
    int spins = 0;
    while (!((ready >> kb) & 1)) {
      ready = __ballot_sync(0xffffffffu, ld_strong(fl) >= FLAG_FULL);
      if (++spins > (1 << 22)) __trap();
    }
  };
  auto load_w_must = [&](int must) {
    while (next_w < must) {
      wait_ready(next_w);
      issue_w(next_w, next_w & 3);
      next_w++;
    }
  };
  auto load_w_may = [&](int may) {
    ready |= __ballot_sync(0xffffffffu, rb >= FLAG_FULL);
    if (next_w < may && ((ready >> next_w) & 1)) {
      issue_w(next_w, next_w & 3);
      next_w++;
    }
    if (ready != 0xffffffffu) rb = ld_strong(fl);
  };

  const uint32_t qbase = sbase + SMEM_Q + warp * 128;
  auto lds_unit = [&](int (&q)[8], int u) {
    mbar_wait(bars + 8 * (B_FULLQ + u), 0);
#pragma unroll
    for (int i = 0; i < 8; i++) q[i] = lds32(qbase + (u & 3) * Q_UNIT + lane * 4 + i * (BN * 4));
  };
  auto arrive_one = [&](uint32_t bar) {
    asm volatile("{\n.reg .pred P;\nelect.sync _|P, 0xffffffff;\n@P mbarrier.arrive.shared::cta.b64 _, [%0];\n}"
                 ::"r"(bar) : "memory");
  };
  int q[8];
  if (warp < 7) {
    const int fcol = j * BN + warp * 32 + lane;
    load_unit(q, qw + (size_t)(it * 8) * F_DIM + fcol);
    lutv = __bfloat162float(lut[lane & 15]);
    sc = __bfloat162float(scales[fcol]);
    emit_unit(q, 0);
    TL(2);
    publish_unit(0);
    TL(3);
    if (elect_one()) {
      const int first = warp < 4 ? B_FULLX + (warp >> 1) * 32 + 5 + (warp & 1) * 5 : B_DONE + (warp - 4) * 21;
#pragma unroll
      for (int i = 0; i < 22; i++) mbar_init(bars + 8 * (first + i), warp < 4 ? 1 : 4);
      asm volatile("fence.mbarrier_init.release.cluster;" ::: "memory");
    }
    __syncwarp();
    bar_arrive(4, 256);
    bar_sync(0, 256);
    lds_unit(q, 1);
    emit_unit(q, 1);
    publish_unit(1);
    TL(4);
    lds_unit(q, 2);
    emit_unit(q, 2);
    TL(5);
    lds_unit(q, 3);
  } else {
    if (elect_one()) {
      asm volatile("prefetch.tensormap [%0];" ::"l"(&tm_x) : "memory");
      asm volatile("prefetch.tensormap [%0];" ::"l"(&tm_q) : "memory");
#pragma unroll
      for (int i = 0; i < B_FULLX + XS; i++) mbar_init(bars + 8 * i, 1);
#pragma unroll
      for (int i = 0; i < XS; i++) mbar_init(bars + 8 * (B_FULLX + 32 + i), 1);
      asm volatile("fence.mbarrier_init.release.cluster;" ::: "memory");
    }
    __syncwarp();
    rb = ld_strong(fl);
    bar_arrive(0, 256);
    TL(4);
    while (clk32() - t_start < PACE_X) {}
    if (elect_one()) {
      load_x(0, 0, 0, 0, 0); load_x(0, 1, 1, 0, 1); load_x(1, 0, 0, 0, 0); load_x(1, 1, 1, 0, 1);
    }
    while (clk32() - t_start < PACE_Q1) {}
    if (elect_one()) load_q(1);
    lutv = 0.f;
    sc = 0.f;
    ready = __ballot_sync(0xffffffffu, rb >= FLAG_FULL);
    while (clk32() - t_start < PACE_Q2) {}
    if (elect_one()) load_q(2);
    while (clk32() - t_start < PACE_Q3) {}
    if (elect_one()) load_q(3);
    load_w_must(1);
    TL(2);
    if (elect_one()) {
      load_q(4);
      load_x(0, 2, 2, 1, 0); load_x(0, 3, 3, 1, 1); load_x(1, 2, 2, 1, 0); load_x(1, 3, 3, 1, 1);
    }
    rb = 0;
    do {
      load_w_may(PU);
    } while (next_w < 2 && !mbar_test(bars + 8 * B_FULLW, 0));
    TL(3);
    if (elect_one()) { load_x(0, 4, 4, 2, 0); load_x(1, 4, 4, 2, 0); }
    bar_sync(4, 256);
  }
  arrive_one(bars + 8 * (B_DONE + wg * 32 + 31));

  float acc0[112], acc1[112];
  constexpr uint32_t DA_HI = (1u << 30) | (1024 >> 4), DB_HI = (128 >> 4);
  const uint32_t da0 = (1u << 16) | ((sbase + SMEM_X + wg * (XS * X_SLICE)) >> 4);
  const uint32_t db0 = ((W_KC >> 4) << 16) | ((sbase + SMEM_W) >> 4);
  const uint32_t fullx = bars + 8 * (B_FULLX + wg * 32), done = bars + 8 * (B_DONE + wg * 32);
  const bool x_issuer = (warp & 3) == 3;

  int xs = 0, xp = 0;
  int unit = PU;
  int next_q = 5;

  auto mma4 = [&](float (&acc)[112], int n, int wslot, int accum) {
    mbar_wait(fullx + 8 * n, 0);
    const uint32_t da = da0 + xs * (X_SLICE >> 4);
    const uint32_t db = db0 + wslot * (W_STAGE >> 4);
    wgmma_fence();
#pragma unroll
    for (int k = 0; k < 4; k++)
      wgmma_m64n224k16(acc, make_desc(da + k * 2, DA_HI), make_desc(db + k * (2 * W_KC >> 4), DB_HI), k != 0 || accum);
    wgmma_commit();
  };
  auto end_slot = [&](int n, int kb, int half) {
    wgmma_wait<1>();
    arrive_one(done + 8 * n);
    if (x_issuer) {
      mbar_wait(done + 8 * n, 0);
      if (n > 0 && elect_one()) load_x(wg, n + 4, xp, kb, half);
    }
    xp = xs;
    xs = xs == XS - 1 ? 0 : xs + 1;
  };
  auto slot = [&](int n, int kb, int half) {
    const bool heavy = warp < 7 && ((HEAVY >> n) & 1);
    if (heavy) dequant_lookup(q, lutv);
    end_slot(n, kb, half);
    if (warp < 7) {
      if (((HEAVY * 2 + 1) >> n) & 1) publish_unit(unit - 1);
      if (heavy) {
        const int un = unit + 1 < NKB ? unit + 1 : unit;
        dequant_finish(q, rb, w_ptr(unit), sc, bars + 8 * (B_FULLQ + un), qbase + (un & 3) * Q_UNIT + lane * 4);
        unit++;
      }
    } else {
      mbar_wait(bars + 8 * (B_DONE + ((n - 1) & 31)), 0);
      unit += ((HEAVY * 4) >> n) & 1;
      if (next_q < NKB && next_q <= unit + 4) {
        if (elect_one()) load_q(next_q);
        next_q++;
      }
      load_w_may(((n - 1) >> 1) + 4);
      if (n == 21) {
        wait_ready(15);
        issue_w(15, 4);
      }
      if (n & 1) load_w_must(n == 2 * NR - 1 ? 15 : (n >> 1) + 2);
    }
  };

#pragma unroll 1
  for (int r = 0; r < NR; r++) {
    mbar_wait(bars + 8 * (B_FULLW + r), 0);
    TL(8 + 2 * r);
    mma4(acc0, 2 * r, r & 3, r);
    slot(2 * r, r == NR - 1 ? 15 : r + 2, 0);
    TL(9 + 2 * r);
    mma4(acc1, 2 * r + 1, r & 3, r);
    slot(2 * r + 1, r >= NR - 2 ? r + 3 : r + 2, r >= NR - 2 ? 0 : 1);
  }

  __nv_bfloat16* op = out + (size_t)(xrow + (warp & 3) * 16 + (lane >> 2)) * F_DIM + j * BN + (lane & 3) * 8;
  TL(40);
  if (wg == 1) bar_sync(1, 256);
#pragma unroll
  for (int e = 0; e < ENDK; e++) {
    const int kb = e < 2 ? NR + e : NR + 5 - e;
    mbar_wait(bars + 8 * (B_FULLW + kb), 0);
    mma4(acc0, 2 * NR + e, kb == 15 ? 4 : (kb & 3), 1);
    if (e == ENDK - 1) bar_arrive(1 + wg, 256);
    end_slot(2 * NR + e, kb, 1);
  }
  wgmma_wait<0>();
  TL(41);
  store_acc(acc0, op);
  TL(42);
  bar_sync(2 + wg, 256);
#pragma unroll
  for (int e = 0; e < ENDK; e++) {
    const int kb = e < 2 ? NR + e : NR + 5 - e;
    mma4(acc1, 2 * NR + ENDK + e, kb == 15 ? 4 : (kb & 3), 1);
    xs = xs == XS - 1 ? 0 : xs + 1;
  }
  if (wg == 0) bar_arrive(3, 256);
  wgmma_wait<0>();
  TL(43);
  store_acc(acc1, op + 64 * F_DIM);
  TL(44);
  if (warp == 0 && lane == 0) {
    if (atomicAdd(fl + 16, 1u) == NI - 1) {
#pragma unroll
      for (int u = 0; u <= 16; u++) fl[u] = 0;
    }
  }
}

typedef CUresult (*EncodeTiledFn)(CUtensorMap*, CUtensorMapDataType, cuuint32_t, void*, const cuuint64_t*,
                                  const cuuint64_t*, const cuuint32_t*, const cuuint32_t*, CUtensorMapInterleave,
                                  CUtensorMapSwizzle, CUtensorMapL2promotion, CUtensorMapFloatOOBfill);

}

#define XPROMO CU_TENSOR_MAP_L2_PROMOTION_L2_128B
extern "C" void kernel_launch(void* const* d_in, const int* in_sizes, int n_in, void* d_out, int out_size) {
  const __nv_bfloat16* x = (const __nv_bfloat16*)d_in[0];
  const int* qw = (const int*)d_in[1];
  const __nv_bfloat16* lut = (const __nv_bfloat16*)d_in[2];
  const __nv_bfloat16* scales = (const __nv_bfloat16*)d_in[3];
  __nv_bfloat16* out = (__nv_bfloat16*)d_out;

  static EncodeTiledFn enc = nullptr;
  static uint8_t* p_scr = nullptr;
  if (!enc) {
    void* fn = nullptr;
    cudaDriverEntryPointQueryResult qr;
    cudaGetDriverEntryPoint("cuTensorMapEncodeTiled", &fn, cudaEnableDefault, &qr);
    enc = (EncodeTiledFn)fn;
    void* p = nullptr;
    cudaGetSymbolAddress(&p, g_scratch);
    p_scr = (uint8_t*)(((uintptr_t)p + REGION - 1) & ~(uintptr_t)(REGION - 1));
    cudaFuncSetAttribute(fused_kernel, cudaFuncAttributeMaxDynamicSharedMemorySize, SMEM_TOTAL);
  }
  CUtensorMap tm_x, tm_q;
  cuuint32_t estr[2] = {1, 1};
  {
    cuuint64_t gdim[2] = {(cuuint64_t)D_DIM, (cuuint64_t)S_DIM};
    cuuint64_t gstr[1] = {(cuuint64_t)D_DIM * 2};
    cuuint32_t box[2] = {(cuuint32_t)BK, 64};
    enc(&tm_x, CU_TENSOR_MAP_DATA_TYPE_BFLOAT16, 2, (void*)x, gdim, gstr, box, estr, CU_TENSOR_MAP_INTERLEAVE_NONE,
        CU_TENSOR_MAP_SWIZZLE_128B, XPROMO, CU_TENSOR_MAP_FLOAT_OOB_FILL_NONE);
  }
  {
    cuuint64_t gdim[2] = {(cuuint64_t)F_DIM, (cuuint64_t)D_DIM};
    cuuint64_t gstr[1] = {(cuuint64_t)F_DIM * 4};
    cuuint32_t box[2] = {(cuuint32_t)BN, 8};
    enc(&tm_q, CU_TENSOR_MAP_DATA_TYPE_INT32, 2, (void*)qw, gdim, gstr, box, estr, CU_TENSOR_MAP_INTERLEAVE_NONE,
        CU_TENSOR_MAP_SWIZZLE_NONE, CU_TENSOR_MAP_L2_PROMOTION_NONE, CU_TENSOR_MAP_FLOAT_OOB_FILL_NONE);
  }
  fused_kernel<<<NI * NJ, 256, SMEM_TOTAL, cudaStreamPerThread>>>(tm_x, tm_q, qw, lut, scales, out, p_scr);
}
```

```cpp
#include <cuda_runtime.h>
#include <cuda_bf16.h>
#include <cuda.h>
#include <stdint.h>

namespace {

constexpr int S_DIM = 2048, D_DIM = 1024, F_DIM = 3584;
constexpr int BM = 256, BN = 224, BK = 64;
constexpr int NKB = D_DIM / BK;
constexpr int NJ = F_DIM / BN;
constexpr int NI = S_DIM / BM;
constexpr int WS = 4;
constexpr int XS = 5;
constexpr int ENDK = 4;
constexpr int NR = NKB - ENDK;
constexpr int X_SLICE = 64 * BK * 2;
constexpr int W_STAGE = BN * BK * 2;
constexpr int W_KC = BN * 16;

constexpr int REGION = 512 * 1024;
__device__ uint4 g_scratch[(NJ + 1) * REGION / 16];

__device__ __forceinline__ uint32_t smem_u32(const void* p) { return (uint32_t)__cvta_generic_to_shared(p); }
__device__ __forceinline__ unsigned clk32() {
  unsigned c;
  asm volatile("mov.u32 %0, %%clock;" : "=r"(c)::"memory");
  return c;
}
__device__ __forceinline__ bool elect_one() {
  uint32_t p;
  asm volatile("{\n.reg .pred P;\nelect.sync _|P, 0xffffffff;\nselp.b32 %0, 1, 0, P;\n}" : "=r"(p));
  return p != 0;
}
__device__ __forceinline__ void mbar_init(uint32_t bar, uint32_t cnt) {
  asm volatile("mbarrier.init.shared::cta.b64 [%0], %1;" ::"r"(bar), "r"(cnt) : "memory");
}
__device__ __forceinline__ void mbar_expect_tx(uint32_t bar, uint32_t bytes) {
  asm volatile("mbarrier.arrive.expect_tx.shared::cta.b64 _, [%0], %1;" ::"r"(bar), "r"(bytes) : "memory");
}
__device__ __forceinline__ void mbar_arrive(uint32_t bar) {
  asm volatile("mbarrier.arrive.shared::cta.b64 _, [%0];" ::"r"(bar) : "memory");
}
__device__ __forceinline__ bool mbar_test(uint32_t bar, uint32_t parity) {
  uint32_t ok;
  asm volatile(
      "{\n.reg .pred p;\nmbarrier.test_wait.parity.shared::cta.b64 p, [%1], %2;\nselp.b32 %0, 1, 0, p;\n}\n"
      : "=r"(ok) : "r"(bar), "r"(parity) : "memory");
  return ok != 0;
}
__device__ __forceinline__ void mbar_wait(uint32_t bar, uint32_t parity) {
  asm volatile(
      "{\n.reg .pred p;\n"
      "LAB_WAIT:\n"
      "mbarrier.try_wait.parity.shared::cta.b64 p, [%0], %1;\n"
      "@p bra LAB_DONE;\n"
      "bra LAB_WAIT;\n"
      "LAB_DONE:\n}\n" ::"r"(bar), "r"(parity) : "memory");
}
__device__ __forceinline__ uint32_t ring(uint32_t base, int i) { return base + 8 * (i & 7); }
__device__ __forceinline__ void ring_wait(uint32_t base, int i) { mbar_wait(ring(base, i), (i >> 3) & 1); }
__device__ __forceinline__ void tma_load_2d(uint32_t dst, const CUtensorMap* tm, int c0, int c1, uint32_t bar) {
  asm volatile(
      "cp.async.bulk.tensor.2d.shared::cluster.global.mbarrier::complete_tx::bytes [%0], [%1, {%3, %4}], [%2];"
      ::"r"(dst), "l"(tm), "r"(bar), "r"(c0), "r"(c1) : "memory");
}
__device__ __forceinline__ void tma_prefetch_2d(const CUtensorMap* tm, int c0, int c1) {
  asm volatile("cp.async.bulk.prefetch.tensor.2d.L2.global [%0, {%1, %2}];" ::"l"(tm), "r"(c0), "r"(c1) : "memory");
}
__device__ __forceinline__ void bulk_load(uint32_t dst, const void* src, uint32_t bytes, uint32_t bar) {
  asm volatile(
      "cp.async.bulk.shared::cluster.global.mbarrier::complete_tx::bytes [%0], [%1], %2, [%3];"
      ::"r"(dst), "l"(src), "r"(bytes), "r"(bar) : "memory");
}
__device__ __forceinline__ int ldg_stream(const int* p) {
  int v;
  asm volatile("ld.global.L1::no_allocate.b32 %0, [%1];" : "=r"(v) : "l"(p) : "memory");
  return v;
}
__device__ __forceinline__ uint32_t ldg_u16(const void* p) {
  uint32_t v;
  asm volatile("ld.global.u16 %0, [%1];" : "=r"(v) : "l"(p) : "memory");
  return v;
}
__device__ __forceinline__ int lds32(uint32_t addr) {
  int v;
  asm volatile("ld.shared.b32 %0, [%1];" : "=r"(v) : "r"(addr) : "memory");
  return v;
}
__device__ __forceinline__ uint64_t make_desc(uint32_t lo, uint32_t hi) {
  uint64_t d;
  asm("mov.b64 %0, {%1, %2};" : "=l"(d) : "r"(lo), "r"(hi));
  return d;
}
__device__ __forceinline__ unsigned ld_strong(const void* p) {
  unsigned v;
  asm volatile("ld.relaxed.gpu.global.u32 %0, [%1];" : "=r"(v) : "l"(p) : "memory");
  return v;
}
__device__ __forceinline__ void st_strong128(void* p, uint4 v) {
  asm volatile("st.relaxed.gpu.global.v4.u32 [%0], {%1, %2, %3, %4};" ::"l"(p), "r"(v.x), "r"(v.y), "r"(v.z), "r"(v.w)
               : "memory");
}
__device__ __forceinline__ void wgmma_fence() { asm volatile("wgmma.fence.sync.aligned;" ::: "memory"); }
__device__ __forceinline__ void wgmma_commit() { asm volatile("wgmma.commit_group.sync.aligned;" ::: "memory"); }
template <int N>
__device__ __forceinline__ void wgmma_wait() { asm volatile("wgmma.wait_group.sync.aligned %0;" ::"n"(N) : "memory"); }
__device__ __forceinline__ void bar_sync(int id, int n) { asm volatile("bar.sync %0, %1;" ::"r"(id), "r"(n) : "memory"); }
__device__ __forceinline__ void bar_arrive(int id, int n) { asm volatile("bar.arrive %0, %1;" ::"r"(id), "r"(n) : "memory"); }

__device__ __forceinline__ void wgmma_m64n224k16(float (&d)[112], uint64_t da, uint64_t db, int scale_d) {
  asm volatile(
    "{\n.reg .pred p;\nsetp.ne.b32 p, %114, 0;\n"
    "wgmma.mma_async.sync.aligned.m64n224k16.f32.bf16.bf16 "
    "{%0, %1, %2, %3, %4, %5, %6, %7, %8, %9, %10, %11, %12, %13, %14, %15, "
    "%16, %17, %18, %19, %20, %21, %22, %23, %24, %25, %26, %27, %28, %29, %30, %31, "
    "%32, %33, %34, %35, %36, %37, %38, %39, %40, %41, %42, %43, %44, %45, %46, %47, "
    "%48, %49, %50, %51, %52, %53, %54, %55, %56, %57, %58, %59, %60, %61, %62, %63, "
    "%64, %65, %66, %67, %68, %69, %70, %71, %72, %73, %74, %75, %76, %77, %78, %79, "
    "%80, %81, %82, %83, %84, %85, %86, %87, %88, %89, %90, %91, %92, %93, %94, %95, "
    "%96, %97, %98, %99, %100, %101, %102, %103, %104, %105, %106, %107, %108, %109, %110, %111}, "
    "%112, %113, p, 1, 1, 0, 0;\n}\n"
    : "+f"(d[0]), "+f"(d[1]), "+f"(d[2]), "+f"(d[3]), "+f"(d[4]), "+f"(d[5]), "+f"(d[6]), "+f"(d[7]),
      "+f"(d[8]), "+f"(d[9]), "+f"(d[10]), "+f"(d[11]), "+f"(d[12]), "+f"(d[13]), "+f"(d[14]), "+f"(d[15]),
      "+f"(d[16]), "+f"(d[17]), "+f"(d[18]), "+f"(d[19]), "+f"(d[20]), "+f"(d[21]), "+f"(d[22]), "+f"(d[23]),
      "+f"(d[24]), "+f"(d[25]), "+f"(d[26]), "+f"(d[27]), "+f"(d[28]), "+f"(d[29]), "+f"(d[30]), "+f"(d[31]),
      "+f"(d[32]), "+f"(d[33]), "+f"(d[34]), "+f"(d[35]), "+f"(d[36]), "+f"(d[37]), "+f"(d[38]), "+f"(d[39]),
      "+f"(d[40]), "+f"(d[41]), "+f"(d[42]), "+f"(d[43]), "+f"(d[44]), "+f"(d[45]), "+f"(d[46]), "+f"(d[47]),
      "+f"(d[48]), "+f"(d[49]), "+f"(d[50]), "+f"(d[51]), "+f"(d[52]), "+f"(d[53]), "+f"(d[54]), "+f"(d[55]),
      "+f"(d[56]), "+f"(d[57]), "+f"(d[58]), "+f"(d[59]), "+f"(d[60]), "+f"(d[61]), "+f"(d[62]), "+f"(d[63]),
      "+f"(d[64]), "+f"(d[65]), "+f"(d[66]), "+f"(d[67]), "+f"(d[68]), "+f"(d[69]), "+f"(d[70]), "+f"(d[71]),
      "+f"(d[72]), "+f"(d[73]), "+f"(d[74]), "+f"(d[75]), "+f"(d[76]), "+f"(d[77]), "+f"(d[78]), "+f"(d[79]),
      "+f"(d[80]), "+f"(d[81]), "+f"(d[82]), "+f"(d[83]), "+f"(d[84]), "+f"(d[85]), "+f"(d[86]), "+f"(d[87]),
      "+f"(d[88]), "+f"(d[89]), "+f"(d[90]), "+f"(d[91]), "+f"(d[92]), "+f"(d[93]), "+f"(d[94]), "+f"(d[95]),
      "+f"(d[96]), "+f"(d[97]), "+f"(d[98]), "+f"(d[99]), "+f"(d[100]), "+f"(d[101]), "+f"(d[102]), "+f"(d[103]),
      "+f"(d[104]), "+f"(d[105]), "+f"(d[106]), "+f"(d[107]), "+f"(d[108]), "+f"(d[109]), "+f"(d[110]), "+f"(d[111])
    : "l"(da), "l"(db), "r"(scale_d));
}

__device__ __forceinline__ uint32_t pack_bf16(float lo, float hi) {
  uint32_t r;
  asm("cvt.rn.bf16x2.f32 %0, %1, %2;" : "=r"(r) : "f"(hi), "f"(lo));
  return r;
}

__device__ __forceinline__ int perm32(int n) { return (n & ~30) | ((n & 6) << 2) | ((n >> 2) & 6); }

constexpr int SMEM_X = 0;
constexpr int SMEM_W = 2 * XS * X_SLICE;
constexpr int SMEM_Q = SMEM_W + WS * W_STAGE;
constexpr int Q_UNIT = 8 * BN * 4;
constexpr int SMEM_BAR = SMEM_Q + W_STAGE;
constexpr int B_FULLW = 0, B_FULLQ = 8, B_FULLX = 16, B_DONE = 32, B_COUNT = 48;
constexpr int SMEM_TL = SMEM_BAR + B_COUNT * 8;
constexpr int SMEM_TOTAL = SMEM_TL + 2048;
constexpr int W_OFF = 128;
constexpr unsigned FLAG_FULL = NI * 7;

#define TL(i)
#define TLG(i)

__device__ __forceinline__ void store_acc(const float (&a)[112], __nv_bfloat16* p) {
#pragma unroll
  for (int J = 0; J < 7; J++) {
    uint4 v0, v1;
    v0.x = pack_bf16(a[16 * J + 0], a[16 * J + 1]);
    v0.y = pack_bf16(a[16 * J + 4], a[16 * J + 5]);
    v0.z = pack_bf16(a[16 * J + 8], a[16 * J + 9]);
    v0.w = pack_bf16(a[16 * J + 12], a[16 * J + 13]);
    v1.x = pack_bf16(a[16 * J + 2], a[16 * J + 3]);
    v1.y = pack_bf16(a[16 * J + 6], a[16 * J + 7]);
    v1.z = pack_bf16(a[16 * J + 10], a[16 * J + 11]);
    v1.w = pack_bf16(a[16 * J + 14], a[16 * J + 15]);
    *reinterpret_cast<uint4*>(p + 32 * J) = v0;
    *reinterpret_cast<uint4*>(p + 8 * F_DIM + 32 * J) = v1;
  }
}

__device__ __forceinline__ void load_unit(int (&q)[8], const int* p) {
#pragma unroll
  for (int i = 0; i < 8; i++) q[i] = ldg_stream(p + i * F_DIM);
}
__device__ __forceinline__ uint4 convert_unit(const int (&q)[8], float lutv, float sc) {
  float v[8];
#pragma unroll
  for (int i = 0; i < 8; i++) v[i] = __shfl_sync(0xffffffffu, lutv, q[i]) * sc;
  uint4 o;
  o.x = pack_bf16(v[0], v[1]);
  o.y = pack_bf16(v[2], v[3]);
  o.z = pack_bf16(v[4], v[5]);
  o.w = pack_bf16(v[6], v[7]);
  return o;
}

__device__ __forceinline__ void dequant_lookup(int (&q)[8], float lutv) {
  asm volatile(
      "shfl.sync.idx.b32 %0, %8, %0, 31, 0xffffffff;\n"
      "shfl.sync.idx.b32 %1, %8, %1, 31, 0xffffffff;\n"
      "shfl.sync.idx.b32 %2, %8, %2, 31, 0xffffffff;\n"
      "shfl.sync.idx.b32 %3, %8, %3, 31, 0xffffffff;\n"
      "shfl.sync.idx.b32 %4, %8, %4, 31, 0xffffffff;\n"
      "shfl.sync.idx.b32 %5, %8, %5, 31, 0xffffffff;\n"
      "shfl.sync.idx.b32 %6, %8, %6, 31, 0xffffffff;\n"
      "shfl.sync.idx.b32 %7, %8, %7, 31, 0xffffffff;\n"
      : "+r"(q[0]), "+r"(q[1]), "+r"(q[2]), "+r"(q[3]), "+r"(q[4]), "+r"(q[5]), "+r"(q[6]), "+r"(q[7])
      : "r"(__float_as_int(lutv)));
}
__device__ __forceinline__ void dequant_finish(int (&q)[8], unsigned& rb, uint4* wp, float sc, uint32_t qbar,
                                               uint32_t qpar, uint32_t qaddr) {
  asm volatile(
      "{\n.reg .pred W;\n.reg .b32 o0, o1, o2, o3;\n"
      "DQ_WAIT:\n"
      "mbarrier.try_wait.parity.shared::cta.b64 W, [%11], %13;\n"
      "@!W bra DQ_WAIT;\n"
      "mul.rn.f32 %0, %0, %10;\nmul.rn.f32 %1, %1, %10;\nmul.rn.f32 %2, %2, %10;\nmul.rn.f32 %3, %3, %10;\n"
      "mul.rn.f32 %4, %4, %10;\nmul.rn.f32 %5, %5, %10;\nmul.rn.f32 %6, %6, %10;\nmul.rn.f32 %7, %7, %10;\n"
      "cvt.rn.bf16x2.f32 o0, %1, %0;\ncvt.rn.bf16x2.f32 o1, %3, %2;\n"
      "cvt.rn.bf16x2.f32 o2, %5, %4;\ncvt.rn.bf16x2.f32 o3, %7, %6;\n"
      "ld.volatile.shared.b32 %0, [%12];\nld.volatile.shared.b32 %1, [%12+896];\n"
      "ld.volatile.shared.b32 %2, [%12+1792];\nld.volatile.shared.b32 %3, [%12+2688];\n"
      "ld.volatile.shared.b32 %4, [%12+3584];\nld.volatile.shared.b32 %5, [%12+4480];\n"
      "ld.volatile.shared.b32 %6, [%12+5376];\nld.volatile.shared.b32 %7, [%12+6272];\n"
      "st.relaxed.gpu.global.v4.u32 [%9], {o0, o1, o2, o3};\n"
      "ld.relaxed.gpu.global.u32 %8, [%9];\n}\n"
      : "+r"(q[0]), "+r"(q[1]), "+r"(q[2]), "+r"(q[3]), "+r"(q[4]), "+r"(q[5]), "+r"(q[6]), "+r"(q[7]), "=r"(rb)
      : "l"(wp), "r"(__float_as_int(sc)), "r"(qbar), "r"(qaddr), "r"(qpar)
      : "memory");
}

constexpr int PU = 4;
#define HEAVY 0xB6DB4u
__host__ __device__ constexpr int popc(unsigned v) { return v ? (v & 1) + popc(v >> 1) : 0; }
__host__ __device__ constexpr bool heavy(int n) { return (HEAVY >> n) & 1; }
__host__ __device__ constexpr int unit_at(int n) { return PU + popc(HEAVY & ((1u << n) - 1)); }
__host__ __device__ constexpr int emit_slot(int u) {
  if (u < PU) return u == PU - 1 ? 1 : -1;
  for (int n = 2; n < 24; n++)
    if (heavy(n) && unit_at(n) == u) return n;
  return 99;
}
__host__ __device__ constexpr int cmax(int a, int b) { return a > b ? a : b; }
__host__ __device__ constexpr int w_slot(int m) {
  return m == 15 ? cmax(emit_slot(15) + 3, 22) : cmax(2 * m - 5, emit_slot(m) + 3);
}
__host__ __device__ constexpr int q_slot(int u) {
  return u == 6 ? 2 : cmax(q_slot(u - 1) + 1, u - 5 < PU ? 2 : emit_slot(u - 5) + 2);
}
__host__ __device__ constexpr int w_at(int n) {
  for (int m = 2; m < NKB; m++)
    if (w_slot(m) == n) return m;
  return -1;
}
__host__ __device__ constexpr int q_at(int n) {
  for (int u = 6; u < NKB; u++)
    if (q_slot(u) == n) return u;
  return -1;
}
constexpr bool schedule_ok() {
  if (popc(HEAVY) != NKB - PU || (HEAVY & 3) || (HEAVY >> 20)) return false;
  for (int m = 2; m < NKB; m++) {
    if (w_at(w_slot(m)) != m || w_slot(m) > 23) return false;
    if (m < NR && w_slot(m) > 2 * m - 2) return false;
  }
  for (int u = 6; u < NKB; u++)
    if (q_slot(u) + 2 > emit_slot(u - 1)) return false;
  return true;
}
static_assert(schedule_ok(), "bad schedule");
template <int V>
struct IC {
  static constexpr int value = V;
};
template <int I, int N, class F>
__device__ __forceinline__ void static_for(F&& f) {
  if constexpr (I < N) {
    f(IC<I>{});
    static_for<I + 1, N>(f);
  }
}

#define PACE_B 350
#define PACE_Q1 700
#define PACE_Q2 1300
#define PACE_X 1700
#define PF_X 1
#define PF_Q 0

constexpr uint32_t sbase = 1024;

__global__ void __launch_bounds__(256, 1)
fused_kernel(const __grid_constant__ CUtensorMap tm_x, const __grid_constant__ CUtensorMap tm_q,
             const int* __restrict__ qw, const __nv_bfloat16* __restrict__ lut,
             const __nv_bfloat16* __restrict__ scales, __nv_bfloat16* __restrict__ out, uint8_t* scratch) {
  extern __shared__ __align__(1024) uint8_t smem_raw[];
  constexpr uint32_t bars = sbase + SMEM_BAR;
  const int j = blockIdx.x >> 3, it = blockIdx.x & 7;
  const int warp = __shfl_sync(0xffffffffu, threadIdx.x >> 5, 0);
  const int wg = warp >> 2;
  int lane;
  asm volatile("mov.u32 %0, %%laneid;" : "=r"(lane));
  const unsigned t_start = clk32();
  auto pace = [&](unsigned t) {
    while (__any_sync(0xffffffffu, clk32() - t_start < t)) {}
  };
  TL(0); TLG(1);

  uint8_t* const region = scratch + (size_t)j * REGION;
  uint8_t* const wp = region + W_OFF + it * W_KC + (warp * 32 + lane) * 16;
  unsigned* const fl = reinterpret_cast<unsigned*>(region) + lane;
  float lutv, sc;
  unsigned rb;
  const int xrow = it * BM + wg * 128;

  auto w_ptr = [&](int u) { return reinterpret_cast<uint4*>(wp + u * W_STAGE); };
  auto emit_unit = [&](const int (&qq)[8], int u) {
    st_strong128(w_ptr(u), convert_unit(qq, lutv, sc));
    rb = ld_strong(w_ptr(u));
  };
  auto publish = [&](int u, unsigned inc) {
    asm volatile(
        "{\n.reg .pred P, Q;\n"
        "setp.ne.u32 P, %1, 0xffffffff;\n"
        "vote.sync.all.pred P, P, 0xffffffff;\n"
        "setp.eq.and.s32 Q, %2, %3, P;\n"
        "@Q red.relaxed.gpu.global.add.u32 [%0], %4;\n}"
        ::"l"(fl), "r"(rb), "r"(lane), "r"(u), "r"(inc) : "memory");
  };
  auto load_x = [&](int g, int n, int kb, int half) {
    const uint32_t bar = ring(bars + 8 * B_FULLX, n) + g * 64;
    mbar_expect_tx(bar, X_SLICE);
    tma_load_2d(sbase + SMEM_X + (n % XS) * X_SLICE + g * (XS * X_SLICE), &tm_x, kb * BK,
                it * BM + g * 128 + half * 64, bar);
  };
  auto load_q = [&](int u) {
    const uint32_t bar = ring(bars + 8 * B_FULLQ, u);
    mbar_expect_tx(bar, Q_UNIT);
    tma_load_2d(sbase + SMEM_Q + (u & 3) * Q_UNIT, &tm_q, j * BN, u * BK + it * 8, bar);
  };
  auto prefetch_x = [&](int g) {
    if (PF_X) tma_prefetch_2d(&tm_x, (4 * g + (j >> 2)) * BK, it * BM + (j & 3) * 64);
  };
  auto prefetch_q = [&](int u) {
    if (PF_Q) tma_prefetch_2d(&tm_q, j * BN, u * BK + it * 8);
  };

  unsigned ready = 0;
  auto load_w = [&](uint32_t bar, int dst, int src, int bytes) {
    asm volatile("fence.proxy.async.global;" ::: "memory");
    mbar_expect_tx(bar, bytes);
    bulk_load(sbase + SMEM_W + dst, region + W_OFF + src, bytes, bar);
  };
  auto poll = [&]() { ready |= __ballot_sync(0xffffffffu, ld_strong(fl) >= FLAG_FULL); };
  auto wait_ready = [&](int kb) {
    int spins = 0;
    while (!((ready >> kb) & 1)) {
      poll();
      if (++spins > (1 << 22)) __trap();
    }
  };

  uint32_t qbase;
  asm volatile("mov.u32 %0, %1;" : "=r"(qbase) : "r"(sbase + SMEM_Q + warp * 128 + perm32(lane) * 4));
  auto lds_unit = [&](int (&q)[8], int u) {
    ring_wait(bars + 8 * B_FULLQ, u);
#pragma unroll
    for (int i = 0; i < 8; i++) q[i] = lds32(qbase + (u & 3) * Q_UNIT + i * (BN * 4));
  };
  auto arrive_one = [&](uint32_t bar) {
    asm volatile("{\n.reg .pred P;\nelect.sync _|P, 0xffffffff;\n@P mbarrier.arrive.shared::cta.b64 _, [%0];\n}"
                 ::"r"(bar) : "memory");
  };

  int q[8];
  constexpr uint32_t bar_w0a = bars + 8 * B_FULLQ, bar_w0b = bars + 8 * B_FULLW, bar_w1 = bar_w0b + 8;
  unsigned issued = 0;
  auto issue_early = [&]() {
    const unsigned go = ready & ~issued & 3;
    if (go && elect_one()) {
      if (go & 1) load_w(bar_w0b, W_STAGE / 2, W_STAGE / 2, W_STAGE / 2);
      if (go & 2) load_w(bar_w1, W_STAGE, W_STAGE, W_STAGE);
    }
    issued |= go;
  };
  auto poll_until = [&](uint32_t bar) {
    int spins = 0;
    while (issued != 3 && !mbar_test(bar, 0)) {
      if (++spins > (1 << 22)) __trap();
      poll();
      issue_early();
    }
  };
  if (warp == 7) {
    if (smem_u32(smem_raw) != sbase) __trap();
    if (elect_one()) {
      asm volatile("prefetch.tensormap [%0];" ::"l"(&tm_q) : "memory");
      asm volatile("prefetch.tensormap [%0];" ::"l"(&tm_x) : "memory");
#pragma unroll
      for (int i = 0; i < B_COUNT; i++) mbar_init(bars + 8 * i, i >= B_DONE ? 4 : 1);
      asm volatile("fence.mbarrier_init.release.cluster;" ::: "memory");
    }
    __syncwarp();
    rb = ld_strong(fl);
    bar_arrive(0, 256);
    TL(4);
    lutv = 0.f;
    sc = 0.f;
    pace(PACE_Q1);
    if (elect_one()) {
      if (j < 4) prefetch_x(0);
      load_q(1);
    }
    pace(PACE_Q2);
    if (elect_one()) {
      load_q(2);
      if (j >= 4) prefetch_x(0);
    }
    pace(PACE_X);
    if (elect_one()) {
      load_x(0, 0, 0, 0); load_x(1, 0, 0, 0); load_x(0, 1, 0, 1); load_x(1, 1, 0, 1);
    }
    ready = __ballot_sync(0xffffffffu, rb >= FLAG_FULL);
    wait_ready(16);
    if (elect_one()) load_w(bar_w0a, 0, 0, W_STAGE / 2);
    issue_early();
    if (elect_one()) load_q(3);
    TL(2);
    poll_until(bar_w0a);
  } else {
    const int fcol = j * BN + warp * 32 + perm32(lane);
    const int half = wg ^ (it & 1);
    const int kc = half * 4 + (it >> 1);
    if (half) pace(PACE_B);
    load_unit(q, qw + (size_t)(kc * 8) * F_DIM + fcol);
    lutv = __uint_as_float(ldg_u16(lut + (lane & 15)) << 16);
    sc = __uint_as_float(ldg_u16(scales + fcol) << 16);
    uint8_t* p = wp + (kc - it) * W_KC;
    st_strong128(p, convert_unit(q, lutv, sc));
    rb = ld_strong(p);
    TL(2);
    publish(half ? 0 : 16, 2);
    TL(3);
    bar_sync(0, 256);
    lds_unit(q, 1);
    emit_unit(q, 1);
    publish(1, 1);
    TL(4);
  }

  float acc0[112], acc1[112];
  constexpr uint32_t DA_HI = (1u << 30) | (1024 >> 4), DB_HI = (128 >> 4);
  const uint32_t da0 = ((1u << 16) | ((sbase + SMEM_X) >> 4)) + wg * (XS * X_SLICE >> 4);
  constexpr uint32_t db0 = ((W_KC >> 4) << 16) | ((sbase + SMEM_W) >> 4);
  const uint32_t fullx = bars + 8 * B_FULLX + wg * 64, done = bars + 8 * B_DONE + wg * 64;
  const bool x_issuer = (warp & 3) == 3;

  auto mma = [&](float (&acc)[112], int n, int kb, int k0, int k1) {
    const int wslot = kb == 15 ? 4 : (kb & 3);
    wgmma_fence();
#pragma unroll
    for (int k = k0; k < k1; k++)
      wgmma_m64n224k16(acc, make_desc(da0 + (n % XS) * (X_SLICE >> 4) + k * 2, DA_HI),
                       make_desc(db0 + wslot * (W_STAGE >> 4) + k * (2 * W_KC >> 4), DB_HI), kb != 0 || k != 0);
    wgmma_commit();
  };
  auto end_slot = [&](int n) {
    wgmma_wait<1>();
    arrive_one(ring(done, n));
    if (x_issuer) {
      ring_wait(done, n);
      const int m = n + 4, e = (m - 2 * NR) & 3;
      if (elect_one())
        load_x(wg, m, m < 2 * NR ? m >> 1 : e < 2 ? NR + e : NR + 5 - e, m < 2 * NR ? m & 1 : (m - 2 * NR) >> 2);
    }
  };
  auto slot = [&](float (&acc)[112], auto N) {
    constexpr int n = decltype(N)::value;
    constexpr bool hv = heavy(n), pub = n == 2 || heavy(n - 1);
    ring_wait(fullx, n);
    mma(acc, n, n >> 1, 0, 4);
    if (hv && warp < 7) dequant_lookup(q, lutv);
    end_slot(n);
    if (warp < 7) {
      constexpr int u = unit_at(n);
      if (pub) publish(u - 1, 1);
      if (hv) {
        constexpr int un = u + 1 < NKB ? u + 1 : u;
        dequant_finish(q, rb, w_ptr(u), sc, ring(bars + 8 * B_FULLQ, un), un >> 3, qbase + (un & 3) * Q_UNIT);
      }
    } else {
      constexpr int m = w_at(n), u = q_at(n), m_next = w_at(n + 1);
      if (m >= 0 || u >= 0) ring_wait(bars + 8 * B_DONE, n - 1);
      if (m >= 0) {
        ready |= __ballot_sync(0xffffffffu, rb >= FLAG_FULL);
        wait_ready(m);
      }
      if ((m >= 0 || u >= 0 || n == 4 || n == 10) && elect_one()) {
        if (m >= 0) load_w(ring(bars + 8 * B_FULLW, m), (m == 15 ? 4 : m & 3) * W_STAGE, m * W_STAGE, W_STAGE);
        if (u >= 0) load_q(u);
        if (u >= 0 && u + 2 < NKB) prefetch_q(u + 2);
        if (n == 4 || n == 10) prefetch_x(n == 4 ? 2 : 3);
      }
      if (m_next >= 0) rb = ld_strong(fl);
    }
  };

  mbar_wait(bar_w0a, 0);
  mbar_wait(fullx, 0);
  TL(8);
  mma(acc0, 0, 0, 0, 2);
  mbar_wait(fullx + 8, 0);
  mma(acc1, 1, 0, 0, 2);
  arrive_one(done);
  if (warp < 7) {
    lds_unit(q, 2);
    emit_unit(q, 2);
    TL(5);
  } else {
    poll_until(bar_w0b);
    if (elect_one()) {
      load_q(4);
      load_x(0, 2, 1, 0); load_x(1, 2, 1, 0); load_x(0, 3, 1, 1); load_x(1, 3, 1, 1);
    }
  }
  mbar_wait(bar_w0b, 0);
  TL(9);
  mma(acc0, 0, 0, 2, 4);
  mma(acc1, 1, 0, 2, 4);
  if (warp < 7) {
    lds_unit(q, 3);
    publish(2, 1);
    emit_unit(q, 3);
    lds_unit(q, 4);
  } else {
    poll_until(bar_w1);
    TL(3);
    mbar_wait(bars + 8 * B_DONE, 0);
    mbar_wait(done, 0);
    if (elect_one()) {
      load_q(5);
      load_x(0, 4, 2, 0); load_x(1, 4, 2, 0);
      prefetch_x(1);
      prefetch_q(6);
      prefetch_q(7);
    }
  }
  end_slot(1);
  if (warp == 7) rb = ld_strong(fl);

  static_for<1, NR>([&](auto R) {
    constexpr int r = decltype(R)::value;
    ring_wait(bars + 8 * B_FULLW, r);
    TL(8 + 2 * r);
    slot(acc0, IC<2 * r>{});
    TL(9 + 2 * r);
    slot(acc1, IC<2 * r + 1>{});
  });

  __nv_bfloat16* op = out + (size_t)(xrow + (warp & 3) * 16 + (lane >> 2)) * F_DIM + j * BN + (lane & 3) * 8;
  TL(40);
  if (wg == 1) bar_sync(1, 256);
#pragma unroll
  for (int e = 0; e < ENDK; e++) {
    const int kb = e < 2 ? NR + e : NR + 5 - e;
    ring_wait(bars + 8 * B_FULLW, kb);
    ring_wait(fullx, 2 * NR + e);
    mma(acc0, 2 * NR + e, kb, 0, 4);
    if (e == ENDK - 1) bar_arrive(1 + wg, 256);
    end_slot(2 * NR + e);
  }
  wgmma_wait<0>();
  TL(41);
  store_acc(acc0, op);
  TL(42);
  bar_sync(2 + wg, 256);
#pragma unroll
  for (int e = 0; e < ENDK; e++) {
    ring_wait(fullx, 2 * NR + ENDK + e);
    mma(acc1, 2 * NR + ENDK + e, e < 2 ? NR + e : NR + 5 - e, 0, 4);
  }
  if (wg == 0) bar_arrive(3, 256);
  wgmma_wait<0>();
  TL(43);
  store_acc(acc1, op + 64 * F_DIM);
  TL(44);
  if (warp == 0 && lane == 0) {
    if (atomicAdd(fl + 17, 1u) == NI - 1) {
#pragma unroll
      for (int u = 0; u <= 17; u++) fl[u] = 0;
    }
  }
}

typedef CUresult (*EncodeTiledFn)(CUtensorMap*, CUtensorMapDataType, cuuint32_t, void*, const cuuint64_t*,
                                  const cuuint64_t*, const cuuint32_t*, const cuuint32_t*, CUtensorMapInterleave,
                                  CUtensorMapSwizzle, CUtensorMapL2promotion, CUtensorMapFloatOOBfill);

}

#define XPROMO CU_TENSOR_MAP_L2_PROMOTION_L2_128B
extern "C" void kernel_launch(void* const* d_in, const int* in_sizes, int n_in, void* d_out, int out_size) {
  const __nv_bfloat16* x = (const __nv_bfloat16*)d_in[0];
  const int* qw = (const int*)d_in[1];
  const __nv_bfloat16* lut = (const __nv_bfloat16*)d_in[2];
  const __nv_bfloat16* scales = (const __nv_bfloat16*)d_in[3];
  __nv_bfloat16* out = (__nv_bfloat16*)d_out;

  static EncodeTiledFn enc = nullptr;
  static uint8_t* p_scr = nullptr;
  if (!enc) {
    void* fn = nullptr;
    cudaDriverEntryPointQueryResult qr;
    cudaGetDriverEntryPoint("cuTensorMapEncodeTiled", &fn, cudaEnableDefault, &qr);
    enc = (EncodeTiledFn)fn;
    void* p = nullptr;
    cudaGetSymbolAddress(&p, g_scratch);
    p_scr = (uint8_t*)(((uintptr_t)p + REGION - 1) & ~(uintptr_t)(REGION - 1));
    cudaFuncSetAttribute(fused_kernel, cudaFuncAttributeMaxDynamicSharedMemorySize, SMEM_TOTAL);
  }
  CUtensorMap tm_x, tm_q;
  cuuint32_t estr[2] = {1, 1};
  {
    cuuint64_t gdim[2] = {(cuuint64_t)D_DIM, (cuuint64_t)S_DIM};
    cuuint64_t gstr[1] = {(cuuint64_t)D_DIM * 2};
    cuuint32_t box[2] = {(cuuint32_t)BK, 64};
    enc(&tm_x, CU_TENSOR_MAP_DATA_TYPE_BFLOAT16, 2, (void*)x, gdim, gstr, box, estr, CU_TENSOR_MAP_INTERLEAVE_NONE,
        CU_TENSOR_MAP_SWIZZLE_128B, XPROMO, CU_TENSOR_MAP_FLOAT_OOB_FILL_NONE);
  }
  {
    cuuint64_t gdim[2] = {(cuuint64_t)F_DIM, (cuuint64_t)D_DIM};
    cuuint64_t gstr[1] = {(cuuint64_t)F_DIM * 4};
    cuuint32_t box[2] = {(cuuint32_t)BN, 8};
    enc(&tm_q, CU_TENSOR_MAP_DATA_TYPE_INT32, 2, (void*)qw, gdim, gstr, box, estr, CU_TENSOR_MAP_INTERLEAVE_NONE,
        CU_TENSOR_MAP_SWIZZLE_NONE, CU_TENSOR_MAP_L2_PROMOTION_NONE, CU_TENSOR_MAP_FLOAT_OOB_FILL_NONE);
  }
  fused_kernel<<<NI * NJ, 256, SMEM_TOTAL, cudaStreamPerThread>>>(tm_x, tm_q, qw, lut, scales, out, p_scr);
}
```

```cpp
#include <cuda_runtime.h>
#include <cuda_bf16.h>
#include <cuda.h>
#include <stdint.h>

namespace {

constexpr int S_DIM = 2048, D_DIM = 1024, F_DIM = 3584;
constexpr int BM = 256, BN = 224, BK = 64;
constexpr int NKB = D_DIM / BK;
constexpr int NJ = F_DIM / BN;
constexpr int NI = S_DIM / BM;
constexpr int WS = 4;
constexpr int XS = 5;
constexpr int ENDK = 4;
constexpr int NR = NKB - ENDK;
constexpr int X_SLICE = 64 * BK * 2;
constexpr int W_STAGE = BN * BK * 2;
constexpr int W_KC = BN * 16;

constexpr int REGION = 512 * 1024;
__device__ uint4 g_scratch[(NJ + 1) * REGION / 16];

__device__ __forceinline__ uint32_t smem_u32(const void* p) { return (uint32_t)__cvta_generic_to_shared(p); }
__device__ __forceinline__ unsigned clk32() {
  unsigned c;
  asm volatile("mov.u32 %0, %%clock;" : "=r"(c)::"memory");
  return c;
}
__device__ __forceinline__ bool elect_one() {
  uint32_t p;
  asm volatile("{\n.reg .pred P;\nelect.sync _|P, 0xffffffff;\nselp.b32 %0, 1, 0, P;\n}" : "=r"(p));
  return p != 0;
}
__device__ __forceinline__ void mbar_init(uint32_t bar, uint32_t cnt) {
  asm volatile("mbarrier.init.shared::cta.b64 [%0], %1;" ::"r"(bar), "r"(cnt) : "memory");
}
__device__ __forceinline__ void mbar_expect_tx(uint32_t bar, uint32_t bytes) {
  asm volatile("mbarrier.arrive.expect_tx.shared::cta.b64 _, [%0], %1;" ::"r"(bar), "r"(bytes) : "memory");
}
__device__ __forceinline__ void mbar_arrive(uint32_t bar) {
  asm volatile("mbarrier.arrive.shared::cta.b64 _, [%0];" ::"r"(bar) : "memory");
}
__device__ __forceinline__ bool mbar_test(uint32_t bar, uint32_t parity) {
  uint32_t ok;
  asm volatile(
      "{\n.reg .pred p;\nmbarrier.test_wait.parity.shared::cta.b64 p, [%1], %2;\nselp.b32 %0, 1, 0, p;\n}\n"
      : "=r"(ok) : "r"(bar), "r"(parity) : "memory");
  return ok != 0;
}
__device__ __forceinline__ void mbar_wait(uint32_t bar, uint32_t parity) {
  asm volatile(
      "{\n.reg .pred p;\n"
      "LAB_WAIT:\n"
      "mbarrier.try_wait.parity.shared::cta.b64 p, [%0], %1;\n"
      "@p bra LAB_DONE;\n"
      "bra LAB_WAIT;\n"
      "LAB_DONE:\n}\n" ::"r"(bar), "r"(parity) : "memory");
}
__device__ __forceinline__ uint32_t ring(uint32_t base, int i) { return base + 8 * (i & 7); }
__device__ __forceinline__ void ring_wait(uint32_t base, int i) { mbar_wait(ring(base, i), (i >> 3) & 1); }
__device__ __forceinline__ void tma_load_2d(uint32_t dst, const CUtensorMap* tm, int c0, int c1, uint32_t bar) {
  asm volatile(
      "cp.async.bulk.tensor.2d.shared::cluster.global.mbarrier::complete_tx::bytes [%0], [%1, {%3, %4}], [%2];"
      ::"r"(dst), "l"(tm), "r"(bar), "r"(c0), "r"(c1) : "memory");
}
__device__ __forceinline__ void tma_prefetch_2d(const CUtensorMap* tm, int c0, int c1) {
  asm volatile("cp.async.bulk.prefetch.tensor.2d.L2.global [%0, {%1, %2}];" ::"l"(tm), "r"(c0), "r"(c1) : "memory");
}
__device__ __forceinline__ void bulk_load(uint32_t dst, const void* src, uint32_t bytes, uint32_t bar) {
  asm volatile(
      "cp.async.bulk.shared::cluster.global.mbarrier::complete_tx::bytes [%0], [%1], %2, [%3];"
      ::"r"(dst), "l"(src), "r"(bytes), "r"(bar) : "memory");
}
__device__ __forceinline__ int ldg_stream(const int* p) {
  int v;
  asm volatile("ld.global.L1::no_allocate.b32 %0, [%1];" : "=r"(v) : "l"(p) : "memory");
  return v;
}
__device__ __forceinline__ uint32_t ldg_u16(const void* p) {
  uint32_t v;
  asm volatile("ld.global.u16 %0, [%1];" : "=r"(v) : "l"(p) : "memory");
  return v;
}
__device__ __forceinline__ int lds32(uint32_t addr) {
  int v;
  asm volatile("ld.shared.b32 %0, [%1];" : "=r"(v) : "r"(addr) : "memory");
  return v;
}
__device__ __forceinline__ uint64_t make_desc(uint32_t lo, uint32_t hi) {
  uint64_t d;
  asm("mov.b64 %0, {%1, %2};" : "=l"(d) : "r"(lo), "r"(hi));
  return d;
}
__device__ __forceinline__ unsigned ld_strong(const void* p) {
  unsigned v;
  asm volatile("ld.relaxed.gpu.global.u32 %0, [%1];" : "=r"(v) : "l"(p) : "memory");
  return v;
}
__device__ __forceinline__ void st_strong128(void* p, uint4 v) {
  asm volatile("st.relaxed.gpu.global.v4.u32 [%0], {%1, %2, %3, %4};" ::"l"(p), "r"(v.x), "r"(v.y), "r"(v.z), "r"(v.w)
               : "memory");
}
__device__ __forceinline__ void wgmma_fence() { asm volatile("wgmma.fence.sync.aligned;" ::: "memory"); }
__device__ __forceinline__ void wgmma_commit() { asm volatile("wgmma.commit_group.sync.aligned;" ::: "memory"); }
template <int N>
__device__ __forceinline__ void wgmma_wait() { asm volatile("wgmma.wait_group.sync.aligned %0;" ::"n"(N) : "memory"); }
__device__ __forceinline__ void bar_sync(int id, int n) { asm volatile("bar.sync %0, %1;" ::"r"(id), "r"(n) : "memory"); }
__device__ __forceinline__ void bar_arrive(int id, int n) { asm volatile("bar.arrive %0, %1;" ::"r"(id), "r"(n) : "memory"); }

__device__ __forceinline__ void wgmma_m64n224k16(float (&d)[112], uint64_t da, uint64_t db, int scale_d) {
  asm volatile(
    "{\n.reg .pred p;\nsetp.ne.b32 p, %114, 0;\n"
    "wgmma.mma_async.sync.aligned.m64n224k16.f32.bf16.bf16 "
    "{%0, %1, %2, %3, %4, %5, %6, %7, %8, %9, %10, %11, %12, %13, %14, %15, "
    "%16, %17, %18, %19, %20, %21, %22, %23, %24, %25, %26, %27, %28, %29, %30, %31, "
    "%32, %33, %34, %35, %36, %37, %38, %39, %40, %41, %42, %43, %44, %45, %46, %47, "
    "%48, %49, %50, %51, %52, %53, %54, %55, %56, %57, %58, %59, %60, %61, %62, %63, "
    "%64, %65, %66, %67, %68, %69, %70, %71, %72, %73, %74, %75, %76, %77, %78, %79, "
    "%80, %81, %82, %83, %84, %85, %86, %87, %88, %89, %90, %91, %92, %93, %94, %95, "
    "%96, %97, %98, %99, %100, %101, %102, %103, %104, %105, %106, %107, %108, %109, %110, %111}, "
    "%112, %113, p, 1, 1, 0, 0;\n}\n"
    : "+f"(d[0]), "+f"(d[1]), "+f"(d[2]), "+f"(d[3]), "+f"(d[4]), "+f"(d[5]), "+f"(d[6]), "+f"(d[7]),
      "+f"(d[8]), "+f"(d[9]), "+f"(d[10]), "+f"(d[11]), "+f"(d[12]), "+f"(d[13]), "+f"(d[14]), "+f"(d[15]),
      "+f"(d[16]), "+f"(d[17]), "+f"(d[18]), "+f"(d[19]), "+f"(d[20]), "+f"(d[21]), "+f"(d[22]), "+f"(d[23]),
      "+f"(d[24]), "+f"(d[25]), "+f"(d[26]), "+f"(d[27]), "+f"(d[28]), "+f"(d[29]), "+f"(d[30]), "+f"(d[31]),
      "+f"(d[32]), "+f"(d[33]), "+f"(d[34]), "+f"(d[35]), "+f"(d[36]), "+f"(d[37]), "+f"(d[38]), "+f"(d[39]),
      "+f"(d[40]), "+f"(d[41]), "+f"(d[42]), "+f"(d[43]), "+f"(d[44]), "+f"(d[45]), "+f"(d[46]), "+f"(d[47]),
      "+f"(d[48]), "+f"(d[49]), "+f"(d[50]), "+f"(d[51]), "+f"(d[52]), "+f"(d[53]), "+f"(d[54]), "+f"(d[55]),
      "+f"(d[56]), "+f"(d[57]), "+f"(d[58]), "+f"(d[59]), "+f"(d[60]), "+f"(d[61]), "+f"(d[62]), "+f"(d[63]),
      "+f"(d[64]), "+f"(d[65]), "+f"(d[66]), "+f"(d[67]), "+f"(d[68]), "+f"(d[69]), "+f"(d[70]), "+f"(d[71]),
      "+f"(d[72]), "+f"(d[73]), "+f"(d[74]), "+f"(d[75]), "+f"(d[76]), "+f"(d[77]), "+f"(d[78]), "+f"(d[79]),
      "+f"(d[80]), "+f"(d[81]), "+f"(d[82]), "+f"(d[83]), "+f"(d[84]), "+f"(d[85]), "+f"(d[86]), "+f"(d[87]),
      "+f"(d[88]), "+f"(d[89]), "+f"(d[90]), "+f"(d[91]), "+f"(d[92]), "+f"(d[93]), "+f"(d[94]), "+f"(d[95]),
      "+f"(d[96]), "+f"(d[97]), "+f"(d[98]), "+f"(d[99]), "+f"(d[100]), "+f"(d[101]), "+f"(d[102]), "+f"(d[103]),
      "+f"(d[104]), "+f"(d[105]), "+f"(d[106]), "+f"(d[107]), "+f"(d[108]), "+f"(d[109]), "+f"(d[110]), "+f"(d[111])
    : "l"(da), "l"(db), "r"(scale_d));
}

__device__ __forceinline__ uint32_t pack_bf16(float lo, float hi) {
  uint32_t r;
  asm("cvt.rn.bf16x2.f32 %0, %1, %2;" : "=r"(r) : "f"(hi), "f"(lo));
  return r;
}

__device__ __forceinline__ int perm32(int n) { return (n & ~30) | ((n & 6) << 2) | ((n >> 2) & 6); }

constexpr int SMEM_X = 0;
constexpr int SMEM_W = 2 * XS * X_SLICE;
constexpr int SMEM_Q = SMEM_W + WS * W_STAGE;
constexpr int Q_UNIT = 8 * BN * 4;
constexpr int SMEM_BAR = SMEM_Q + W_STAGE;
constexpr int B_FULLW = 0, B_FULLQ = 8, B_FULLX = 16, B_DONE = 32, B_COUNT = 48;
constexpr int SMEM_TL = SMEM_BAR + B_COUNT * 8;
constexpr int SMEM_TOTAL = SMEM_TL + 2048;
constexpr int W_OFF = 128;
constexpr unsigned FLAG_FULL = NI * 7;

#define TL(i)
#define TLG(i)

__device__ __forceinline__ void store_acc(const float (&a)[112], __nv_bfloat16* p) {
#pragma unroll
  for (int J = 0; J < 7; J++) {
    uint4 v0, v1;
    v0.x = pack_bf16(a[16 * J + 0], a[16 * J + 1]);
    v0.y = pack_bf16(a[16 * J + 4], a[16 * J + 5]);
    v0.z = pack_bf16(a[16 * J + 8], a[16 * J + 9]);
    v0.w = pack_bf16(a[16 * J + 12], a[16 * J + 13]);
    v1.x = pack_bf16(a[16 * J + 2], a[16 * J + 3]);
    v1.y = pack_bf16(a[16 * J + 6], a[16 * J + 7]);
    v1.z = pack_bf16(a[16 * J + 10], a[16 * J + 11]);
    v1.w = pack_bf16(a[16 * J + 14], a[16 * J + 15]);
    *reinterpret_cast<uint4*>(p + 32 * J) = v0;
    *reinterpret_cast<uint4*>(p + 8 * F_DIM + 32 * J) = v1;
  }
}

__device__ __forceinline__ void load_unit(int (&q)[8], const int* p) {
#pragma unroll
  for (int i = 0; i < 8; i++) q[i] = ldg_stream(p + i * F_DIM);
}
__device__ __forceinline__ uint4 convert_unit(const int (&q)[8], float lutv, float sc) {
  float v[8];
#pragma unroll
  for (int i = 0; i < 8; i++) v[i] = __shfl_sync(0xffffffffu, lutv, q[i]) * sc;
  uint4 o;
  o.x = pack_bf16(v[0], v[1]);
  o.y = pack_bf16(v[2], v[3]);
  o.z = pack_bf16(v[4], v[5]);
  o.w = pack_bf16(v[6], v[7]);
  return o;
}

__device__ __forceinline__ void dequant_lookup(int (&q)[8], float lutv) {
  asm volatile(
      "shfl.sync.idx.b32 %0, %8, %0, 31, 0xffffffff;\n"
      "shfl.sync.idx.b32 %1, %8, %1, 31, 0xffffffff;\n"
      "shfl.sync.idx.b32 %2, %8, %2, 31, 0xffffffff;\n"
      "shfl.sync.idx.b32 %3, %8, %3, 31, 0xffffffff;\n"
      "shfl.sync.idx.b32 %4, %8, %4, 31, 0xffffffff;\n"
      "shfl.sync.idx.b32 %5, %8, %5, 31, 0xffffffff;\n"
      "shfl.sync.idx.b32 %6, %8, %6, 31, 0xffffffff;\n"
      "shfl.sync.idx.b32 %7, %8, %7, 31, 0xffffffff;\n"
      : "+r"(q[0]), "+r"(q[1]), "+r"(q[2]), "+r"(q[3]), "+r"(q[4]), "+r"(q[5]), "+r"(q[6]), "+r"(q[7])
      : "r"(__float_as_int(lutv)));
}
__device__ __forceinline__ void dequant_finish(int (&q)[8], unsigned& rb, uint4* wp, float sc, uint32_t qbar,
                                               uint32_t qpar, uint32_t qaddr) {
  asm volatile(
      "{\n.reg .pred W;\n.reg .b32 o0, o1, o2, o3;\n"
      "DQ_WAIT:\n"
      "mbarrier.try_wait.parity.shared::cta.b64 W, [%11], %13;\n"
      "@!W bra DQ_WAIT;\n"
      "mul.rn.f32 %0, %0, %10;\nmul.rn.f32 %1, %1, %10;\nmul.rn.f32 %2, %2, %10;\nmul.rn.f32 %3, %3, %10;\n"
      "mul.rn.f32 %4, %4, %10;\nmul.rn.f32 %5, %5, %10;\nmul.rn.f32 %6, %6, %10;\nmul.rn.f32 %7, %7, %10;\n"
      "cvt.rn.bf16x2.f32 o0, %1, %0;\ncvt.rn.bf16x2.f32 o1, %3, %2;\n"
      "cvt.rn.bf16x2.f32 o2, %5, %4;\ncvt.rn.bf16x2.f32 o3, %7, %6;\n"
      "ld.volatile.shared.b32 %0, [%12];\nld.volatile.shared.b32 %1, [%12+896];\n"
      "ld.volatile.shared.b32 %2, [%12+1792];\nld.volatile.shared.b32 %3, [%12+2688];\n"
      "ld.volatile.shared.b32 %4, [%12+3584];\nld.volatile.shared.b32 %5, [%12+4480];\n"
      "ld.volatile.shared.b32 %6, [%12+5376];\nld.volatile.shared.b32 %7, [%12+6272];\n"
      "st.relaxed.gpu.global.v4.u32 [%9], {o0, o1, o2, o3};\n"
      "ld.relaxed.gpu.global.u32 %8, [%9];\n}\n"
      : "+r"(q[0]), "+r"(q[1]), "+r"(q[2]), "+r"(q[3]), "+r"(q[4]), "+r"(q[5]), "+r"(q[6]), "+r"(q[7]), "=r"(rb)
      : "l"(wp), "r"(__float_as_int(sc)), "r"(qbar), "r"(qaddr), "r"(qpar)
      : "memory");
}

constexpr int PU = 4;
#define HEAVY 0xB6DB4u
__host__ __device__ constexpr int popc(unsigned v) { return v ? (v & 1) + popc(v >> 1) : 0; }
__host__ __device__ constexpr bool heavy(int n) { return (HEAVY >> n) & 1; }
__host__ __device__ constexpr int unit_at(int n) { return PU + popc(HEAVY & ((1u << n) - 1)); }
__host__ __device__ constexpr int emit_slot(int u) {
  if (u < PU) return u == PU - 1 ? 1 : -1;
  for (int n = 2; n < 24; n++)
    if (heavy(n) && unit_at(n) == u) return n;
  return 99;
}
__host__ __device__ constexpr int cmax(int a, int b) { return a > b ? a : b; }
__host__ __device__ constexpr int w_slot(int m) {
  return m == 15 ? cmax(emit_slot(15) + 3, 22) : cmax(2 * m - 5, emit_slot(m) + 3);
}
__host__ __device__ constexpr int q_slot(int u) {
  return u == 6 ? 2 : cmax(q_slot(u - 1) + 1, u - 5 < PU ? 2 : emit_slot(u - 5) + 2);
}
__host__ __device__ constexpr int w_at(int n) {
  for (int m = 2; m < NKB; m++)
    if (w_slot(m) == n) return m;
  return -1;
}
__host__ __device__ constexpr int q_at(int n) {
  for (int u = 6; u < NKB; u++)
    if (q_slot(u) == n) return u;
  return -1;
}
constexpr bool schedule_ok() {
  if (popc(HEAVY) != NKB - PU || (HEAVY & 3) || (HEAVY >> 20)) return false;
  for (int m = 2; m < NKB; m++) {
    if (w_at(w_slot(m)) != m || w_slot(m) > 23) return false;
    if (m < NR && w_slot(m) > 2 * m - 2) return false;
  }
  for (int u = 6; u < NKB; u++)
    if (q_slot(u) + 2 > emit_slot(u - 1)) return false;
  return true;
}
static_assert(schedule_ok(), "bad schedule");
template <int V>
struct IC {
  static constexpr int value = V;
};
template <int I, int N, class F>
__device__ __forceinline__ void static_for(F&& f) {
  if constexpr (I < N) {
    f(IC<I>{});
    static_for<I + 1, N>(f);
  }
}

#define PACE_B 350
#define PACE_Q1 700
#define PACE_Q2 1300
#define PACE_Q3 1900
#define PACE_X 450
#define X_FIRST (PACE_X < PACE_Q1)
#define PF_X 0
#define PF_Q 0

constexpr uint32_t sbase = 1024;

__global__ void __launch_bounds__(256, 1)
fused_kernel(const int* __restrict__ qw, const __nv_bfloat16* __restrict__ lut,
             const __nv_bfloat16* __restrict__ scales, __nv_bfloat16* __restrict__ out, uint8_t* scratch,
             const __grid_constant__ CUtensorMap tm_x, const __grid_constant__ CUtensorMap tm_q) {
  extern __shared__ __align__(1024) uint8_t smem_raw[];
  constexpr uint32_t bars = sbase + SMEM_BAR;
  const int j = blockIdx.x >> 3, it = blockIdx.x & 7;
  const int warp = __shfl_sync(0xffffffffu, threadIdx.x >> 5, 0);
  const int wg = warp >> 2;
  int lane;
  asm volatile("mov.u32 %0, %%laneid;" : "=r"(lane));
  const unsigned t_start = clk32();
  auto pace = [&](unsigned t) {
    while (__any_sync(0xffffffffu, clk32() - t_start < t)) {}
  };
  TL(0); TLG(1);

  uint8_t* const region = scratch + (size_t)j * REGION;
  uint8_t* const wp = region + W_OFF + it * W_KC + (warp * 32 + lane) * 16;
  unsigned* const fl = reinterpret_cast<unsigned*>(region) + lane;
  float lutv, sc;
  unsigned rb;
  const int xrow = it * BM + wg * 128;

  auto w_ptr = [&](int u) { return reinterpret_cast<uint4*>(wp + u * W_STAGE); };
  auto emit_unit = [&](const int (&qq)[8], int u) {
    st_strong128(w_ptr(u), convert_unit(qq, lutv, sc));
    rb = ld_strong(w_ptr(u));
  };
  auto publish = [&](int u, unsigned inc) {
    asm volatile(
        "{\n.reg .pred P, Q;\n"
        "setp.ne.u32 P, %1, 0xffffffff;\n"
        "vote.sync.all.pred P, P, 0xffffffff;\n"
        "setp.eq.and.s32 Q, %2, %3, P;\n"
        "@Q red.relaxed.gpu.global.add.u32 [%0], %4;\n}"
        ::"l"(fl), "r"(rb), "r"(lane), "r"(u), "r"(inc) : "memory");
  };
  auto load_x = [&](int g, int n, int kb, int half) {
    const uint32_t bar = ring(bars + 8 * B_FULLX, n) + g * 64;
    mbar_expect_tx(bar, X_SLICE);
    tma_load_2d(sbase + SMEM_X + (n % XS) * X_SLICE + g * (XS * X_SLICE), &tm_x, kb * BK,
                it * BM + g * 128 + half * 64, bar);
  };
  auto load_q = [&](int u) {
    const uint32_t bar = ring(bars + 8 * B_FULLQ, u);
    mbar_expect_tx(bar, Q_UNIT);
    tma_load_2d(sbase + SMEM_Q + (u & 3) * Q_UNIT, &tm_q, j * BN, u * BK + it * 8, bar);
  };
  auto prefetch_x = [&](int g) {
    if (PF_X) tma_prefetch_2d(&tm_x, (4 * g + (j >> 2)) * BK, it * BM + (j & 3) * 64);
  };
  auto prefetch_q = [&](int u) {
    if (PF_Q) tma_prefetch_2d(&tm_q, j * BN, u * BK + it * 8);
  };

  unsigned ready = 0;
  auto load_w = [&](uint32_t bar, int dst, int src, int bytes) {
    asm volatile("fence.proxy.async.global;" ::: "memory");
    mbar_expect_tx(bar, bytes);
    bulk_load(sbase + SMEM_W + dst, region + W_OFF + src, bytes, bar);
  };
  auto poll = [&]() { ready |= __ballot_sync(0xffffffffu, ld_strong(fl) >= FLAG_FULL); };
  auto wait_ready = [&](int kb) {
    int spins = 0;
    while (!((ready >> kb) & 1)) {
      poll();
      if (++spins > (1 << 22)) __trap();
    }
  };

  uint32_t qbase;
  asm volatile("mov.u32 %0, %1;" : "=r"(qbase) : "r"(sbase + SMEM_Q + warp * 128 + perm32(lane) * 4));
  auto lds_unit = [&](int (&q)[8], int u) {
    ring_wait(bars + 8 * B_FULLQ, u);
#pragma unroll
    for (int i = 0; i < 8; i++) q[i] = lds32(qbase + (u & 3) * Q_UNIT + i * (BN * 4));
  };
  auto arrive_one = [&](uint32_t bar) {
    asm volatile("{\n.reg .pred P;\nelect.sync _|P, 0xffffffff;\n@P mbarrier.arrive.shared::cta.b64 _, [%0];\n}"
                 ::"r"(bar) : "memory");
  };

  int q[8];
  constexpr uint32_t bar_w0a = bars + 8 * B_FULLQ, bar_w0b = bars + 8 * B_FULLW, bar_w1 = bar_w0b + 8;
  unsigned issued = 0;
  auto issue_early = [&]() {
    const unsigned go = ready & ~issued & 3;
    if (go && elect_one()) {
      if (go & 1) load_w(bar_w0b, W_STAGE / 2, W_STAGE / 2, W_STAGE / 2);
      if (go & 2) {
        load_w(bar_w1, W_STAGE, W_STAGE, W_STAGE);
        load_x(0, 2, 1, 0); load_x(1, 2, 1, 0); load_x(0, 3, 1, 1); load_x(1, 3, 1, 1);
      }
    }
    issued |= go;
  };
  auto poll_until = [&](uint32_t bar) {
    int spins = 0;
    while (issued != 3 && !mbar_test(bar, 0)) {
      if (++spins > (1 << 22)) __trap();
      poll();
      issue_early();
    }
  };
  if (warp == 7) {
    if (elect_one()) {
#pragma unroll
      for (int i = 0; i < B_COUNT; i++) mbar_init(bars + 8 * i, i >= B_DONE ? 4 : 1);
      asm volatile("fence.mbarrier_init.release.cluster;" ::: "memory");
    }
    __syncwarp();
    rb = ld_strong(fl);
    bar_arrive(0, 256);
    TL(4);
    lutv = 0.f;
    sc = 0.f;
    if (smem_u32(smem_raw) != sbase) __trap();
    if (X_FIRST) {
      pace(PACE_X);
      if (elect_one()) {
        load_x(0, 0, 0, 0); load_x(1, 0, 0, 0); load_x(0, 1, 0, 1); load_x(1, 1, 0, 1);
      }
    }
    pace(PACE_Q1);
    if (elect_one()) load_q(1);
    if (!X_FIRST) {
      pace(PACE_X);
      if (elect_one()) {
        load_x(0, 0, 0, 0); load_x(1, 0, 0, 0); load_x(0, 1, 0, 1); load_x(1, 1, 0, 1);
      }
    }
    pace(PACE_Q2);
    if (elect_one()) {
      load_q(2);
      if (j >= 4) prefetch_x(0);
    }
    if (PACE_Q3) {
      pace(PACE_Q3);
      if (elect_one()) load_q(3);
    }
    ready = __ballot_sync(0xffffffffu, rb >= FLAG_FULL);
    wait_ready(16);
    if (elect_one()) load_w(bar_w0a, 0, 0, W_STAGE / 2);
    issue_early();
    if (elect_one()) {
      if (!PACE_Q3) load_q(3);
      load_q(4);
    }
    TL(2);
    poll_until(bar_w0a);
  } else {
    const int fcol = j * BN + warp * 32 + perm32(lane);
    const int half = wg ^ (it & 1);
    const int kc = half * 4 + (it >> 1);
    if (half) {
      if ((warp & 3) == 0 && elect_one()) {
        asm volatile("prefetch.tensormap [%0];" ::"l"(&tm_x) : "memory");
        asm volatile("prefetch.tensormap [%0];" ::"l"(&tm_q) : "memory");
      }
      pace(PACE_B);
    }
    load_unit(q, qw + (size_t)(kc * 8) * F_DIM + fcol);
    lutv = __uint_as_float(ldg_u16(lut + (lane & 15)) << 16);
    sc = __uint_as_float(ldg_u16(scales + fcol) << 16);
    uint8_t* p = wp + (kc - it) * W_KC;
    st_strong128(p, convert_unit(q, lutv, sc));
    rb = ld_strong(p);
    TL(2);
    publish(half ? 0 : 16, 2);
    TL(3);
    bar_sync(0, 256);
    lds_unit(q, 1);
    emit_unit(q, 1);
    publish(1, 1);
    TL(4);
  }

  float acc0[112], acc1[112];
  constexpr uint32_t DA_HI = (1u << 30) | (1024 >> 4), DB_HI = (128 >> 4);
  const uint32_t da0 = ((1u << 16) | ((sbase + SMEM_X) >> 4)) + wg * (XS * X_SLICE >> 4);
  constexpr uint32_t db0 = ((W_KC >> 4) << 16) | ((sbase + SMEM_W) >> 4);
  const uint32_t fullx = bars + 8 * B_FULLX + wg * 64, done = bars + 8 * B_DONE + wg * 64;
  const bool x_issuer = (warp & 3) == 3;

  auto mma = [&](float (&acc)[112], int n, int kb, int k0, int k1) {
    const int wslot = kb == 15 ? 4 : (kb & 3);
    wgmma_fence();
#pragma unroll
    for (int k = k0; k < k1; k++)
      wgmma_m64n224k16(acc, make_desc(da0 + (n % XS) * (X_SLICE >> 4) + k * 2, DA_HI),
                       make_desc(db0 + wslot * (W_STAGE >> 4) + k * (2 * W_KC >> 4), DB_HI), kb != 0 || k != 0);
    wgmma_commit();
  };
  auto end_slot = [&](int n) {
    wgmma_wait<1>();
    arrive_one(ring(done, n));
    if (x_issuer) {
      ring_wait(done, n);
      const int m = n + 4, e = (m - 2 * NR) & 3;
      if (elect_one())
        load_x(wg, m, m < 2 * NR ? m >> 1 : e < 2 ? NR + e : NR + 5 - e, m < 2 * NR ? m & 1 : (m - 2 * NR) >> 2);
    }
  };
  auto slot = [&](float (&acc)[112], auto N) {
    constexpr int n = decltype(N)::value;
    constexpr bool hv = heavy(n), pub = n == 2 || heavy(n - 1);
    ring_wait(fullx, n);
    mma(acc, n, n >> 1, 0, 4);
    if (hv && warp < 7) dequant_lookup(q, lutv);
    end_slot(n);
    if (warp < 7) {
      constexpr int u = unit_at(n);
      if (pub) publish(u - 1, 1);
      if (hv) {
        constexpr int un = u + 1 < NKB ? u + 1 : u;
        dequant_finish(q, rb, w_ptr(u), sc, ring(bars + 8 * B_FULLQ, un), un >> 3, qbase + (un & 3) * Q_UNIT);
      }
    } else {
      constexpr int m = w_at(n), u = q_at(n), m_next = w_at(n + 1);
      if (m >= 0 || u >= 0) ring_wait(bars + 8 * B_DONE, n - 1);
      if (m >= 0) {
        ready |= __ballot_sync(0xffffffffu, rb >= FLAG_FULL);
        wait_ready(m);
      }
      if ((m >= 0 || u >= 0 || n == 4 || n == 10) && elect_one()) {
        if (m >= 0) load_w(ring(bars + 8 * B_FULLW, m), (m == 15 ? 4 : m & 3) * W_STAGE, m * W_STAGE, W_STAGE);
        if (u >= 0) load_q(u);
        if (u >= 0 && u + 2 < NKB) prefetch_q(u + 2);
        if (n == 4 || n == 10) prefetch_x(n == 4 ? 2 : 3);
      }
      if (m_next >= 0) rb = ld_strong(fl);
    }
  };

  mbar_wait(bar_w0a, 0);
  mbar_wait(fullx, 0);
  TL(8);
  mma(acc0, 0, 0, 0, 2);
  mbar_wait(fullx + 8, 0);
  mma(acc1, 1, 0, 0, 2);
  arrive_one(done);
  if (warp < 7) {
    lds_unit(q, 2);
    emit_unit(q, 2);
    TL(5);
  } else {
    if (issued != 3) {
      poll();
      issue_early();
    }
    poll_until(bar_w0b);
  }
  mbar_wait(bar_w0b, 0);
  TL(9);
  mma(acc0, 0, 0, 2, 4);
  mma(acc1, 1, 0, 2, 4);
  if (warp < 7) {
    lds_unit(q, 3);
    publish(2, 1);
    emit_unit(q, 3);
    lds_unit(q, 4);
  } else {
    poll_until(bar_w1);
    TL(3);
    mbar_wait(bars + 8 * B_DONE, 0);
    mbar_wait(done, 0);
    if (elect_one()) {
      load_q(5);
      load_x(0, 4, 2, 0); load_x(1, 4, 2, 0);
      prefetch_x(1);
      prefetch_q(6);
      prefetch_q(7);
    }
  }
  end_slot(1);
  if (warp == 7) rb = ld_strong(fl);

  static_for<1, NR>([&](auto R) {
    constexpr int r = decltype(R)::value;
    ring_wait(bars + 8 * B_FULLW, r);
    TL(8 + 2 * r);
    slot(acc0, IC<2 * r>{});
    TL(9 + 2 * r);
    slot(acc1, IC<2 * r + 1>{});
  });

  __nv_bfloat16* op = out + (size_t)(xrow + (warp & 3) * 16 + (lane >> 2)) * F_DIM + j * BN + (lane & 3) * 8;
  TL(40);
  if (wg == 1) bar_sync(1, 256);
#pragma unroll
  for (int e = 0; e < ENDK; e++) {
    const int kb = e < 2 ? NR + e : NR + 5 - e;
    ring_wait(bars + 8 * B_FULLW, kb);
    ring_wait(fullx, 2 * NR + e);
    mma(acc0, 2 * NR + e, kb, 0, 4);
    if (e == ENDK - 1) bar_arrive(1 + wg, 256);
    end_slot(2 * NR + e);
  }
  wgmma_wait<0>();
  TL(41);
  store_acc(acc0, op);
  TL(42);
  bar_sync(2 + wg, 256);
#pragma unroll
  for (int e = 0; e < ENDK; e++) {
    ring_wait(fullx, 2 * NR + ENDK + e);
    mma(acc1, 2 * NR + ENDK + e, e < 2 ? NR + e : NR + 5 - e, 0, 4);
  }
  if (wg == 0) bar_arrive(3, 256);
  wgmma_wait<0>();
  TL(43);
  store_acc(acc1, op + 64 * F_DIM);
  TL(44);
  if (warp == 0 && lane == 0) {
    if (atomicAdd(fl + 17, 1u) == NI - 1) {
#pragma unroll
      for (int u = 0; u <= 17; u++) fl[u] = 0;
    }
  }
}

typedef CUresult (*EncodeTiledFn)(CUtensorMap*, CUtensorMapDataType, cuuint32_t, void*, const cuuint64_t*,
                                  const cuuint64_t*, const cuuint32_t*, const cuuint32_t*, CUtensorMapInterleave,
                                  CUtensorMapSwizzle, CUtensorMapL2promotion, CUtensorMapFloatOOBfill);

}

#define XPROMO CU_TENSOR_MAP_L2_PROMOTION_L2_128B
extern "C" void kernel_launch(void* const* d_in, const int* in_sizes, int n_in, void* d_out, int out_size) {
  const __nv_bfloat16* x = (const __nv_bfloat16*)d_in[0];
  const int* qw = (const int*)d_in[1];
  const __nv_bfloat16* lut = (const __nv_bfloat16*)d_in[2];
  const __nv_bfloat16* scales = (const __nv_bfloat16*)d_in[3];
  __nv_bfloat16* out = (__nv_bfloat16*)d_out;

  static EncodeTiledFn enc = nullptr;
  static uint8_t* p_scr = nullptr;
  if (!enc) {
    void* fn = nullptr;
    cudaDriverEntryPointQueryResult qr;
    cudaGetDriverEntryPoint("cuTensorMapEncodeTiled", &fn, cudaEnableDefault, &qr);
    enc = (EncodeTiledFn)fn;
    void* p = nullptr;
    cudaGetSymbolAddress(&p, g_scratch);
    p_scr = (uint8_t*)(((uintptr_t)p + REGION - 1) & ~(uintptr_t)(REGION - 1));
    cudaFuncSetAttribute(fused_kernel, cudaFuncAttributeMaxDynamicSharedMemorySize, SMEM_TOTAL);
  }
  CUtensorMap tm_x, tm_q;
  cuuint32_t estr[2] = {1, 1};
  {
    cuuint64_t gdim[2] = {(cuuint64_t)D_DIM, (cuuint64_t)S_DIM};
    cuuint64_t gstr[1] = {(cuuint64_t)D_DIM * 2};
    cuuint32_t box[2] = {(cuuint32_t)BK, 64};
    enc(&tm_x, CU_TENSOR_MAP_DATA_TYPE_BFLOAT16, 2, (void*)x, gdim, gstr, box, estr, CU_TENSOR_MAP_INTERLEAVE_NONE,
        CU_TENSOR_MAP_SWIZZLE_128B, XPROMO, CU_TENSOR_MAP_FLOAT_OOB_FILL_NONE);
  }
  {
    cuuint64_t gdim[2] = {(cuuint64_t)F_DIM, (cuuint64_t)D_DIM};
    cuuint64_t gstr[1] = {(cuuint64_t)F_DIM * 4};
    cuuint32_t box[2] = {(cuuint32_t)BN, 8};
    enc(&tm_q, CU_TENSOR_MAP_DATA_TYPE_INT32, 2, (void*)qw, gdim, gstr, box, estr, CU_TENSOR_MAP_INTERLEAVE_NONE,
        CU_TENSOR_MAP_SWIZZLE_NONE, CU_TENSOR_MAP_L2_PROMOTION_NONE, CU_TENSOR_MAP_FLOAT_OOB_FILL_NONE);
  }
  fused_kernel<<<NI * NJ, 256, SMEM_TOTAL, cudaStreamPerThread>>>(qw, lut, scales, out, p_scr, tm_x, tm_q);
}
```

```cpp
#include <cuda_runtime.h>
#include <cuda_bf16.h>
#include <cuda.h>
#include <stdint.h>

namespace {

constexpr int S_DIM = 2048, D_DIM = 1024, F_DIM = 3584;
constexpr int BM = 256, BN = 224, BK = 64;
constexpr int NKB = D_DIM / BK;
constexpr int NJ = F_DIM / BN;
constexpr int NI = S_DIM / BM;
constexpr int WS = 4;
constexpr int XS = 5;
constexpr int ENDK = 4;
constexpr int NR = NKB - ENDK;
constexpr int X_SLICE = 64 * BK * 2;
constexpr int W_STAGE = BN * BK * 2;
constexpr int W_KC = BN * 16;

constexpr int REGION = 512 * 1024;
__device__ uint4 g_scratch[(NJ + 1) * REGION / 16];

__device__ __forceinline__ uint32_t smem_u32(const void* p) { return (uint32_t)__cvta_generic_to_shared(p); }
__device__ __forceinline__ unsigned clk32() {
  unsigned c;
  asm volatile("mov.u32 %0, %%clock;" : "=r"(c)::"memory");
  return c;
}
__device__ __forceinline__ bool elect_one() {
  uint32_t p;
  asm volatile("{\n.reg .pred P;\nelect.sync _|P, 0xffffffff;\nselp.b32 %0, 1, 0, P;\n}" : "=r"(p));
  return p != 0;
}
__device__ __forceinline__ void mbar_init(uint32_t bar, uint32_t cnt) {
  asm volatile("mbarrier.init.shared::cta.b64 [%0], %1;" ::"r"(bar), "r"(cnt) : "memory");
}
__device__ __forceinline__ void mbar_expect_tx(uint32_t bar, uint32_t bytes) {
  asm volatile("mbarrier.arrive.expect_tx.shared::cta.b64 _, [%0], %1;" ::"r"(bar), "r"(bytes) : "memory");
}
__device__ __forceinline__ void mbar_arrive(uint32_t bar) {
  asm volatile("mbarrier.arrive.shared::cta.b64 _, [%0];" ::"r"(bar) : "memory");
}
__device__ __forceinline__ bool mbar_test(uint32_t bar, uint32_t parity) {
  uint32_t ok;
  asm volatile(
      "{\n.reg .pred p;\nmbarrier.test_wait.parity.shared::cta.b64 p, [%1], %2;\nselp.b32 %0, 1, 0, p;\n}\n"
      : "=r"(ok) : "r"(bar), "r"(parity) : "memory");
  return ok != 0;
}
__device__ __forceinline__ void mbar_wait(uint32_t bar, uint32_t parity) {
  asm volatile(
      "{\n.reg .pred p;\n"
      "LAB_WAIT:\n"
      "mbarrier.try_wait.parity.shared::cta.b64 p, [%0], %1;\n"
      "@p bra LAB_DONE;\n"
      "bra LAB_WAIT;\n"
      "LAB_DONE:\n}\n" ::"r"(bar), "r"(parity) : "memory");
}
__device__ __forceinline__ uint32_t ring(uint32_t base, int i) { return base + 8 * (i & 7); }
__device__ __forceinline__ void ring_wait(uint32_t base, int i) { mbar_wait(ring(base, i), (i >> 3) & 1); }
__device__ __forceinline__ void tma_load_2d(uint32_t dst, const CUtensorMap* tm, int c0, int c1, uint32_t bar) {
  asm volatile(
      "cp.async.bulk.tensor.2d.shared::cluster.global.mbarrier::complete_tx::bytes [%0], [%1, {%3, %4}], [%2];"
      ::"r"(dst), "l"(tm), "r"(bar), "r"(c0), "r"(c1) : "memory");
}
__device__ __forceinline__ void tma_prefetch_2d(const CUtensorMap* tm, int c0, int c1) {
  asm volatile("cp.async.bulk.prefetch.tensor.2d.L2.global [%0, {%1, %2}];" ::"l"(tm), "r"(c0), "r"(c1) : "memory");
}
__device__ __forceinline__ void bulk_load(uint32_t dst, const void* src, uint32_t bytes, uint32_t bar) {
  asm volatile(
      "cp.async.bulk.shared::cluster.global.mbarrier::complete_tx::bytes [%0], [%1], %2, [%3];"
      ::"r"(dst), "l"(src), "r"(bytes), "r"(bar) : "memory");
}
__device__ __forceinline__ int ldg_stream(const int* p) {
  int v;
  asm volatile("ld.global.L1::no_allocate.b32 %0, [%1];" : "=r"(v) : "l"(p) : "memory");
  return v;
}
__device__ __forceinline__ uint32_t ldg_u16(const void* p) {
  uint32_t v;
  asm volatile("ld.global.u16 %0, [%1];" : "=r"(v) : "l"(p) : "memory");
  return v;
}
__device__ __forceinline__ int lds32(uint32_t addr) {
  int v;
  asm volatile("ld.shared.b32 %0, [%1];" : "=r"(v) : "r"(addr) : "memory");
  return v;
}
__device__ __forceinline__ uint64_t make_desc(uint32_t lo, uint32_t hi) {
  uint64_t d;
  asm("mov.b64 %0, {%1, %2};" : "=l"(d) : "r"(lo), "r"(hi));
  return d;
}
__device__ __forceinline__ unsigned ld_strong(const void* p) {
  unsigned v;
  asm volatile("ld.relaxed.gpu.global.u32 %0, [%1];" : "=r"(v) : "l"(p) : "memory");
  return v;
}
__device__ __forceinline__ void st_strong128(void* p, uint4 v) {
  asm volatile("st.relaxed.gpu.global.v4.u32 [%0], {%1, %2, %3, %4};" ::"l"(p), "r"(v.x), "r"(v.y), "r"(v.z), "r"(v.w)
               : "memory");
}
__device__ __forceinline__ void wgmma_fence() { asm volatile("wgmma.fence.sync.aligned;" ::: "memory"); }
__device__ __forceinline__ void wgmma_commit() { asm volatile("wgmma.commit_group.sync.aligned;" ::: "memory"); }
template <int N>
__device__ __forceinline__ void wgmma_wait() { asm volatile("wgmma.wait_group.sync.aligned %0;" ::"n"(N) : "memory"); }
__device__ __forceinline__ void bar_sync(int id, int n) { asm volatile("bar.sync %0, %1;" ::"r"(id), "r"(n) : "memory"); }
__device__ __forceinline__ void bar_arrive(int id, int n) { asm volatile("bar.arrive %0, %1;" ::"r"(id), "r"(n) : "memory"); }

__device__ __forceinline__ void wgmma_m64n224k16(float (&d)[112], uint64_t da, uint64_t db, int scale_d) {
  asm volatile(
    "{\n.reg .pred p;\nsetp.ne.b32 p, %114, 0;\n"
    "wgmma.mma_async.sync.aligned.m64n224k16.f32.bf16.bf16 "
    "{%0, %1, %2, %3, %4, %5, %6, %7, %8, %9, %10, %11, %12, %13, %14, %15, "
    "%16, %17, %18, %19, %20, %21, %22, %23, %24, %25, %26, %27, %28, %29, %30, %31, "
    "%32, %33, %34, %35, %36, %37, %38, %39, %40, %41, %42, %43, %44, %45, %46, %47, "
    "%48, %49, %50, %51, %52, %53, %54, %55, %56, %57, %58, %59, %60, %61, %62, %63, "
    "%64, %65, %66, %67, %68, %69, %70, %71, %72, %73, %74, %75, %76, %77, %78, %79, "
    "%80, %81, %82, %83, %84, %85, %86, %87, %88, %89, %90, %91, %92, %93, %94, %95, "
    "%96, %97, %98, %99, %100, %101, %102, %103, %104, %105, %106, %107, %108, %109, %110, %111}, "
    "%112, %113, p, 1, 1, 0, 0;\n}\n"
    : "+f"(d[0]), "+f"(d[1]), "+f"(d[2]), "+f"(d[3]), "+f"(d[4]), "+f"(d[5]), "+f"(d[6]), "+f"(d[7]),
      "+f"(d[8]), "+f"(d[9]), "+f"(d[10]), "+f"(d[11]), "+f"(d[12]), "+f"(d[13]), "+f"(d[14]), "+f"(d[15]),
      "+f"(d[16]), "+f"(d[17]), "+f"(d[18]), "+f"(d[19]), "+f"(d[20]), "+f"(d[21]), "+f"(d[22]), "+f"(d[23]),
      "+f"(d[24]), "+f"(d[25]), "+f"(d[26]), "+f"(d[27]), "+f"(d[28]), "+f"(d[29]), "+f"(d[30]), "+f"(d[31]),
      "+f"(d[32]), "+f"(d[33]), "+f"(d[34]), "+f"(d[35]), "+f"(d[36]), "+f"(d[37]), "+f"(d[38]), "+f"(d[39]),
      "+f"(d[40]), "+f"(d[41]), "+f"(d[42]), "+f"(d[43]), "+f"(d[44]), "+f"(d[45]), "+f"(d[46]), "+f"(d[47]),
      "+f"(d[48]), "+f"(d[49]), "+f"(d[50]), "+f"(d[51]), "+f"(d[52]), "+f"(d[53]), "+f"(d[54]), "+f"(d[55]),
      "+f"(d[56]), "+f"(d[57]), "+f"(d[58]), "+f"(d[59]), "+f"(d[60]), "+f"(d[61]), "+f"(d[62]), "+f"(d[63]),
      "+f"(d[64]), "+f"(d[65]), "+f"(d[66]), "+f"(d[67]), "+f"(d[68]), "+f"(d[69]), "+f"(d[70]), "+f"(d[71]),
      "+f"(d[72]), "+f"(d[73]), "+f"(d[74]), "+f"(d[75]), "+f"(d[76]), "+f"(d[77]), "+f"(d[78]), "+f"(d[79]),
      "+f"(d[80]), "+f"(d[81]), "+f"(d[82]), "+f"(d[83]), "+f"(d[84]), "+f"(d[85]), "+f"(d[86]), "+f"(d[87]),
      "+f"(d[88]), "+f"(d[89]), "+f"(d[90]), "+f"(d[91]), "+f"(d[92]), "+f"(d[93]), "+f"(d[94]), "+f"(d[95]),
      "+f"(d[96]), "+f"(d[97]), "+f"(d[98]), "+f"(d[99]), "+f"(d[100]), "+f"(d[101]), "+f"(d[102]), "+f"(d[103]),
      "+f"(d[104]), "+f"(d[105]), "+f"(d[106]), "+f"(d[107]), "+f"(d[108]), "+f"(d[109]), "+f"(d[110]), "+f"(d[111])
    : "l"(da), "l"(db), "r"(scale_d));
}

__device__ __forceinline__ uint32_t pack_bf16(float lo, float hi) {
  uint32_t r;
  asm("cvt.rn.bf16x2.f32 %0, %1, %2;" : "=r"(r) : "f"(hi), "f"(lo));
  return r;
}

__device__ __forceinline__ int perm32(int n) { return (n & ~30) | ((n & 6) << 2) | ((n >> 2) & 6); }

constexpr int SMEM_X = 0;
constexpr int SMEM_W = 2 * XS * X_SLICE;
constexpr int SMEM_Q = SMEM_W + WS * W_STAGE;
constexpr int Q_UNIT = 8 * BN * 4;
constexpr int SMEM_BAR = SMEM_Q + W_STAGE;
constexpr int B_FULLW = 0, B_FULLQ = 8, B_FULLX = 16, B_DONE = 32, B_COUNT = 48;
constexpr int SMEM_TL = SMEM_BAR + B_COUNT * 8;
constexpr int SMEM_TOTAL = SMEM_TL + 2048;
constexpr int W_OFF = 128;
constexpr unsigned FLAG_FULL = NI * 7;

#define TL(i)
#define TLG(i)

__device__ __forceinline__ void store_acc(const float (&a)[112], __nv_bfloat16* p) {
#pragma unroll
  for (int J = 0; J < 7; J++) {
    uint4 v0, v1;
    v0.x = pack_bf16(a[16 * J + 0], a[16 * J + 1]);
    v0.y = pack_bf16(a[16 * J + 4], a[16 * J + 5]);
    v0.z = pack_bf16(a[16 * J + 8], a[16 * J + 9]);
    v0.w = pack_bf16(a[16 * J + 12], a[16 * J + 13]);
    v1.x = pack_bf16(a[16 * J + 2], a[16 * J + 3]);
    v1.y = pack_bf16(a[16 * J + 6], a[16 * J + 7]);
    v1.z = pack_bf16(a[16 * J + 10], a[16 * J + 11]);
    v1.w = pack_bf16(a[16 * J + 14], a[16 * J + 15]);
    *reinterpret_cast<uint4*>(p + 32 * J) = v0;
    *reinterpret_cast<uint4*>(p + 8 * F_DIM + 32 * J) = v1;
  }
}

__device__ __forceinline__ void load_unit(int (&q)[8], const int* p) {
#pragma unroll
  for (int i = 0; i < 8; i++) q[i] = ldg_stream(p + i * F_DIM);
}
__device__ __forceinline__ uint4 convert_unit(const int (&q)[8], float lutv, float sc) {
  float v[8];
#pragma unroll
  for (int i = 0; i < 8; i++) v[i] = __shfl_sync(0xffffffffu, lutv, q[i]) * sc;
  uint4 o;
  o.x = pack_bf16(v[0], v[1]);
  o.y = pack_bf16(v[2], v[3]);
  o.z = pack_bf16(v[4], v[5]);
  o.w = pack_bf16(v[6], v[7]);
  return o;
}

__device__ __forceinline__ void dequant_lookup(int (&q)[8], float lutv) {
  asm volatile(
      "shfl.sync.idx.b32 %0, %8, %0, 31, 0xffffffff;\n"
      "shfl.sync.idx.b32 %1, %8, %1, 31, 0xffffffff;\n"
      "shfl.sync.idx.b32 %2, %8, %2, 31, 0xffffffff;\n"
      "shfl.sync.idx.b32 %3, %8, %3, 31, 0xffffffff;\n"
      "shfl.sync.idx.b32 %4, %8, %4, 31, 0xffffffff;\n"
      "shfl.sync.idx.b32 %5, %8, %5, 31, 0xffffffff;\n"
      "shfl.sync.idx.b32 %6, %8, %6, 31, 0xffffffff;\n"
      "shfl.sync.idx.b32 %7, %8, %7, 31, 0xffffffff;\n"
      : "+r"(q[0]), "+r"(q[1]), "+r"(q[2]), "+r"(q[3]), "+r"(q[4]), "+r"(q[5]), "+r"(q[6]), "+r"(q[7])
      : "r"(__float_as_int(lutv)));
}
__device__ __forceinline__ void dequant_finish(int (&q)[8], unsigned& rb, uint4* wp, float sc, uint32_t qbar,
                                               uint32_t qpar, uint32_t qaddr) {
  asm volatile(
      "{\n.reg .pred W;\n.reg .b32 o0, o1, o2, o3;\n"
      "DQ_WAIT:\n"
      "mbarrier.try_wait.parity.shared::cta.b64 W, [%11], %13;\n"
      "@!W bra DQ_WAIT;\n"
      "mul.rn.f32 %0, %0, %10;\nmul.rn.f32 %1, %1, %10;\nmul.rn.f32 %2, %2, %10;\nmul.rn.f32 %3, %3, %10;\n"
      "mul.rn.f32 %4, %4, %10;\nmul.rn.f32 %5, %5, %10;\nmul.rn.f32 %6, %6, %10;\nmul.rn.f32 %7, %7, %10;\n"
      "cvt.rn.bf16x2.f32 o0, %1, %0;\ncvt.rn.bf16x2.f32 o1, %3, %2;\n"
      "cvt.rn.bf16x2.f32 o2, %5, %4;\ncvt.rn.bf16x2.f32 o3, %7, %6;\n"
      "ld.volatile.shared.b32 %0, [%12];\nld.volatile.shared.b32 %1, [%12+896];\n"
      "ld.volatile.shared.b32 %2, [%12+1792];\nld.volatile.shared.b32 %3, [%12+2688];\n"
      "ld.volatile.shared.b32 %4, [%12+3584];\nld.volatile.shared.b32 %5, [%12+4480];\n"
      "ld.volatile.shared.b32 %6, [%12+5376];\nld.volatile.shared.b32 %7, [%12+6272];\n"
      "st.relaxed.gpu.global.v4.u32 [%9], {o0, o1, o2, o3};\n"
      "ld.relaxed.gpu.global.u32 %8, [%9];\n}\n"
      : "+r"(q[0]), "+r"(q[1]), "+r"(q[2]), "+r"(q[3]), "+r"(q[4]), "+r"(q[5]), "+r"(q[6]), "+r"(q[7]), "=r"(rb)
      : "l"(wp), "r"(__float_as_int(sc)), "r"(qbar), "r"(qaddr), "r"(qpar)
      : "memory");
}

constexpr int PU = 4;
#define HEAVY 0xB6DB4u
__host__ __device__ constexpr int popc(unsigned v) { return v ? (v & 1) + popc(v >> 1) : 0; }
__host__ __device__ constexpr bool heavy(int n) { return (HEAVY >> n) & 1; }
__host__ __device__ constexpr int unit_at(int n) { return PU + popc(HEAVY & ((1u << n) - 1)); }
__host__ __device__ constexpr int emit_slot(int u) {
  if (u < PU) return u == PU - 1 ? 1 : -1;
  for (int n = 2; n < 24; n++)
    if (heavy(n) && unit_at(n) == u) return n;
  return 99;
}
__host__ __device__ constexpr int cmax(int a, int b) { return a > b ? a : b; }
__host__ __device__ constexpr int w_slot(int m) {
  return m == 15 ? cmax(emit_slot(15) + 3, 22) : cmax(2 * m - 5, emit_slot(m) + 3);
}
__host__ __device__ constexpr int q_slot(int u) {
  return u == 7 ? 2 : cmax(q_slot(u - 1) + 1, u - 5 < PU ? 2 : emit_slot(u - 5) + 2);
}
__host__ __device__ constexpr int w_at(int n) {
  for (int m = 2; m < NKB; m++)
    if (w_slot(m) == n) return m;
  return -1;
}
__host__ __device__ constexpr int q_at(int n) {
  for (int u = 7; u < NKB; u++)
    if (q_slot(u) == n) return u;
  return -1;
}
constexpr bool schedule_ok() {
  if (popc(HEAVY) != NKB - PU || (HEAVY & 3) || (HEAVY >> 20)) return false;
  for (int m = 2; m < NKB; m++) {
    if (w_at(w_slot(m)) != m || w_slot(m) > 23) return false;
    if (m < NR && w_slot(m) > 2 * m - 2) return false;
  }
  for (int u = 7; u < NKB; u++)
    if (q_slot(u) + 2 > emit_slot(u - 1)) return false;
  return true;
}
static_assert(schedule_ok(), "bad schedule");
template <int V>
struct IC {
  static constexpr int value = V;
};
template <int I, int N, class F>
__device__ __forceinline__ void static_for(F&& f) {
  if constexpr (I < N) {
    f(IC<I>{});
    static_for<I + 1, N>(f);
  }
}

#define PACE_B 350
#define PACE_Q1 700
#define PACE_Q2 1300
#define X1_AT 0
#define PACE_Q3 0
#define PACE_X 450
#define X_FIRST (PACE_X < PACE_Q1)
#define PF_X 0
#define PF_Q 0

constexpr uint32_t sbase = 1024;

__global__ void __launch_bounds__(256, 1)
fused_kernel(const int* __restrict__ qw, const __nv_bfloat16* __restrict__ lut,
             const __nv_bfloat16* __restrict__ scales, __nv_bfloat16* __restrict__ out, uint8_t* scratch,
             const __grid_constant__ CUtensorMap tm_x, const __grid_constant__ CUtensorMap tm_q) {
  extern __shared__ __align__(1024) uint8_t smem_raw[];
  constexpr uint32_t bars = sbase + SMEM_BAR;
  const int j = blockIdx.x >> 3, it = blockIdx.x & 7;
  const int warp = __shfl_sync(0xffffffffu, threadIdx.x >> 5, 0);
  const int wg = warp >> 2;
  int lane;
  asm volatile("mov.u32 %0, %%laneid;" : "=r"(lane));
  const unsigned t_start = clk32();
  auto pace = [&](unsigned t) {
    while (__any_sync(0xffffffffu, clk32() - t_start < t)) {}
  };
  TL(0); TLG(1);

  uint8_t* const region = scratch + (size_t)j * REGION;
  uint8_t* const wp = region + W_OFF + it * W_KC + (warp * 32 + lane) * 16;
  unsigned* const fl = reinterpret_cast<unsigned*>(region) + lane;
  float lutv, sc;
  unsigned rb;
  const int xrow = it * BM + wg * 128;

  auto w_ptr = [&](int u) { return reinterpret_cast<uint4*>(wp + u * W_STAGE); };
  auto emit_unit = [&](const int (&qq)[8], int u) {
    st_strong128(w_ptr(u), convert_unit(qq, lutv, sc));
    rb = ld_strong(w_ptr(u));
  };
  auto publish = [&](int u, unsigned inc) {
    asm volatile(
        "{\n.reg .pred P, Q;\n"
        "setp.ne.u32 P, %1, 0xffffffff;\n"
        "vote.sync.all.pred P, P, 0xffffffff;\n"
        "setp.eq.and.s32 Q, %2, %3, P;\n"
        "@Q red.relaxed.gpu.global.add.u32 [%0], %4;\n}"
        ::"l"(fl), "r"(rb), "r"(lane), "r"(u), "r"(inc) : "memory");
  };
  auto load_x = [&](int g, int n, int kb, int half) {
    const uint32_t bar = ring(bars + 8 * B_FULLX, n) + g * 64;
    mbar_expect_tx(bar, X_SLICE);
    tma_load_2d(sbase + SMEM_X + (n % XS) * X_SLICE + g * (XS * X_SLICE), &tm_x, kb * BK,
                it * BM + g * 128 + half * 64, bar);
  };
  auto load_q = [&](int u) {
    const uint32_t bar = ring(bars + 8 * B_FULLQ, u);
    mbar_expect_tx(bar, Q_UNIT);
    tma_load_2d(sbase + SMEM_Q + (u & 3) * Q_UNIT, &tm_q, j * BN, u * BK + it * 8, bar);
  };
  auto prefetch_x = [&](int g) {
    if (PF_X) tma_prefetch_2d(&tm_x, (4 * g + (j >> 2)) * BK, it * BM + (j & 3) * 64);
  };
  auto prefetch_q = [&](int u) {
    if (PF_Q) tma_prefetch_2d(&tm_q, j * BN, u * BK + it * 8);
  };

  unsigned ready = 0;
  auto load_w = [&](uint32_t bar, int dst, int src, int bytes) {
    mbar_expect_tx(bar, bytes);
    bulk_load(sbase + SMEM_W + dst, region + W_OFF + src, bytes, bar);
  };
  auto poll = [&]() { ready |= __ballot_sync(0xffffffffu, ld_strong(fl) >= FLAG_FULL); };
  auto wait_ready = [&](int kb) {
    int spins = 0;
    while (!((ready >> kb) & 1)) {
      poll();
      if (++spins > (1 << 22)) __trap();
    }
  };

  uint32_t qbase;
  asm volatile("mov.u32 %0, %1;" : "=r"(qbase) : "r"(sbase + SMEM_Q + warp * 128 + perm32(lane) * 4));
  auto lds_unit = [&](int (&q)[8], int u) {
    ring_wait(bars + 8 * B_FULLQ, u);
#pragma unroll
    for (int i = 0; i < 8; i++) q[i] = lds32(qbase + (u & 3) * Q_UNIT + i * (BN * 4));
  };
  auto arrive_one = [&](uint32_t bar) {
    asm volatile("{\n.reg .pred P;\nelect.sync _|P, 0xffffffff;\n@P mbarrier.arrive.shared::cta.b64 _, [%0];\n}"
                 ::"r"(bar) : "memory");
  };

  int q[8];
  constexpr uint32_t bar_w0a = bars + 8 * B_FULLQ, bar_w0b = bars + 8 * B_FULLW, bar_w1 = bar_w0b + 8;
  unsigned issued = 0;
  int spins = 0;
  auto step = [&]() {
    ready |= __ballot_sync(0xffffffffu, rb >= FLAG_FULL);
    const unsigned go = ready & ~issued & 0x10007u;
    asm volatile("fence.proxy.async.global;" ::: "memory");
    rb = ld_strong(fl);
    if (go && elect_one()) {
      if (go & 0x10000) load_w(bar_w0a, 0, 0, W_STAGE / 2);
      if (go & 1) load_w(bar_w0b, W_STAGE / 2, W_STAGE / 2, W_STAGE / 2);
      if (go & 2) load_w(bar_w1, W_STAGE, W_STAGE, W_STAGE);
      if (go & 4) load_w(bar_w1 + 8, 2 * W_STAGE, 2 * W_STAGE, W_STAGE);
    }
    issued |= go;
    if (++spins > (1 << 22)) __trap();
  };
  if (warp == 7) {
    if (elect_one()) {
#pragma unroll
      for (int i = 0; i < B_COUNT; i++) mbar_init(bars + 8 * i, i >= B_DONE ? 4 : 1);
      asm volatile("fence.mbarrier_init.release.cluster;" ::: "memory");
    }
    __syncwarp();
    rb = ld_strong(fl);
    bar_arrive(0, 256);
    TL(4);
    lutv = 0.f;
    sc = 0.f;
    if (smem_u32(smem_raw) != sbase) __trap();
    if (X_FIRST) {
      pace(PACE_X);
      if (elect_one()) {
        load_x(0, 0, 0, 0); load_x(1, 0, 0, 0); load_x(0, 1, 0, 1); load_x(1, 1, 0, 1);
      }
    }
    pace(PACE_Q1);
    if (elect_one()) load_q(1);
    if (!X_FIRST) {
      pace(PACE_X);
      if (elect_one()) {
        load_x(0, 0, 0, 0); load_x(1, 0, 0, 0); load_x(0, 1, 0, 1); load_x(1, 1, 0, 1);
      }
    }
    pace(PACE_Q2);
    if (elect_one()) {
      load_q(2);
      if (j >= 4) prefetch_x(0);
    }
    if (PACE_Q3) {
      pace(PACE_Q3);
      if (elect_one()) load_q(3);
    }
    step();
    if (X1_AT == 0 && elect_one()) {
      load_x(0, 2, 1, 0); load_x(1, 2, 1, 0); load_x(0, 3, 1, 1); load_x(1, 3, 1, 1);
    }
    if (X1_AT == 1) {
      if (elect_one()) { load_x(0, 2, 1, 0); load_x(1, 2, 1, 0); }
      step();
      if (elect_one()) { load_x(0, 3, 1, 1); load_x(1, 3, 1, 1); }
    }
    while (!(issued & 0x10000)) step();
    if (elect_one()) {
      if (!PACE_Q3) load_q(3);
      load_q(4);
      if (X1_AT == 2) { load_x(0, 2, 1, 0); load_x(1, 2, 1, 0); load_x(0, 3, 1, 1); load_x(1, 3, 1, 1); }
    }
    TL(2);
    step();
  } else {
    const int fcol = j * BN + warp * 32 + perm32(lane);
    const int half = wg ^ (it & 1);
    const int kc = half * 4 + (it >> 1);
    if (half) {
      if ((warp & 3) == 0 && elect_one()) {
        asm volatile("prefetch.tensormap [%0];" ::"l"(&tm_x) : "memory");
        asm volatile("prefetch.tensormap [%0];" ::"l"(&tm_q) : "memory");
      }
      pace(PACE_B);
    }
    load_unit(q, qw + (size_t)(kc * 8) * F_DIM + fcol);
    lutv = __uint_as_float(ldg_u16(lut + (lane & 15)) << 16);
    sc = __uint_as_float(ldg_u16(scales + fcol) << 16);
    uint8_t* p = wp + (kc - it) * W_KC;
    st_strong128(p, convert_unit(q, lutv, sc));
    rb = ld_strong(p);
    TL(2);
    publish(half ? 0 : 16, 2);
    TL(3);
    bar_sync(0, 256);
    lds_unit(q, 1);
    emit_unit(q, 1);
    publish(1, 1);
    TL(4);
    lds_unit(q, 2);
  }

  float acc0[112], acc1[112];
  constexpr uint32_t DA_HI = (1u << 30) | (1024 >> 4), DB_HI = (128 >> 4);
  const uint32_t da0 = ((1u << 16) | ((sbase + SMEM_X) >> 4)) + wg * (XS * X_SLICE >> 4);
  constexpr uint32_t db0 = ((W_KC >> 4) << 16) | ((sbase + SMEM_W) >> 4);
  const uint32_t fullx = bars + 8 * B_FULLX + wg * 64, done = bars + 8 * B_DONE + wg * 64;
  const bool x_issuer = (warp & 3) == 3;

  auto mma = [&](float (&acc)[112], int n, int kb, int k0, int k1) {
    const int wslot = kb == 15 ? 4 : (kb & 3);
    wgmma_fence();
#pragma unroll
    for (int k = k0; k < k1; k++)
      wgmma_m64n224k16(acc, make_desc(da0 + (n % XS) * (X_SLICE >> 4) + k * 2, DA_HI),
                       make_desc(db0 + wslot * (W_STAGE >> 4) + k * (2 * W_KC >> 4), DB_HI), kb != 0 || k != 0);
    wgmma_commit();
  };
  auto end_slot = [&](int n) {
    wgmma_wait<1>();
    arrive_one(ring(done, n));
    if (x_issuer) {
      ring_wait(done, n);
      const int m = n + 4, e = (m - 2 * NR) & 3;
      if (elect_one())
        load_x(wg, m, m < 2 * NR ? m >> 1 : e < 2 ? NR + e : NR + 5 - e, m < 2 * NR ? m & 1 : (m - 2 * NR) >> 2);
    }
  };
  auto slot = [&](float (&acc)[112], auto N) {
    constexpr int n = decltype(N)::value;
    constexpr bool hv = heavy(n), pub = n == 2 || heavy(n - 1);
    ring_wait(fullx, n);
    mma(acc, n, n >> 1, 0, 4);
    if (hv && warp < 7) dequant_lookup(q, lutv);
    end_slot(n);
    if (warp < 7) {
      constexpr int u = unit_at(n);
      if (pub) publish(u - 1, 1);
      if (hv) {
        constexpr int un = u + 1 < NKB ? u + 1 : u;
        dequant_finish(q, rb, w_ptr(u), sc, ring(bars + 8 * B_FULLQ, un), un >> 3, qbase + (un & 3) * Q_UNIT);
      }
    } else {
      constexpr int m = w_at(n), u = q_at(n), m_next = w_at(n + 1);
      if (m >= 0 || u >= 0) ring_wait(bars + 8 * B_DONE, n - 1);
      if (m >= 0) {
        ready |= __ballot_sync(0xffffffffu, rb >= FLAG_FULL);
        wait_ready(m);
        asm volatile("fence.proxy.async.global;" ::: "memory");
      }
      if (m_next >= 0) rb = ld_strong(fl);
      if ((m >= 0 || u >= 0 || n == 4 || n == 10) && elect_one()) {
        if (m >= 0 && (m != 2 || !(issued & 4)))
          load_w(ring(bars + 8 * B_FULLW, m), (m == 15 ? 4 : m & 3) * W_STAGE, m * W_STAGE, W_STAGE);
        if (u >= 0) load_q(u);
        if (u >= 0 && u + 2 < NKB) prefetch_q(u + 2);
        if (n == 4 || n == 10) prefetch_x(n == 4 ? 2 : 3);
      }
    }
  };

  mbar_wait(bar_w0a, 0);
  mbar_wait(fullx, 0);
  TL(8); TLG(46);
  mma(acc0, 0, 0, 0, 2);
  mbar_wait(fullx + 8, 0);
  mma(acc1, 1, 0, 0, 2);
  arrive_one(done);
  if (warp < 7) {
    emit_unit(q, 2);
    TL(5);
  } else {
    mbar_wait(bars + 8 * B_DONE, 0);
    mbar_wait(done, 0);
    if (elect_one()) load_q(5);
    while (!(issued & 1)) step();
  }
  mbar_wait(bar_w0b, 0);
  TL(9);
  mma(acc0, 0, 0, 2, 4);
  mma(acc1, 1, 0, 2, 4);
  if (warp < 7) {
    publish(2, 1);
    lds_unit(q, 3);
    emit_unit(q, 3);
    lds_unit(q, 4);
  } else {
    do step(); while (!(issued & 2));
    TL(3);
    if (elect_one()) {
      load_q(6);
      load_x(0, 4, 2, 0); load_x(1, 4, 2, 0);
      prefetch_x(1);
    }
  }
  end_slot(1);
  if (warp == 7) step();

  static_for<1, NR>([&](auto R) {
    constexpr int r = decltype(R)::value;
    ring_wait(bars + 8 * B_FULLW, r);
    TL(8 + 2 * r);
    slot(acc0, IC<2 * r>{});
    TL(9 + 2 * r);
    slot(acc1, IC<2 * r + 1>{});
  });

  __nv_bfloat16* op = out + (size_t)(xrow + (warp & 3) * 16 + (lane >> 2)) * F_DIM + j * BN + (lane & 3) * 8;
  TL(40); TLG(48);
  if (wg == 1) bar_sync(1, 256);
#pragma unroll
  for (int e = 0; e < ENDK; e++) {
    const int kb = e < 2 ? NR + e : NR + 5 - e;
    ring_wait(bars + 8 * B_FULLW, kb);
    ring_wait(fullx, 2 * NR + e);
    mma(acc0, 2 * NR + e, kb, 0, 4);
    if (e == ENDK - 1) bar_arrive(1 + wg, 256);
    end_slot(2 * NR + e);
  }
  wgmma_wait<0>();
  TL(41);
  store_acc(acc0, op);
  TL(42);
  bar_sync(2 + wg, 256);
#pragma unroll
  for (int e = 0; e < ENDK; e++) {
    ring_wait(fullx, 2 * NR + ENDK + e);
    mma(acc1, 2 * NR + ENDK + e, e < 2 ? NR + e : NR + 5 - e, 0, 4);
  }
  if (wg == 0) bar_arrive(3, 256);
  wgmma_wait<0>();
  TL(43); TLG(47);
  store_acc(acc1, op + 64 * F_DIM);
  TL(44);
  if (warp == 0 && lane == 0) {
    if (atomicAdd(fl + 17, 1u) == NI - 1) {
#pragma unroll
      for (int u = 0; u <= 17; u++) fl[u] = 0;
    }
  }
}

typedef CUresult (*EncodeTiledFn)(CUtensorMap*, CUtensorMapDataType, cuuint32_t, void*, const cuuint64_t*,
                                  const cuuint64_t*, const cuuint32_t*, const cuuint32_t*, CUtensorMapInterleave,
                                  CUtensorMapSwizzle, CUtensorMapL2promotion, CUtensorMapFloatOOBfill);

}

#define XPROMO CU_TENSOR_MAP_L2_PROMOTION_L2_128B
extern "C" void kernel_launch(void* const* d_in, const int* in_sizes, int n_in, void* d_out, int out_size) {
  const __nv_bfloat16* x = (const __nv_bfloat16*)d_in[0];
  const int* qw = (const int*)d_in[1];
  const __nv_bfloat16* lut = (const __nv_bfloat16*)d_in[2];
  const __nv_bfloat16* scales = (const __nv_bfloat16*)d_in[3];
  __nv_bfloat16* out = (__nv_bfloat16*)d_out;

  static EncodeTiledFn enc = nullptr;
  static uint8_t* p_scr = nullptr;
  if (!enc) {
    void* fn = nullptr;
    cudaDriverEntryPointQueryResult qr;
    cudaGetDriverEntryPoint("cuTensorMapEncodeTiled", &fn, cudaEnableDefault, &qr);
    enc = (EncodeTiledFn)fn;
    void* p = nullptr;
    cudaGetSymbolAddress(&p, g_scratch);
    p_scr = (uint8_t*)(((uintptr_t)p + REGION - 1) & ~(uintptr_t)(REGION - 1));
    cudaFuncSetAttribute(fused_kernel, cudaFuncAttributeMaxDynamicSharedMemorySize, SMEM_TOTAL);
  }
  CUtensorMap tm_x, tm_q;
  cuuint32_t estr[2] = {1, 1};
  {
    cuuint64_t gdim[2] = {(cuuint64_t)D_DIM, (cuuint64_t)S_DIM};
    cuuint64_t gstr[1] = {(cuuint64_t)D_DIM * 2};
    cuuint32_t box[2] = {(cuuint32_t)BK, 64};
    enc(&tm_x, CU_TENSOR_MAP_DATA_TYPE_BFLOAT16, 2, (void*)x, gdim, gstr, box, estr, CU_TENSOR_MAP_INTERLEAVE_NONE,
        CU_TENSOR_MAP_SWIZZLE_128B, XPROMO, CU_TENSOR_MAP_FLOAT_OOB_FILL_NONE);
  }
  {
    cuuint64_t gdim[2] = {(cuuint64_t)F_DIM, (cuuint64_t)D_DIM};
    cuuint64_t gstr[1] = {(cuuint64_t)F_DIM * 4};
    cuuint32_t box[2] = {(cuuint32_t)BN, 8};
    enc(&tm_q, CU_TENSOR_MAP_DATA_TYPE_INT32, 2, (void*)qw, gdim, gstr, box, estr, CU_TENSOR_MAP_INTERLEAVE_NONE,
        CU_TENSOR_MAP_SWIZZLE_NONE, CU_TENSOR_MAP_L2_PROMOTION_NONE, CU_TENSOR_MAP_FLOAT_OOB_FILL_NONE);
  }
  fused_kernel<<<NI * NJ, 256, SMEM_TOTAL, cudaStreamPerThread>>>(qw, lut, scales, out, p_scr, tm_x, tm_q);
}
```

```cpp
#include <cuda_runtime.h>
#include <cuda_bf16.h>
#include <cuda.h>
#include <stdint.h>

namespace {

constexpr int S_DIM = 2048, D_DIM = 1024, F_DIM = 3584;
constexpr int BM = 256, BN = 224, BK = 64;
constexpr int NKB = D_DIM / BK;
constexpr int NJ = F_DIM / BN;
constexpr int NI = S_DIM / BM;
constexpr int WS = 4;
constexpr int XS = 5;
constexpr int ENDK = 4;
constexpr int NR = NKB - ENDK;
constexpr int X_SLICE = 64 * BK * 2;
constexpr int W_STAGE = BN * BK * 2;
constexpr int W_KC = BN * 16;

constexpr int REGION = 512 * 1024;
__device__ uint4 g_scratch[(NJ + 1) * REGION / 16];

__device__ __forceinline__ uint32_t smem_u32(const void* p) { return (uint32_t)__cvta_generic_to_shared(p); }
__device__ __forceinline__ unsigned clk32() {
  unsigned c;
  asm volatile("mov.u32 %0, %%clock;" : "=r"(c)::"memory");
  return c;
}
__device__ __forceinline__ bool elect_one() {
  uint32_t p;
  asm volatile("{\n.reg .pred P;\nelect.sync _|P, 0xffffffff;\nselp.b32 %0, 1, 0, P;\n}" : "=r"(p));
  return p != 0;
}
__device__ __forceinline__ void mbar_init(uint32_t bar, uint32_t cnt) {
  asm volatile("mbarrier.init.shared::cta.b64 [%0], %1;" ::"r"(bar), "r"(cnt) : "memory");
}
__device__ __forceinline__ void mbar_expect_tx(uint32_t bar, uint32_t bytes) {
  asm volatile("mbarrier.arrive.expect_tx.shared::cta.b64 _, [%0], %1;" ::"r"(bar), "r"(bytes) : "memory");
}
__device__ __forceinline__ void mbar_arrive(uint32_t bar) {
  asm volatile("mbarrier.arrive.shared::cta.b64 _, [%0];" ::"r"(bar) : "memory");
}
__device__ __forceinline__ bool mbar_test(uint32_t bar, uint32_t parity) {
  uint32_t ok;
  asm volatile(
      "{\n.reg .pred p;\nmbarrier.test_wait.parity.shared::cta.b64 p, [%1], %2;\nselp.b32 %0, 1, 0, p;\n}\n"
      : "=r"(ok) : "r"(bar), "r"(parity) : "memory");
  return ok != 0;
}
__device__ __forceinline__ void mbar_wait(uint32_t bar, uint32_t parity) {
  asm volatile(
      "{\n.reg .pred p;\n"
      "LAB_WAIT:\n"
      "mbarrier.try_wait.parity.shared::cta.b64 p, [%0], %1;\n"
      "@p bra LAB_DONE;\n"
      "bra LAB_WAIT;\n"
      "LAB_DONE:\n}\n" ::"r"(bar), "r"(parity) : "memory");
}
__device__ __forceinline__ uint32_t ring(uint32_t base, int i) { return base + 8 * (i & 7); }
__device__ __forceinline__ void ring_wait(uint32_t base, int i) { mbar_wait(ring(base, i), (i >> 3) & 1); }
__device__ __forceinline__ void tma_load_2d(uint32_t dst, const CUtensorMap* tm, int c0, int c1, uint32_t bar) {
  asm volatile(
      "cp.async.bulk.tensor.2d.shared::cluster.global.mbarrier::complete_tx::bytes [%0], [%1, {%3, %4}], [%2];"
      ::"r"(dst), "l"(tm), "r"(bar), "r"(c0), "r"(c1) : "memory");
}
__device__ __forceinline__ void tma_prefetch_2d(const CUtensorMap* tm, int c0, int c1) {
  asm volatile("cp.async.bulk.prefetch.tensor.2d.L2.global [%0, {%1, %2}];" ::"l"(tm), "r"(c0), "r"(c1) : "memory");
}
__device__ __forceinline__ void bulk_load(uint32_t dst, const void* src, uint32_t bytes, uint32_t bar) {
  asm volatile(
      "cp.async.bulk.shared::cluster.global.mbarrier::complete_tx::bytes [%0], [%1], %2, [%3];"
      ::"r"(dst), "l"(src), "r"(bytes), "r"(bar) : "memory");
}
__device__ __forceinline__ int ldg_stream(const int* p) {
  int v;
  asm volatile("ld.global.L1::no_allocate.b32 %0, [%1];" : "=r"(v) : "l"(p) : "memory");
  return v;
}
__device__ __forceinline__ uint32_t ldg_u16(const void* p) {
  uint32_t v;
  asm volatile("ld.global.u16 %0, [%1];" : "=r"(v) : "l"(p) : "memory");
  return v;
}
__device__ __forceinline__ int lds32(uint32_t addr) {
  int v;
  asm volatile("ld.shared.b32 %0, [%1];" : "=r"(v) : "r"(addr) : "memory");
  return v;
}
__device__ __forceinline__ uint64_t make_desc(uint32_t lo, uint32_t hi) {
  uint64_t d;
  asm("mov.b64 %0, {%1, %2};" : "=l"(d) : "r"(lo), "r"(hi));
  return d;
}
__device__ __forceinline__ unsigned ld_strong(const void* p) {
  unsigned v;
  asm volatile("ld.relaxed.gpu.global.u32 %0, [%1];" : "=r"(v) : "l"(p) : "memory");
  return v;
}
__device__ __forceinline__ void st_strong128(void* p, uint4 v) {
  asm volatile("st.relaxed.gpu.global.v4.u32 [%0], {%1, %2, %3, %4};" ::"l"(p), "r"(v.x), "r"(v.y), "r"(v.z), "r"(v.w)
               : "memory");
}
__device__ __forceinline__ void wgmma_fence() { asm volatile("wgmma.fence.sync.aligned;" ::: "memory"); }
__device__ __forceinline__ void wgmma_commit() { asm volatile("wgmma.commit_group.sync.aligned;" ::: "memory"); }
template <int N>
__device__ __forceinline__ void wgmma_wait() { asm volatile("wgmma.wait_group.sync.aligned %0;" ::"n"(N) : "memory"); }
__device__ __forceinline__ void bar_sync(int id, int n) { asm volatile("bar.sync %0, %1;" ::"r"(id), "r"(n) : "memory"); }
__device__ __forceinline__ void bar_arrive(int id, int n) { asm volatile("bar.arrive %0, %1;" ::"r"(id), "r"(n) : "memory"); }

__device__ __forceinline__ void wgmma_m64n224k16(float (&d)[112], uint64_t da, uint64_t db, int scale_d) {
  asm volatile(
    "{\n.reg .pred p;\nsetp.ne.b32 p, %114, 0;\n"
    "wgmma.mma_async.sync.aligned.m64n224k16.f32.bf16.bf16 "
    "{%0, %1, %2, %3, %4, %5, %6, %7, %8, %9, %10, %11, %12, %13, %14, %15, "
    "%16, %17, %18, %19, %20, %21, %22, %23, %24, %25, %26, %27, %28, %29, %30, %31, "
    "%32, %33, %34, %35, %36, %37, %38, %39, %40, %41, %42, %43, %44, %45, %46, %47, "
    "%48, %49, %50, %51, %52, %53, %54, %55, %56, %57, %58, %59, %60, %61, %62, %63, "
    "%64, %65, %66, %67, %68, %69, %70, %71, %72, %73, %74, %75, %76, %77, %78, %79, "
    "%80, %81, %82, %83, %84, %85, %86, %87, %88, %89, %90, %91, %92, %93, %94, %95, "
    "%96, %97, %98, %99, %100, %101, %102, %103, %104, %105, %106, %107, %108, %109, %110, %111}, "
    "%112, %113, p, 1, 1, 0, 0;\n}\n"
    : "+f"(d[0]), "+f"(d[1]), "+f"(d[2]), "+f"(d[3]), "+f"(d[4]), "+f"(d[5]), "+f"(d[6]), "+f"(d[7]),
      "+f"(d[8]), "+f"(d[9]), "+f"(d[10]), "+f"(d[11]), "+f"(d[12]), "+f"(d[13]), "+f"(d[14]), "+f"(d[15]),
      "+f"(d[16]), "+f"(d[17]), "+f"(d[18]), "+f"(d[19]), "+f"(d[20]), "+f"(d[21]), "+f"(d[22]), "+f"(d[23]),
      "+f"(d[24]), "+f"(d[25]), "+f"(d[26]), "+f"(d[27]), "+f"(d[28]), "+f"(d[29]), "+f"(d[30]), "+f"(d[31]),
      "+f"(d[32]), "+f"(d[33]), "+f"(d[34]), "+f"(d[35]), "+f"(d[36]), "+f"(d[37]), "+f"(d[38]), "+f"(d[39]),
      "+f"(d[40]), "+f"(d[41]), "+f"(d[42]), "+f"(d[43]), "+f"(d[44]), "+f"(d[45]), "+f"(d[46]), "+f"(d[47]),
      "+f"(d[48]), "+f"(d[49]), "+f"(d[50]), "+f"(d[51]), "+f"(d[52]), "+f"(d[53]), "+f"(d[54]), "+f"(d[55]),
      "+f"(d[56]), "+f"(d[57]), "+f"(d[58]), "+f"(d[59]), "+f"(d[60]), "+f"(d[61]), "+f"(d[62]), "+f"(d[63]),
      "+f"(d[64]), "+f"(d[65]), "+f"(d[66]), "+f"(d[67]), "+f"(d[68]), "+f"(d[69]), "+f"(d[70]), "+f"(d[71]),
      "+f"(d[72]), "+f"(d[73]), "+f"(d[74]), "+f"(d[75]), "+f"(d[76]), "+f"(d[77]), "+f"(d[78]), "+f"(d[79]),
      "+f"(d[80]), "+f"(d[81]), "+f"(d[82]), "+f"(d[83]), "+f"(d[84]), "+f"(d[85]), "+f"(d[86]), "+f"(d[87]),
      "+f"(d[88]), "+f"(d[89]), "+f"(d[90]), "+f"(d[91]), "+f"(d[92]), "+f"(d[93]), "+f"(d[94]), "+f"(d[95]),
      "+f"(d[96]), "+f"(d[97]), "+f"(d[98]), "+f"(d[99]), "+f"(d[100]), "+f"(d[101]), "+f"(d[102]), "+f"(d[103]),
      "+f"(d[104]), "+f"(d[105]), "+f"(d[106]), "+f"(d[107]), "+f"(d[108]), "+f"(d[109]), "+f"(d[110]), "+f"(d[111])
    : "l"(da), "l"(db), "r"(scale_d));
}

__device__ __forceinline__ uint32_t pack_bf16(float lo, float hi) {
  uint32_t r;
  asm("cvt.rn.bf16x2.f32 %0, %1, %2;" : "=r"(r) : "f"(hi), "f"(lo));
  return r;
}

__device__ __forceinline__ int perm32(int n) { return (n & ~30) | ((n & 6) << 2) | ((n >> 2) & 6); }

constexpr int SMEM_X = 0;
constexpr int SMEM_W = 2 * XS * X_SLICE;
constexpr int SMEM_Q = SMEM_W + WS * W_STAGE;
constexpr int Q_UNIT = 8 * BN * 4;
constexpr int SMEM_BAR = SMEM_Q + W_STAGE;
constexpr int B_FULLW = 0, B_FULLQ = 8, B_FULLX = 16, B_DONE = 32, B_COUNT = 48;
constexpr int SMEM_TL = SMEM_BAR + B_COUNT * 8;
constexpr int SMEM_TOTAL = SMEM_TL + 2048;
constexpr int W_OFF = 128;
constexpr unsigned FLAG_FULL = NI * 7;

#define TL(i)
#define TLG(i)

__device__ __forceinline__ void store_acc(const float (&a)[112], __nv_bfloat16* p) {
#pragma unroll
  for (int J = 0; J < 7; J++) {
    uint4 v0, v1;
    v0.x = pack_bf16(a[16 * J + 0], a[16 * J + 1]);
    v0.y = pack_bf16(a[16 * J + 4], a[16 * J + 5]);
    v0.z = pack_bf16(a[16 * J + 8], a[16 * J + 9]);
    v0.w = pack_bf16(a[16 * J + 12], a[16 * J + 13]);
    v1.x = pack_bf16(a[16 * J + 2], a[16 * J + 3]);
    v1.y = pack_bf16(a[16 * J + 6], a[16 * J + 7]);
    v1.z = pack_bf16(a[16 * J + 10], a[16 * J + 11]);
    v1.w = pack_bf16(a[16 * J + 14], a[16 * J + 15]);
    *reinterpret_cast<uint4*>(p + 32 * J) = v0;
    *reinterpret_cast<uint4*>(p + 8 * F_DIM + 32 * J) = v1;
  }
}

__device__ __forceinline__ void load_unit(int (&q)[8], const int* p) {
#pragma unroll
  for (int i = 0; i < 8; i++) q[i] = ldg_stream(p + i * F_DIM);
}
__device__ __forceinline__ uint4 convert_unit(const int (&q)[8], float lutv, float sc) {
  float v[8];
#pragma unroll
  for (int i = 0; i < 8; i++) v[i] = __shfl_sync(0xffffffffu, lutv, q[i]) * sc;
  uint4 o;
  o.x = pack_bf16(v[0], v[1]);
  o.y = pack_bf16(v[2], v[3]);
  o.z = pack_bf16(v[4], v[5]);
  o.w = pack_bf16(v[6], v[7]);
  return o;
}

__device__ __forceinline__ void dequant_lookup(int (&q)[8], float lutv) {
  asm volatile(
      "shfl.sync.idx.b32 %0, %8, %0, 31, 0xffffffff;\n"
      "shfl.sync.idx.b32 %1, %8, %1, 31, 0xffffffff;\n"
      "shfl.sync.idx.b32 %2, %8, %2, 31, 0xffffffff;\n"
      "shfl.sync.idx.b32 %3, %8, %3, 31, 0xffffffff;\n"
      "shfl.sync.idx.b32 %4, %8, %4, 31, 0xffffffff;\n"
      "shfl.sync.idx.b32 %5, %8, %5, 31, 0xffffffff;\n"
      "shfl.sync.idx.b32 %6, %8, %6, 31, 0xffffffff;\n"
      "shfl.sync.idx.b32 %7, %8, %7, 31, 0xffffffff;\n"
      : "+r"(q[0]), "+r"(q[1]), "+r"(q[2]), "+r"(q[3]), "+r"(q[4]), "+r"(q[5]), "+r"(q[6]), "+r"(q[7])
      : "r"(__float_as_int(lutv)));
}
__device__ __forceinline__ void dequant_finish(int (&q)[8], unsigned& rb, uint4* wp, float sc, uint32_t qbar,
                                               uint32_t qpar, uint32_t qaddr) {
  asm volatile(
      "{\n.reg .pred W;\n.reg .b32 o0, o1, o2, o3;\n"
      "DQ_WAIT:\n"
      "mbarrier.try_wait.parity.shared::cta.b64 W, [%11], %13;\n"
      "@!W bra DQ_WAIT;\n"
      "mul.rn.f32 %0, %0, %10;\nmul.rn.f32 %1, %1, %10;\nmul.rn.f32 %2, %2, %10;\nmul.rn.f32 %3, %3, %10;\n"
      "mul.rn.f32 %4, %4, %10;\nmul.rn.f32 %5, %5, %10;\nmul.rn.f32 %6, %6, %10;\nmul.rn.f32 %7, %7, %10;\n"
      "cvt.rn.bf16x2.f32 o0, %1, %0;\ncvt.rn.bf16x2.f32 o1, %3, %2;\n"
      "cvt.rn.bf16x2.f32 o2, %5, %4;\ncvt.rn.bf16x2.f32 o3, %7, %6;\n"
      "ld.volatile.shared.b32 %0, [%12];\nld.volatile.shared.b32 %1, [%12+896];\n"
      "ld.volatile.shared.b32 %2, [%12+1792];\nld.volatile.shared.b32 %3, [%12+2688];\n"
      "ld.volatile.shared.b32 %4, [%12+3584];\nld.volatile.shared.b32 %5, [%12+4480];\n"
      "ld.volatile.shared.b32 %6, [%12+5376];\nld.volatile.shared.b32 %7, [%12+6272];\n"
      "st.relaxed.gpu.global.v4.u32 [%9], {o0, o1, o2, o3};\n"
      "ld.relaxed.gpu.global.u32 %8, [%9];\n}\n"
      : "+r"(q[0]), "+r"(q[1]), "+r"(q[2]), "+r"(q[3]), "+r"(q[4]), "+r"(q[5]), "+r"(q[6]), "+r"(q[7]), "=r"(rb)
      : "l"(wp), "r"(__float_as_int(sc)), "r"(qbar), "r"(qaddr), "r"(qpar)
      : "memory");
}

constexpr int PU = 4;
#define HEAVY 0xDB6D8u
__host__ __device__ constexpr int popc(unsigned v) { return v ? (v & 1) + popc(v >> 1) : 0; }
__host__ __device__ constexpr bool heavy(int n) { return (HEAVY >> n) & 1; }
__host__ __device__ constexpr int unit_at(int n) { return PU + popc(HEAVY & ((1u << n) - 1)); }
__host__ __device__ constexpr int emit_slot(int u) {
  if (u < PU) return u == PU - 1 ? 1 : -1;
  for (int n = 2; n < 24; n++)
    if (heavy(n) && unit_at(n) == u) return n;
  return 99;
}
__host__ __device__ constexpr int cmax(int a, int b) { return a > b ? a : b; }
__host__ __device__ constexpr int w_slot(int m) {
  return m == 15 ? cmax(emit_slot(15) + 3, 22) : cmax(2 * m - 5, emit_slot(m) + 3);
}
__host__ __device__ constexpr int q_slot(int u) {
  return u == 7 ? 2 : cmax(q_slot(u - 1) + 1, u - 5 < PU ? 2 : emit_slot(u - 5) + 2);
}
__host__ __device__ constexpr int w_at(int n) {
  for (int m = 2; m < NKB; m++)
    if (w_slot(m) == n) return m;
  return -1;
}
__host__ __device__ constexpr int q_at(int n) {
  for (int u = 7; u < NKB; u++)
    if (q_slot(u) == n) return u;
  return -1;
}
constexpr bool schedule_ok() {
  if (popc(HEAVY) != NKB - PU || (HEAVY & 3) || (HEAVY >> 20)) return false;
  for (int m = 2; m < NKB; m++) {
    if (w_at(w_slot(m)) != m || w_slot(m) > 23) return false;
    if (m < NR && w_slot(m) > 2 * m - 2) return false;
  }
  for (int u = 7; u < NKB; u++)
    if (q_slot(u) + 2 > emit_slot(u - 1)) return false;
  return true;
}
static_assert(schedule_ok(), "bad schedule");
template <int V>
struct IC {
  static constexpr int value = V;
};
template <int I, int N, class F>
__device__ __forceinline__ void static_for(F&& f) {
  if constexpr (I < N) {
    f(IC<I>{});
    static_for<I + 1, N>(f);
  }
}

#define PACE_B 350
#define PACE_Q1 500
#define PACE_Q2 1200
#define X1_AT 0
#define STAG 80
#define Q34_AT 1
#define PACE_X 450
#define X_FIRST (PACE_X < PACE_Q1)
#define PF_X 0
#define PF_Q 0

constexpr uint32_t sbase = 1024;

__global__ void __launch_bounds__(256, 1)
fused_kernel(const int* __restrict__ qw, const __nv_bfloat16* __restrict__ lut,
             const __nv_bfloat16* __restrict__ scales, __nv_bfloat16* __restrict__ out, uint8_t* scratch,
             const __grid_constant__ CUtensorMap tm_x, const __grid_constant__ CUtensorMap tm_q) {
  extern __shared__ __align__(1024) uint8_t smem_raw[];
  constexpr uint32_t bars = sbase + SMEM_BAR;
  const int j = blockIdx.x >> 3, it = blockIdx.x & 7;
  const int warp = __shfl_sync(0xffffffffu, threadIdx.x >> 5, 0);
  const int wg = warp >> 2;
  int lane;
  asm volatile("mov.u32 %0, %%laneid;" : "=r"(lane));
  const unsigned t_start = clk32();
  auto pace = [&](unsigned t) {
    while (__any_sync(0xffffffffu, clk32() - t_start < t)) {}
  };
  TL(0); TLG(1);

  uint8_t* const region = scratch + (size_t)j * REGION;
  uint8_t* const wp = region + W_OFF + it * W_KC + (warp * 32 + lane) * 16;
  unsigned* const fl = reinterpret_cast<unsigned*>(region) + lane;
  float lutv, sc;
  unsigned rb;
  const int xrow = it * BM + wg * 128;

  auto w_ptr = [&](int u) { return reinterpret_cast<uint4*>(wp + u * W_STAGE); };
  auto emit_unit = [&](const int (&qq)[8], int u) {
    st_strong128(w_ptr(u), convert_unit(qq, lutv, sc));
    rb = ld_strong(w_ptr(u));
  };
  auto publish = [&](int u, unsigned inc) {
    asm volatile(
        "{\n.reg .pred P, Q;\n"
        "setp.ne.u32 P, %1, 0xffffffff;\n"
        "vote.sync.all.pred P, P, 0xffffffff;\n"
        "setp.eq.and.s32 Q, %2, %3, P;\n"
        "@Q red.relaxed.gpu.global.add.u32 [%0], %4;\n}"
        ::"l"(fl), "r"(rb), "r"(lane), "r"(u), "r"(inc) : "memory");
  };
  auto load_x = [&](int g, int n, int kb, int half) {
    const uint32_t bar = ring(bars + 8 * B_FULLX, n) + g * 64;
    mbar_expect_tx(bar, X_SLICE);
    tma_load_2d(sbase + SMEM_X + (n % XS) * X_SLICE + g * (XS * X_SLICE), &tm_x, kb * BK,
                it * BM + g * 128 + half * 64, bar);
  };
  auto load_q = [&](int u) {
    const uint32_t bar = ring(bars + 8 * B_FULLQ, u);
    mbar_expect_tx(bar, Q_UNIT);
    tma_load_2d(sbase + SMEM_Q + (u & 3) * Q_UNIT, &tm_q, j * BN, u * BK + it * 8, bar);
  };
  auto prefetch_x = [&](int g) {
    if (PF_X) tma_prefetch_2d(&tm_x, (4 * g + (j >> 2)) * BK, it * BM + (j & 3) * 64);
  };
  auto prefetch_q = [&](int u) {
    if (PF_Q) tma_prefetch_2d(&tm_q, j * BN, u * BK + it * 8);
  };

  unsigned ready = 0;
  auto load_w = [&](uint32_t bar, int dst, int src, int bytes) {
    mbar_expect_tx(bar, bytes);
    bulk_load(sbase + SMEM_W + dst, region + W_OFF + src, bytes, bar);
  };
  auto poll = [&]() { ready |= __ballot_sync(0xffffffffu, ld_strong(fl) >= FLAG_FULL); };
  auto wait_ready = [&](int kb) {
    int spins = 0;
    while (!((ready >> kb) & 1)) {
      poll();
      if (++spins > (1 << 22)) __trap();
    }
  };

  uint32_t qbase;
  asm volatile("mov.u32 %0, %1;" : "=r"(qbase) : "r"(sbase + SMEM_Q + warp * 128 + perm32(lane) * 4));
  auto lds_unit = [&](int (&q)[8], int u) {
    ring_wait(bars + 8 * B_FULLQ, u);
#pragma unroll
    for (int i = 0; i < 8; i++) q[i] = lds32(qbase + (u & 3) * Q_UNIT + i * (BN * 4));
  };
  auto arrive_one = [&](uint32_t bar) {
    asm volatile("{\n.reg .pred P;\nelect.sync _|P, 0xffffffff;\n@P mbarrier.arrive.shared::cta.b64 _, [%0];\n}"
                 ::"r"(bar) : "memory");
  };

  int q[8];
  constexpr uint32_t bar_w0a = bars + 8 * B_FULLQ, bar_w0b = bars + 8 * B_FULLW, bar_w1 = bar_w0b + 8;
  unsigned issued = 0;
  int spins = 0;
  auto step = [&]() {
    ready |= __ballot_sync(0xffffffffu, rb >= FLAG_FULL);
    const unsigned go = ready & ~issued & 0x10007u;
    asm volatile("fence.proxy.async.global;" ::: "memory");
    rb = ld_strong(fl);
    if (go && elect_one()) {
      if (go & 0x10000) load_w(bar_w0a, 0, 0, W_STAGE / 2);
      if (go & 1) load_w(bar_w0b, W_STAGE / 2, W_STAGE / 2, W_STAGE / 2);
      if (go & 2) load_w(bar_w1, W_STAGE, W_STAGE, W_STAGE);
      if (go & 4) load_w(bar_w1 + 8, 2 * W_STAGE, 2 * W_STAGE, W_STAGE);
    }
    issued |= go;
    if (++spins > (1 << 22)) __trap();
  };
  if (warp == 7) {
    if (elect_one()) {
#pragma unroll
      for (int i = 0; i < B_COUNT; i++) mbar_init(bars + 8 * i, i >= B_DONE ? 4 : 1);
      asm volatile("fence.mbarrier_init.release.cluster;" ::: "memory");
    }
    __syncwarp();
    rb = ld_strong(fl);
    bar_arrive(0, 256);
    TL(4);
    lutv = 0.f;
    sc = 0.f;
    if (smem_u32(smem_raw) != sbase) __trap();
    if (X_FIRST) {
      pace(PACE_X);
      if (elect_one()) {
        load_x(0, 0, 0, 0); load_x(1, 0, 0, 0); load_x(0, 1, 0, 1); load_x(1, 1, 0, 1);
      }
    }
    pace(PACE_Q1 + it * STAG);
    if (elect_one()) load_q(1);
    if (!X_FIRST) {
      pace(PACE_X);
      if (elect_one()) {
        load_x(0, 0, 0, 0); load_x(1, 0, 0, 0); load_x(0, 1, 0, 1); load_x(1, 1, 0, 1);
      }
    }
    pace(PACE_Q2 + it * STAG);
    if (elect_one()) {
      load_q(2);
      if (j >= 4) prefetch_x(0);
    }
    step();
    if (X1_AT == 0 && elect_one()) {
      load_x(0, 2, 1, 0); load_x(1, 2, 1, 0); load_x(0, 3, 1, 1); load_x(1, 3, 1, 1);
    }
    if (X1_AT == 1) {
      if (elect_one()) { load_x(0, 2, 1, 0); load_x(1, 2, 1, 0); }
      step();
      if (elect_one()) { load_x(0, 3, 1, 1); load_x(1, 3, 1, 1); }
    }
    arrive_one(bars + 8 * B_DONE + 64);
    while (!(issued & 0x10000)) step();
    if (elect_one()) {
      load_q(3);
      if (Q34_AT == 0) load_q(4);
      if (X1_AT == 2) { load_x(0, 2, 1, 0); load_x(1, 2, 1, 0); load_x(0, 3, 1, 1); load_x(1, 3, 1, 1); }
    }
    TL(2);
    step();
    if (Q34_AT == 1 && elect_one()) load_q(4);
    while ((issued & 3) != 3) step();
    TL(3);
    mbar_wait(bars + 8 * B_DONE, 0);
    mbar_wait(bars + 8 * B_DONE + 64, 0);
    if (elect_one()) load_q(5);
  } else {
    const int fcol = j * BN + warp * 32 + perm32(lane);
    const int half = wg ^ (it & 1);
    const int kc = half * 4 + (it >> 1);
    if (half) {
      if ((warp & 3) == 0 && elect_one()) {
        asm volatile("prefetch.tensormap [%0];" ::"l"(&tm_x) : "memory");
        asm volatile("prefetch.tensormap [%0];" ::"l"(&tm_q) : "memory");
      }
      pace(PACE_B);
    }
    load_unit(q, qw + (size_t)(kc * 8) * F_DIM + fcol);
    const uint32_t lut_raw = ldg_u16(lut + (lane & 15)), sc_raw = ldg_u16(scales + fcol);
    bar_sync(0, 256);
    lutv = __uint_as_float(lut_raw << 16);
    sc = __uint_as_float(sc_raw << 16);
    uint8_t* p = wp + (kc - it) * W_KC;
    st_strong128(p, convert_unit(q, lutv, sc));
    rb = ld_strong(p);
    TL(2);
    publish(half ? 0 : 16, 2);
    TL(3);
    lds_unit(q, 1);
    emit_unit(q, 1);
    publish(1, 1);
    TL(4);
    lds_unit(q, 2);
    arrive_one(bars + 8 * B_DONE + wg * 64);
    if (wg == 1) {
      emit_unit(q, 2);
      publish(2, 1);
    }
  }

  float acc0[112], acc1[112];
  constexpr uint32_t DA_HI = (1u << 30) | (1024 >> 4), DB_HI = (128 >> 4);
  const uint32_t da0 = ((1u << 16) | ((sbase + SMEM_X) >> 4)) + wg * (XS * X_SLICE >> 4);
  constexpr uint32_t db0 = ((W_KC >> 4) << 16) | ((sbase + SMEM_W) >> 4);
  const uint32_t fullx = bars + 8 * B_FULLX + wg * 64, done = bars + 8 * B_DONE + wg * 64;
  const bool x_issuer = (warp & 3) == 3;

  auto mma = [&](float (&acc)[112], int n, int kb, int k0, int k1) {
    const int wslot = kb == 15 ? 4 : (kb & 3);
    wgmma_fence();
#pragma unroll
    for (int k = k0; k < k1; k++)
      wgmma_m64n224k16(acc, make_desc(da0 + (n % XS) * (X_SLICE >> 4) + k * 2, DA_HI),
                       make_desc(db0 + wslot * (W_STAGE >> 4) + k * (2 * W_KC >> 4), DB_HI), kb != 0 || k != 0);
    wgmma_commit();
  };
  auto end_slot = [&](int n) {
    wgmma_wait<1>();
    arrive_one(ring(done, n));
    if (x_issuer) {
      ring_wait(done, n);
      const int m = n + 4, e = (m - 2 * NR) & 3;
      if (elect_one())
        load_x(wg, m, m < 2 * NR ? m >> 1 : e < 2 ? NR + e : NR + 5 - e, m < 2 * NR ? m & 1 : (m - 2 * NR) >> 2);
    }
  };
  auto slot = [&](float (&acc)[112], auto N) {
    constexpr int n = decltype(N)::value;
    constexpr bool hv = heavy(n), pub = n == 2 || heavy(n - 1);
    ring_wait(fullx, n);
    mma(acc, n, n >> 1, 0, 4);
    if (hv && warp < 7) dequant_lookup(q, lutv);
    end_slot(n);
    if (warp < 7) {
      constexpr int u = unit_at(n);
      if (pub) publish(u - 1, 1);
      if (hv) {
        constexpr int un = u + 1 < NKB ? u + 1 : u;
        dequant_finish(q, rb, w_ptr(u), sc, ring(bars + 8 * B_FULLQ, un), un >> 3, qbase + (un & 3) * Q_UNIT);
      }
    } else {
      constexpr int m = w_at(n), u = q_at(n), m_next = w_at(n + 1);
      if (m >= 0 || u >= 0) ring_wait(bars + 8 * B_DONE, n - 1);
      if (m >= 0) {
        ready |= __ballot_sync(0xffffffffu, rb >= FLAG_FULL);
        wait_ready(m);
        asm volatile("fence.proxy.async.global;" ::: "memory");
      }
      if (m_next >= 0) rb = ld_strong(fl);
      if ((m >= 0 || u >= 0 || n == 4 || n == 10) && elect_one()) {
        if (m >= 0 && (m != 2 || !(issued & 4)))
          load_w(ring(bars + 8 * B_FULLW, m), (m == 15 ? 4 : m & 3) * W_STAGE, m * W_STAGE, W_STAGE);
        if (u >= 0) load_q(u);
        if (u >= 0 && u + 2 < NKB) prefetch_q(u + 2);
        if (n == 4 || n == 10) prefetch_x(n == 4 ? 2 : 3);
      }
    }
  };

  mbar_wait(bar_w0a, 0);
  mbar_wait(fullx, 0);
  TL(8); TLG(46);
  mma(acc0, 0, 0, 0, 2);
  mbar_wait(fullx + 8, 0);
  mma(acc1, 1, 0, 0, 2);
  if (wg == 0) emit_unit(q, 2);
  TL(5);
  mbar_wait(bar_w0b, 0);
  TL(9);
  mma(acc0, 0, 0, 2, 4);
  mma(acc1, 1, 0, 2, 4);
  if (warp < 7) {
    if (wg == 0) publish(2, 1);
    lds_unit(q, 3);
    emit_unit(q, 3);
    lds_unit(q, 4);
  } else {
    step();
    if (elect_one()) {
      load_q(6);
      load_x(0, 4, 2, 0); load_x(1, 4, 2, 0);
      prefetch_x(1);
    }
  }
  end_slot(1);
  if (warp == 7) step();

  static_for<1, NR>([&](auto R) {
    constexpr int r = decltype(R)::value;
    ring_wait(bars + 8 * B_FULLW, r);
    TL(8 + 2 * r);
    slot(acc0, IC<2 * r>{});
    TL(9 + 2 * r);
    slot(acc1, IC<2 * r + 1>{});
  });

  __nv_bfloat16* op = out + (size_t)(xrow + (warp & 3) * 16 + (lane >> 2)) * F_DIM + j * BN + (lane & 3) * 8;
  TL(40); TLG(48);
  if (wg == 1) bar_sync(1, 256);
#pragma unroll
  for (int e = 0; e < ENDK; e++) {
    const int kb = e < 2 ? NR + e : NR + 5 - e;
    ring_wait(bars + 8 * B_FULLW, kb);
    ring_wait(fullx, 2 * NR + e);
    mma(acc0, 2 * NR + e, kb, 0, 4);
    if (e == ENDK - 1) bar_arrive(1 + wg, 256);
    end_slot(2 * NR + e);
  }
  wgmma_wait<0>();
  TL(41);
  store_acc(acc0, op);
  TL(42);
  bar_sync(2 + wg, 256);
#pragma unroll
  for (int e = 0; e < ENDK; e++) {
    ring_wait(fullx, 2 * NR + ENDK + e);
    mma(acc1, 2 * NR + ENDK + e, e < 2 ? NR + e : NR + 5 - e, 0, 4);
  }
  if (wg == 0) bar_arrive(3, 256);
  wgmma_wait<0>();
  TL(43); TLG(47);
  store_acc(acc1, op + 64 * F_DIM);
  TL(44);
  if (warp == 0 && lane == 0) {
    if (atomicAdd(fl + 17, 1u) == NI - 1) {
#pragma unroll
      for (int u = 0; u <= 17; u++) fl[u] = 0;
    }
  }
}

typedef CUresult (*EncodeTiledFn)(CUtensorMap*, CUtensorMapDataType, cuuint32_t, void*, const cuuint64_t*,
                                  const cuuint64_t*, const cuuint32_t*, const cuuint32_t*, CUtensorMapInterleave,
                                  CUtensorMapSwizzle, CUtensorMapL2promotion, CUtensorMapFloatOOBfill);

}

#define XPROMO CU_TENSOR_MAP_L2_PROMOTION_L2_128B
extern "C" void kernel_launch(void* const* d_in, const int* in_sizes, int n_in, void* d_out, int out_size) {
  const __nv_bfloat16* x = (const __nv_bfloat16*)d_in[0];
  const int* qw = (const int*)d_in[1];
  const __nv_bfloat16* lut = (const __nv_bfloat16*)d_in[2];
  const __nv_bfloat16* scales = (const __nv_bfloat16*)d_in[3];
  __nv_bfloat16* out = (__nv_bfloat16*)d_out;

  static EncodeTiledFn enc = nullptr;
  static uint8_t* p_scr = nullptr;
  if (!enc) {
    void* fn = nullptr;
    cudaDriverEntryPointQueryResult qr;
    cudaGetDriverEntryPoint("cuTensorMapEncodeTiled", &fn, cudaEnableDefault, &qr);
    enc = (EncodeTiledFn)fn;
    void* p = nullptr;
    cudaGetSymbolAddress(&p, g_scratch);
    p_scr = (uint8_t*)(((uintptr_t)p + REGION - 1) & ~(uintptr_t)(REGION - 1));
    cudaFuncSetAttribute(fused_kernel, cudaFuncAttributeMaxDynamicSharedMemorySize, SMEM_TOTAL);
  }
  CUtensorMap tm_x, tm_q;
  cuuint32_t estr[2] = {1, 1};
  {
    cuuint64_t gdim[2] = {(cuuint64_t)D_DIM, (cuuint64_t)S_DIM};
    cuuint64_t gstr[1] = {(cuuint64_t)D_DIM * 2};
    cuuint32_t box[2] = {(cuuint32_t)BK, 64};
    enc(&tm_x, CU_TENSOR_MAP_DATA_TYPE_BFLOAT16, 2, (void*)x, gdim, gstr, box, estr, CU_TENSOR_MAP_INTERLEAVE_NONE,
        CU_TENSOR_MAP_SWIZZLE_128B, XPROMO, CU_TENSOR_MAP_FLOAT_OOB_FILL_NONE);
  }
  {
    cuuint64_t gdim[2] = {(cuuint64_t)F_DIM, (cuuint64_t)D_DIM};
    cuuint64_t gstr[1] = {(cuuint64_t)F_DIM * 4};
    cuuint32_t box[2] = {(cuuint32_t)BN, 8};
    enc(&tm_q, CU_TENSOR_MAP_DATA_TYPE_INT32, 2, (void*)qw, gdim, gstr, box, estr, CU_TENSOR_MAP_INTERLEAVE_NONE,
        CU_TENSOR_MAP_SWIZZLE_NONE, CU_TENSOR_MAP_L2_PROMOTION_NONE, CU_TENSOR_MAP_FLOAT_OOB_FILL_NONE);
  }
  fused_kernel<<<NI * NJ, 256, SMEM_TOTAL, cudaStreamPerThread>>>(qw, lut, scales, out, p_scr, tm_x, tm_q);
}
```

```cpp
#include <cuda_runtime.h>
#include <cuda_bf16.h>
#include <cuda.h>
#include <stdint.h>

namespace {

constexpr int S_DIM = 2048, D_DIM = 1024, F_DIM = 3584;
constexpr int BM = 256, BN = 224, BK = 64;
constexpr int NKB = D_DIM / BK;
constexpr int NJ = F_DIM / BN;
constexpr int NI = S_DIM / BM;
constexpr int WS = 4;
constexpr int XS = 5;
constexpr int ENDK = 4;
constexpr int NR = NKB - ENDK;
constexpr int X_SLICE = 64 * BK * 2;
constexpr int W_STAGE = BN * BK * 2;
constexpr int W_KC = BN * 16;

constexpr int REGION = 512 * 1024;
__device__ uint4 g_scratch[(NJ + 1) * REGION / 16];

__device__ __forceinline__ uint32_t smem_u32(const void* p) { return (uint32_t)__cvta_generic_to_shared(p); }
__device__ __forceinline__ unsigned clk32() {
  unsigned c;
  asm volatile("mov.u32 %0, %%clock;" : "=r"(c)::"memory");
  return c;
}
__device__ __forceinline__ bool elect_one() {
  uint32_t p;
  asm volatile("{\n.reg .pred P;\nelect.sync _|P, 0xffffffff;\nselp.b32 %0, 1, 0, P;\n}" : "=r"(p));
  return p != 0;
}
__device__ __forceinline__ void mbar_init(uint32_t bar, uint32_t cnt) {
  asm volatile("mbarrier.init.shared::cta.b64 [%0], %1;" ::"r"(bar), "r"(cnt) : "memory");
}
__device__ __forceinline__ void mbar_expect_tx(uint32_t bar, uint32_t bytes) {
  asm volatile("mbarrier.arrive.expect_tx.shared::cta.b64 _, [%0], %1;" ::"r"(bar), "r"(bytes) : "memory");
}
__device__ __forceinline__ void mbar_arrive(uint32_t bar) {
  asm volatile("mbarrier.arrive.shared::cta.b64 _, [%0];" ::"r"(bar) : "memory");
}
__device__ __forceinline__ bool mbar_test(uint32_t bar, uint32_t parity) {
  uint32_t ok;
  asm volatile(
      "{\n.reg .pred p;\nmbarrier.test_wait.parity.shared::cta.b64 p, [%1], %2;\nselp.b32 %0, 1, 0, p;\n}\n"
      : "=r"(ok) : "r"(bar), "r"(parity) : "memory");
  return ok != 0;
}
__device__ __forceinline__ void mbar_wait(uint32_t bar, uint32_t parity) {
  asm volatile(
      "{\n.reg .pred p;\n"
      "LAB_WAIT:\n"
      "mbarrier.try_wait.parity.shared::cta.b64 p, [%0], %1;\n"
      "@p bra LAB_DONE;\n"
      "bra LAB_WAIT;\n"
      "LAB_DONE:\n}\n" ::"r"(bar), "r"(parity) : "memory");
}
__device__ __forceinline__ uint32_t ring(uint32_t base, int i) { return base + 8 * (i & 7); }
__device__ __forceinline__ void ring_wait(uint32_t base, int i) { mbar_wait(ring(base, i), (i >> 3) & 1); }
__device__ __forceinline__ void tma_load_2d(uint32_t dst, const CUtensorMap* tm, int c0, int c1, uint32_t bar) {
  asm volatile(
      "cp.async.bulk.tensor.2d.shared::cluster.global.mbarrier::complete_tx::bytes [%0], [%1, {%3, %4}], [%2];"
      ::"r"(dst), "l"(tm), "r"(bar), "r"(c0), "r"(c1) : "memory");
}
__device__ __forceinline__ void tma_prefetch_2d(const CUtensorMap* tm, int c0, int c1) {
  asm volatile("cp.async.bulk.prefetch.tensor.2d.L2.global [%0, {%1, %2}];" ::"l"(tm), "r"(c0), "r"(c1) : "memory");
}
__device__ __forceinline__ void bulk_load(uint32_t dst, const void* src, uint32_t bytes, uint32_t bar) {
  asm volatile(
      "cp.async.bulk.shared::cluster.global.mbarrier::complete_tx::bytes [%0], [%1], %2, [%3];"
      ::"r"(dst), "l"(src), "r"(bytes), "r"(bar) : "memory");
}
__device__ __forceinline__ int ldg_stream(const int* p) {
  int v;
  asm volatile("ld.global.L1::no_allocate.b32 %0, [%1];" : "=r"(v) : "l"(p) : "memory");
  return v;
}
__device__ __forceinline__ uint32_t ldg_u16(const void* p) {
  uint32_t v;
  asm volatile("ld.global.u16 %0, [%1];" : "=r"(v) : "l"(p) : "memory");
  return v;
}
__device__ __forceinline__ int lds32(uint32_t addr) {
  int v;
  asm volatile("ld.shared.b32 %0, [%1];" : "=r"(v) : "r"(addr) : "memory");
  return v;
}
__device__ __forceinline__ void sts128(uint32_t addr, uint4 v) {
  asm volatile("st.shared.v4.u32 [%0], {%1, %2, %3, %4};" ::"r"(addr), "r"(v.x), "r"(v.y), "r"(v.z), "r"(v.w) : "memory");
}
__device__ __forceinline__ uint64_t make_desc(uint32_t lo, uint32_t hi) {
  uint64_t d;
  asm("mov.b64 %0, {%1, %2};" : "=l"(d) : "r"(lo), "r"(hi));
  return d;
}
__device__ __forceinline__ unsigned ld_strong(const void* p) {
  unsigned v;
  asm volatile("ld.relaxed.gpu.global.u32 %0, [%1];" : "=r"(v) : "l"(p) : "memory");
  return v;
}
__device__ __forceinline__ void st_strong128(void* p, uint4 v) {
  asm volatile("st.relaxed.gpu.global.v4.u32 [%0], {%1, %2, %3, %4};" ::"l"(p), "r"(v.x), "r"(v.y), "r"(v.z), "r"(v.w)
               : "memory");
}
__device__ __forceinline__ void wgmma_fence() { asm volatile("wgmma.fence.sync.aligned;" ::: "memory"); }
__device__ __forceinline__ void wgmma_commit() { asm volatile("wgmma.commit_group.sync.aligned;" ::: "memory"); }
template <int N>
__device__ __forceinline__ void wgmma_wait() { asm volatile("wgmma.wait_group.sync.aligned %0;" ::"n"(N) : "memory"); }
__device__ __forceinline__ void bar_sync(int id, int n) { asm volatile("bar.sync %0, %1;" ::"r"(id), "r"(n) : "memory"); }
__device__ __forceinline__ void bar_arrive(int id, int n) { asm volatile("bar.arrive %0, %1;" ::"r"(id), "r"(n) : "memory"); }

__device__ __forceinline__ void wgmma_m64n224k16(float (&d)[112], uint64_t da, uint64_t db, int scale_d) {
  asm volatile(
    "{\n.reg .pred p;\nsetp.ne.b32 p, %114, 0;\n"
    "wgmma.mma_async.sync.aligned.m64n224k16.f32.bf16.bf16 "
    "{%0, %1, %2, %3, %4, %5, %6, %7, %8, %9, %10, %11, %12, %13, %14, %15, "
    "%16, %17, %18, %19, %20, %21, %22, %23, %24, %25, %26, %27, %28, %29, %30, %31, "
    "%32, %33, %34, %35, %36, %37, %38, %39, %40, %41, %42, %43, %44, %45, %46, %47, "
    "%48, %49, %50, %51, %52, %53, %54, %55, %56, %57, %58, %59, %60, %61, %62, %63, "
    "%64, %65, %66, %67, %68, %69, %70, %71, %72, %73, %74, %75, %76, %77, %78, %79, "
    "%80, %81, %82, %83, %84, %85, %86, %87, %88, %89, %90, %91, %92, %93, %94, %95, "
    "%96, %97, %98, %99, %100, %101, %102, %103, %104, %105, %106, %107, %108, %109, %110, %111}, "
    "%112, %113, p, 1, 1, 0, 0;\n}\n"
    : "+f"(d[0]), "+f"(d[1]), "+f"(d[2]), "+f"(d[3]), "+f"(d[4]), "+f"(d[5]), "+f"(d[6]), "+f"(d[7]),
      "+f"(d[8]), "+f"(d[9]), "+f"(d[10]), "+f"(d[11]), "+f"(d[12]), "+f"(d[13]), "+f"(d[14]), "+f"(d[15]),
      "+f"(d[16]), "+f"(d[17]), "+f"(d[18]), "+f"(d[19]), "+f"(d[20]), "+f"(d[21]), "+f"(d[22]), "+f"(d[23]),
      "+f"(d[24]), "+f"(d[25]), "+f"(d[26]), "+f"(d[27]), "+f"(d[28]), "+f"(d[29]), "+f"(d[30]), "+f"(d[31]),
      "+f"(d[32]), "+f"(d[33]), "+f"(d[34]), "+f"(d[35]), "+f"(d[36]), "+f"(d[37]), "+f"(d[38]), "+f"(d[39]),
      "+f"(d[40]), "+f"(d[41]), "+f"(d[42]), "+f"(d[43]), "+f"(d[44]), "+f"(d[45]), "+f"(d[46]), "+f"(d[47]),
      "+f"(d[48]), "+f"(d[49]), "+f"(d[50]), "+f"(d[51]), "+f"(d[52]), "+f"(d[53]), "+f"(d[54]), "+f"(d[55]),
      "+f"(d[56]), "+f"(d[57]), "+f"(d[58]), "+f"(d[59]), "+f"(d[60]), "+f"(d[61]), "+f"(d[62]), "+f"(d[63]),
      "+f"(d[64]), "+f"(d[65]), "+f"(d[66]), "+f"(d[67]), "+f"(d[68]), "+f"(d[69]), "+f"(d[70]), "+f"(d[71]),
      "+f"(d[72]), "+f"(d[73]), "+f"(d[74]), "+f"(d[75]), "+f"(d[76]), "+f"(d[77]), "+f"(d[78]), "+f"(d[79]),
      "+f"(d[80]), "+f"(d[81]), "+f"(d[82]), "+f"(d[83]), "+f"(d[84]), "+f"(d[85]), "+f"(d[86]), "+f"(d[87]),
      "+f"(d[88]), "+f"(d[89]), "+f"(d[90]), "+f"(d[91]), "+f"(d[92]), "+f"(d[93]), "+f"(d[94]), "+f"(d[95]),
      "+f"(d[96]), "+f"(d[97]), "+f"(d[98]), "+f"(d[99]), "+f"(d[100]), "+f"(d[101]), "+f"(d[102]), "+f"(d[103]),
      "+f"(d[104]), "+f"(d[105]), "+f"(d[106]), "+f"(d[107]), "+f"(d[108]), "+f"(d[109]), "+f"(d[110]), "+f"(d[111])
    : "l"(da), "l"(db), "r"(scale_d));
}

__device__ __forceinline__ uint32_t pack_bf16(float lo, float hi) {
  uint32_t r;
  asm("cvt.rn.bf16x2.f32 %0, %1, %2;" : "=r"(r) : "f"(hi), "f"(lo));
  return r;
}

__device__ __forceinline__ int perm32(int n) { return (n & ~30) | ((n & 6) << 2) | ((n >> 2) & 6); }

constexpr int SMEM_X = 0;
constexpr int SMEM_W = 2 * XS * X_SLICE;
constexpr int SMEM_Q = SMEM_W + WS * W_STAGE;
constexpr int Q_UNIT = 8 * BN * 4;
constexpr int SMEM_BAR = SMEM_Q + W_STAGE;
constexpr int B_FULLW = 0, B_FULLQ = 8, B_FULLX = 16, B_DONE = 32, B_W0 = 48, B_RAW0 = 49, B_COUNT = 57;
constexpr int SMEM_TL = SMEM_BAR + B_COUNT * 8;
constexpr int SMEM_TOTAL = SMEM_TL + 2048;
constexpr int W_OFF = 128;
constexpr unsigned FLAG_FULL = NI * 7;

#define TL(i)
#define TLG(i)

__device__ __forceinline__ void store_acc(const float (&a)[112], __nv_bfloat16* p) {
#pragma unroll
  for (int J = 0; J < 7; J++) {
    uint4 v0, v1;
    v0.x = pack_bf16(a[16 * J + 0], a[16 * J + 1]);
    v0.y = pack_bf16(a[16 * J + 4], a[16 * J + 5]);
    v0.z = pack_bf16(a[16 * J + 8], a[16 * J + 9]);
    v0.w = pack_bf16(a[16 * J + 12], a[16 * J + 13]);
    v1.x = pack_bf16(a[16 * J + 2], a[16 * J + 3]);
    v1.y = pack_bf16(a[16 * J + 6], a[16 * J + 7]);
    v1.z = pack_bf16(a[16 * J + 10], a[16 * J + 11]);
    v1.w = pack_bf16(a[16 * J + 14], a[16 * J + 15]);
    *reinterpret_cast<uint4*>(p + 32 * J) = v0;
    *reinterpret_cast<uint4*>(p + 8 * F_DIM + 32 * J) = v1;
  }
}

__device__ __forceinline__ void load_unit(int (&q)[8], const int* p) {
#pragma unroll
  for (int i = 0; i < 8; i++) q[i] = ldg_stream(p + i * F_DIM);
}
__device__ __forceinline__ uint4 convert_unit(const int (&q)[8], float lutv, float sc) {
  float v[8];
#pragma unroll
  for (int i = 0; i < 8; i++) v[i] = __shfl_sync(0xffffffffu, lutv, q[i]) * sc;
  uint4 o;
  o.x = pack_bf16(v[0], v[1]);
  o.y = pack_bf16(v[2], v[3]);
  o.z = pack_bf16(v[4], v[5]);
  o.w = pack_bf16(v[6], v[7]);
  return o;
}

__device__ __forceinline__ void dequant_lookup(int (&q)[8], float lutv) {
  asm volatile(
      "shfl.sync.idx.b32 %0, %8, %0, 31, 0xffffffff;\n"
      "shfl.sync.idx.b32 %1, %8, %1, 31, 0xffffffff;\n"
      "shfl.sync.idx.b32 %2, %8, %2, 31, 0xffffffff;\n"
      "shfl.sync.idx.b32 %3, %8, %3, 31, 0xffffffff;\n"
      "shfl.sync.idx.b32 %4, %8, %4, 31, 0xffffffff;\n"
      "shfl.sync.idx.b32 %5, %8, %5, 31, 0xffffffff;\n"
      "shfl.sync.idx.b32 %6, %8, %6, 31, 0xffffffff;\n"
      "shfl.sync.idx.b32 %7, %8, %7, 31, 0xffffffff;\n"
      : "+r"(q[0]), "+r"(q[1]), "+r"(q[2]), "+r"(q[3]), "+r"(q[4]), "+r"(q[5]), "+r"(q[6]), "+r"(q[7])
      : "r"(__float_as_int(lutv)));
}
__device__ __forceinline__ void dequant_finish(int (&q)[8], unsigned& rb, uint4* wp, float sc, uint32_t qbar,
                                               uint32_t qpar, uint32_t qaddr) {
  asm volatile(
      "{\n.reg .pred W;\n.reg .b32 o0, o1, o2, o3;\n"
      "DQ_WAIT:\n"
      "mbarrier.try_wait.parity.shared::cta.b64 W, [%11], %13;\n"
      "@!W bra DQ_WAIT;\n"
      "mul.rn.f32 %0, %0, %10;\nmul.rn.f32 %1, %1, %10;\nmul.rn.f32 %2, %2, %10;\nmul.rn.f32 %3, %3, %10;\n"
      "mul.rn.f32 %4, %4, %10;\nmul.rn.f32 %5, %5, %10;\nmul.rn.f32 %6, %6, %10;\nmul.rn.f32 %7, %7, %10;\n"
      "cvt.rn.bf16x2.f32 o0, %1, %0;\ncvt.rn.bf16x2.f32 o1, %3, %2;\n"
      "cvt.rn.bf16x2.f32 o2, %5, %4;\ncvt.rn.bf16x2.f32 o3, %7, %6;\n"
      "ld.volatile.shared.b32 %0, [%12];\nld.volatile.shared.b32 %1, [%12+896];\n"
      "ld.volatile.shared.b32 %2, [%12+1792];\nld.volatile.shared.b32 %3, [%12+2688];\n"
      "ld.volatile.shared.b32 %4, [%12+3584];\nld.volatile.shared.b32 %5, [%12+4480];\n"
      "ld.volatile.shared.b32 %6, [%12+5376];\nld.volatile.shared.b32 %7, [%12+6272];\n"
      "st.relaxed.gpu.global.v4.u32 [%9], {o0, o1, o2, o3};\n"
      "ld.relaxed.gpu.global.u32 %8, [%9];\n}\n"
      : "+r"(q[0]), "+r"(q[1]), "+r"(q[2]), "+r"(q[3]), "+r"(q[4]), "+r"(q[5]), "+r"(q[6]), "+r"(q[7]), "=r"(rb)
      : "l"(wp), "r"(__float_as_int(sc)), "r"(qbar), "r"(qaddr), "r"(qpar)
      : "memory");
}

constexpr int PU = 3;
#define HEAVY 0xDB6DAu
__host__ __device__ constexpr int popc(unsigned v) { return v ? (v & 1) + popc(v >> 1) : 0; }
__host__ __device__ constexpr bool heavy(int n) { return n >= 0 && ((HEAVY >> n) & 1); }
__host__ __device__ constexpr int unit_at(int n) { return PU + popc(HEAVY & ((1u << n) - 1)); }
__host__ __device__ constexpr int emit_slot(int u) {
  if (u < PU) return -1;
  for (int n = 0; n < 24; n++)
    if (heavy(n) && unit_at(n) == u) return n;
  return 99;
}
__host__ __device__ constexpr int cmax(int a, int b) { return a > b ? a : b; }
__host__ __device__ constexpr int w_slot(int m) {
  return m == 15 ? cmax(emit_slot(15) + 3, 22) : cmax(2 * m - 5, emit_slot(m) + 3);
}
__host__ __device__ constexpr int q_slot(int u) {
  return u == 5 ? 0 : cmax(q_slot(u - 1) + 1, u - 5 < PU ? u - 5 : emit_slot(u - 5) + 2);
}
__host__ __device__ constexpr int w_at(int n) {
  for (int m = 2; m < NKB; m++)
    if (w_slot(m) == n) return m;
  return -1;
}
__host__ __device__ constexpr int q_at(int n) {
  for (int u = 5; u < NKB; u++)
    if (q_slot(u) == n) return u;
  return -1;
}
constexpr bool schedule_ok() {
  if (popc(HEAVY) != NKB - PU || (HEAVY & 1) || (HEAVY >> 20)) return false;
  for (int m = 2; m < NKB; m++) {
    if (w_at(w_slot(m)) != m || w_slot(m) > 23) return false;
    if (m < NR && w_slot(m) > 2 * m - 2) return false;
  }
  for (int u = 5; u < NKB; u++)
    if (q_slot(u) + 2 > emit_slot(u - 1)) return false;
  return true;
}
static_assert(schedule_ok(), "bad schedule");
template <int V>
struct IC {
  static constexpr int value = V;
};
template <int I, int N, class F>
__device__ __forceinline__ void static_for(F&& f) {
  if constexpr (I < N) {
    f(IC<I>{});
    static_for<I + 1, N>(f);
  }
}

#define U1_FIRST 1
#define PACE_L 0
#define STAG_L 80
#define PACE_U1 600
#define PACE_X 1400
#define PACE_Q2 1600
#define PACE_Q3 2600
#define STAG 60
#define EMIT_AT -1
#define PUB_AT 4
#define PF_X 0
#define PF_Q 0

constexpr uint32_t sbase = 1024;

__global__ void __launch_bounds__(256, 1)
fused_kernel(const int* __restrict__ qw, const __nv_bfloat16* __restrict__ lut,
             const __nv_bfloat16* __restrict__ scales, __nv_bfloat16* __restrict__ out, uint8_t* scratch,
             const __grid_constant__ CUtensorMap tm_x, const __grid_constant__ CUtensorMap tm_q) {
  extern __shared__ __align__(1024) uint8_t smem_raw[];
  constexpr uint32_t bars = sbase + SMEM_BAR;
  const int j = blockIdx.x >> 3, it = blockIdx.x & 7;
  const int warp = __shfl_sync(0xffffffffu, threadIdx.x >> 5, 0);
  const int wg = warp >> 2;
  int lane;
  asm volatile("mov.u32 %0, %%laneid;" : "=r"(lane));
  const unsigned t_start = clk32();
  auto pace = [&](unsigned t) {
    while (__any_sync(0xffffffffu, clk32() - t_start < t)) {}
  };
  TL(0); TLG(1);

  uint8_t* const region = scratch + (size_t)j * REGION;
  uint8_t* const wp = region + W_OFF + it * W_KC + (warp * 32 + lane) * 16;
  unsigned* const fl = reinterpret_cast<unsigned*>(region) + lane;
  float lutv, sc;
  unsigned rb;
  const int xrow = it * BM + wg * 128;

  auto w_ptr = [&](int u) { return reinterpret_cast<uint4*>(wp + u * W_STAGE); };
  auto emit_unit = [&](const int (&qq)[8], int u) {
    st_strong128(w_ptr(u), convert_unit(qq, lutv, sc));
    rb = ld_strong(w_ptr(u));
  };
  auto publish = [&](int u, unsigned inc) {
    asm volatile(
        "{\n.reg .pred P, Q;\n"
        "setp.ne.u32 P, %1, 0xffffffff;\n"
        "vote.sync.all.pred P, P, 0xffffffff;\n"
        "setp.eq.and.s32 Q, %2, %3, P;\n"
        "@Q red.relaxed.gpu.global.add.u32 [%0], %4;\n}"
        ::"l"(fl), "r"(rb), "r"(lane), "r"(u), "r"(inc) : "memory");
  };
  auto load_x = [&](int g, int n, int kb, int half) {
    const uint32_t bar = ring(bars + 8 * B_FULLX, n) + g * 64;
    mbar_expect_tx(bar, X_SLICE);
    tma_load_2d(sbase + SMEM_X + (n % XS) * X_SLICE + g * (XS * X_SLICE), &tm_x, kb * BK,
                it * BM + g * 128 + half * 64, bar);
  };
  auto load_q = [&](int u) {
    const uint32_t bar = ring(bars + 8 * B_FULLQ, u);
    mbar_expect_tx(bar, Q_UNIT);
    tma_load_2d(sbase + SMEM_Q + (u & 3) * Q_UNIT, &tm_q, j * BN, u * BK + it * 8, bar);
  };
  auto prefetch_x = [&](int g) {
    if (PF_X) tma_prefetch_2d(&tm_x, (4 * g + (j >> 2)) * BK, it * BM + (j & 3) * 64);
  };
  auto prefetch_q = [&](int u) {
    if (PF_Q) tma_prefetch_2d(&tm_q, j * BN, u * BK + it * 8);
  };

  unsigned ready = 0;
  auto load_w = [&](uint32_t bar, int dst, int src, int bytes) {
    mbar_expect_tx(bar, bytes);
    bulk_load(sbase + SMEM_W + dst, region + W_OFF + src, bytes, bar);
  };
  auto poll = [&]() { ready |= __ballot_sync(0xffffffffu, ld_strong(fl) >= FLAG_FULL); };
  auto wait_ready = [&](int kb) {
    int spins = 0;
    while (!((ready >> kb) & 1)) {
      poll();
      if (++spins > (1 << 22)) __trap();
    }
  };

  uint32_t qbase;
  asm volatile("mov.u32 %0, %1;" : "=r"(qbase) : "r"(sbase + SMEM_Q + warp * 128 + perm32(lane) * 4));
  auto lds_unit = [&](int (&q)[8], int u) {
    ring_wait(bars + 8 * B_FULLQ, u);
#pragma unroll
    for (int i = 0; i < 8; i++) q[i] = lds32(qbase + (u & 3) * Q_UNIT + i * (BN * 4));
  };
  auto arrive_one = [&](uint32_t bar) {
    asm volatile("{\n.reg .pred P;\nelect.sync _|P, 0xffffffff;\n@P mbarrier.arrive.shared::cta.b64 _, [%0];\n}"
                 ::"r"(bar) : "memory");
  };

  int q[8];
  constexpr uint32_t raw0 = sbase + SMEM_W + 2 * W_STAGE;
  const int fcol = j * BN + (warp < 7 ? warp : 0) * 32 + perm32(lane);
  if (elect_one()) {
    mbar_init(bars + 8 * B_RAW0 + 8 * warp, 1);
    if (warp == 7) {
#pragma unroll
      for (int i = 0; i < B_RAW0; i++) mbar_init(bars + 8 * i, i == B_W0 ? 7 : i >= B_DONE ? 4 : 1);
    }
    asm volatile("fence.mbarrier_init.release.cluster;" ::: "memory");
    if (warp == 6) {
      asm volatile("prefetch.tensormap [%0];" ::"l"(&tm_q) : "memory");
      asm volatile("prefetch.tensormap [%0];" ::"l"(&tm_x) : "memory");
    }
  }
  uint32_t lut_raw = 0, sc_raw = 0;
  if (warp < 7) {
    if (U1_FIRST) load_unit(q, qw + (size_t)(BK + it * 8) * F_DIM + fcol);
    lut_raw = ldg_u16(lut + (lane & 15));
    sc_raw = ldg_u16(scales + fcol);
  }
  pace(PACE_L + warp * STAG_L);
  if (elect_one()) {
    mbar_expect_tx(bars + 8 * B_RAW0 + 8 * warp, Q_UNIT);
#pragma unroll
    for (int i = 0; i < 8; i++)
      bulk_load(raw0 + (warp * 8 + i) * (BN * 4), qw + (size_t)(warp * 8 + i) * F_DIM + j * BN, BN * 4,
                bars + 8 * B_RAW0 + 8 * warp);
  }
  if (warp == 7) {
    rb = ld_strong(fl);
    bar_arrive(0, 256);
    TL(4);
    lutv = 0.f;
    sc = 0.f;
    if (smem_u32(smem_raw) != sbase) __trap();
    pace(PACE_U1 + it * STAG);
    if (elect_one()) {
      mbar_arrive(bars + 8 * B_FULLW);
      mbar_arrive(bars + 8 * B_FULLQ);
      if (U1_FIRST) mbar_arrive(bars + 8 * B_FULLQ + 8);
      else load_q(1);
    }
    pace(PACE_X);
    if (elect_one()) {
      load_x(0, 0, 0, 0); load_x(1, 0, 0, 0); load_x(0, 1, 0, 1); load_x(1, 1, 0, 1);
    }
    pace(PACE_Q2 + it * STAG);
    if (elect_one()) load_q(2);
    pace(PACE_Q3 + it * STAG);
    ready = __ballot_sync(0xffffffffu, rb >= FLAG_FULL);
    rb = ld_strong(fl);
    if (elect_one()) {
      load_q(3);
      load_x(0, 2, 1, 0); load_x(1, 2, 1, 0); load_x(0, 3, 1, 1); load_x(1, 3, 1, 1);
    }
    ready |= __ballot_sync(0xffffffffu, rb >= FLAG_FULL);
    wait_ready(1);
    asm volatile("fence.proxy.async.global;" ::: "memory");
    if (elect_one()) {
      load_w(bars + 8 * B_FULLW + 8, W_STAGE, W_STAGE, W_STAGE);
      load_q(4);
      load_x(0, 4, 2, 0); load_x(1, 4, 2, 0);
    }
    TL(2);
    TL(3);
  } else {
    bar_sync(0, 256);
    asm volatile("shl.b32 %0, %0, 16;\nshl.b32 %1, %1, 16;" : "+r"(lut_raw), "+r"(sc_raw));
    lutv = __uint_as_float(lut_raw);
    sc = __uint_as_float(sc_raw);
    int r[2][8];
    auto lds_raw0 = [&](int c) {
      mbar_wait(bars + 8 * B_RAW0 + 8 * c, 0);
#pragma unroll
      for (int i = 0; i < 8; i++) r[c & 1][i] = lds32(qbase + (raw0 - sbase - SMEM_Q) + (c * 8 + i) * (BN * 4));
    };
    if (EMIT_AT < 0) {
      emit_unit(q, 1);
      TL(2);
    }
    lds_raw0(0);
    TL(6);
#pragma unroll
    for (int c = 0; c < 8; c++) {
      if (c == EMIT_AT) {
        if (!U1_FIRST) lds_unit(q, 1);
        emit_unit(q, 1);
        TL(2);
      }
      if (c == PUB_AT) {
        publish(1, 1);
        TL(3);
      }
      if (c < 7) lds_raw0(c + 1);
      sts128(sbase + SMEM_W + c * W_KC + (warp * 32 + lane) * 16, convert_unit(r[c & 1], lutv, sc));
    }
    asm volatile("fence.proxy.async.shared::cta;" ::: "memory");
    __syncwarp();
    arrive_one(bars + 8 * B_W0);
    if (PUB_AT == 8) {
      publish(1, 1);
      TL(3);
    }
    TL(4);
    lds_unit(q, 2);
    emit_unit(q, 2);
    TL(5);
  }

  float acc0[112], acc1[112];
  constexpr uint32_t DA_HI = (1u << 30) | (1024 >> 4), DB_HI = (128 >> 4);
  const uint32_t da0 = ((1u << 16) | ((sbase + SMEM_X) >> 4)) + wg * (XS * X_SLICE >> 4);
  constexpr uint32_t db0 = ((W_KC >> 4) << 16) | ((sbase + SMEM_W) >> 4);
  const uint32_t fullx = bars + 8 * B_FULLX + wg * 64, done = bars + 8 * B_DONE + wg * 64;
  const bool x_issuer = (warp & 3) == 3;

  auto mma = [&](float (&acc)[112], int n, int kb, int k0, int k1) {
    const int wslot = kb == 15 ? 4 : (kb & 3);
    wgmma_fence();
#pragma unroll
    for (int k = k0; k < k1; k++)
      wgmma_m64n224k16(acc, make_desc(da0 + (n % XS) * (X_SLICE >> 4) + k * 2, DA_HI),
                       make_desc(db0 + wslot * (W_STAGE >> 4) + k * (2 * W_KC >> 4), DB_HI), kb != 0 || k != 0);
    wgmma_commit();
  };
  auto end_slot = [&](int n) {
    wgmma_wait<1>();
    arrive_one(ring(done, n));
    if (x_issuer) {
      ring_wait(done, n);
      const int m = n + 4, e = (m - 2 * NR) & 3;
      if (n > 0 && elect_one())
        load_x(wg, m, m < 2 * NR ? m >> 1 : e < 2 ? NR + e : NR + 5 - e, m < 2 * NR ? m & 1 : (m - 2 * NR) >> 2);
    }
  };
  auto slot = [&](float (&acc)[112], auto N) {
    constexpr int n = decltype(N)::value;
    constexpr bool hv = heavy(n), pub = n == 0 || heavy(n - 1);
    ring_wait(fullx, n);
    mma(acc, n, n >> 1, 0, 4);
    if (hv && warp < 7) dequant_lookup(q, lutv);
    end_slot(n);
    if (warp < 7) {
      constexpr int u = unit_at(n);
      if (pub) publish(u - 1, 1);
      if (n == 0) lds_unit(q, PU);
      if (hv) {
        constexpr int un = u + 1 < NKB ? u + 1 : u;
        dequant_finish(q, rb, w_ptr(u), sc, ring(bars + 8 * B_FULLQ, un), un >> 3, qbase + (un & 3) * Q_UNIT);
      }
    } else {
      constexpr int m = w_at(n), u = q_at(n), m_next = w_at(n + 1);
      if (n > 0 && (m >= 0 || u >= 0)) ring_wait(bars + 8 * B_DONE, n - 1);
      if (m >= 0) {
        ready |= __ballot_sync(0xffffffffu, rb >= FLAG_FULL);
        wait_ready(m);
        asm volatile("fence.proxy.async.global;" ::: "memory");
      }
      if (m_next >= 0) rb = ld_strong(fl);
      if ((m >= 0 || u >= 0 || n == 4 || n == 10) && elect_one()) {
        if (m >= 0)
          load_w(ring(bars + 8 * B_FULLW, m), (m == 15 ? 4 : m & 3) * W_STAGE, m * W_STAGE, W_STAGE);
        if (u >= 0) load_q(u);
        if (u >= 0 && u + 2 < NKB) prefetch_q(u + 2);
        if (n == 4 || n == 10) prefetch_x(n == 4 ? 2 : 3);
      }
    }
  };

  static_for<0, NR>([&](auto R) {
    constexpr int r = decltype(R)::value;
    if (r == 0) mbar_wait(bars + 8 * B_W0, 0);
    else ring_wait(bars + 8 * B_FULLW, r);
    TL(8 + 2 * r);
    if (r == 0) TLG(46);
    slot(acc0, IC<2 * r>{});
    TL(9 + 2 * r);
    slot(acc1, IC<2 * r + 1>{});
  });

  __nv_bfloat16* op = out + (size_t)(xrow + (warp & 3) * 16 + (lane >> 2)) * F_DIM + j * BN + (lane & 3) * 8;
  TL(40); TLG(48);
  if (wg == 1) bar_sync(1, 256);
#pragma unroll
  for (int e = 0; e < ENDK; e++) {
    const int kb = e < 2 ? NR + e : NR + 5 - e;
    ring_wait(bars + 8 * B_FULLW, kb);
    ring_wait(fullx, 2 * NR + e);
    mma(acc0, 2 * NR + e, kb, 0, 4);
    if (e == ENDK - 1) bar_arrive(1 + wg, 256);
    end_slot(2 * NR + e);
  }
  wgmma_wait<0>();
  TL(41);
  store_acc(acc0, op);
  TL(42);
  bar_sync(2 + wg, 256);
#pragma unroll
  for (int e = 0; e < ENDK; e++) {
    ring_wait(fullx, 2 * NR + ENDK + e);
    mma(acc1, 2 * NR + ENDK + e, e < 2 ? NR + e : NR + 5 - e, 0, 4);
  }
  if (wg == 0) bar_arrive(3, 256);
  wgmma_wait<0>();
  TL(43); TLG(47);
  store_acc(acc1, op + 64 * F_DIM);
  TL(44);
  if (warp == 0 && lane == 0) {
    if (atomicAdd(fl + 17, 1u) == NI - 1) {
#pragma unroll
      for (int u = 0; u <= 17; u++) fl[u] = 0;
    }
  }
}

typedef CUresult (*EncodeTiledFn)(CUtensorMap*, CUtensorMapDataType, cuuint32_t, void*, const cuuint64_t*,
                                  const cuuint64_t*, const cuuint32_t*, const cuuint32_t*, CUtensorMapInterleave,
                                  CUtensorMapSwizzle, CUtensorMapL2promotion, CUtensorMapFloatOOBfill);

}

#define XPROMO CU_TENSOR_MAP_L2_PROMOTION_L2_128B
extern "C" void kernel_launch(void* const* d_in, const int* in_sizes, int n_in, void* d_out, int out_size) {
  const __nv_bfloat16* x = (const __nv_bfloat16*)d_in[0];
  const int* qw = (const int*)d_in[1];
  const __nv_bfloat16* lut = (const __nv_bfloat16*)d_in[2];
  const __nv_bfloat16* scales = (const __nv_bfloat16*)d_in[3];
  __nv_bfloat16* out = (__nv_bfloat16*)d_out;

  static EncodeTiledFn enc = nullptr;
  static uint8_t* p_scr = nullptr;
  if (!enc) {
    void* fn = nullptr;
    cudaDriverEntryPointQueryResult qr;
    cudaGetDriverEntryPoint("cuTensorMapEncodeTiled", &fn, cudaEnableDefault, &qr);
    enc = (EncodeTiledFn)fn;
    void* p = nullptr;
    cudaGetSymbolAddress(&p, g_scratch);
    p_scr = (uint8_t*)(((uintptr_t)p + REGION - 1) & ~(uintptr_t)(REGION - 1));
    cudaFuncSetAttribute(fused_kernel, cudaFuncAttributeMaxDynamicSharedMemorySize, SMEM_TOTAL);
  }
  CUtensorMap tm_x, tm_q;
  cuuint32_t estr[2] = {1, 1};
  {
    cuuint64_t gdim[2] = {(cuuint64_t)D_DIM, (cuuint64_t)S_DIM};
    cuuint64_t gstr[1] = {(cuuint64_t)D_DIM * 2};
    cuuint32_t box[2] = {(cuuint32_t)BK, 64};
    enc(&tm_x, CU_TENSOR_MAP_DATA_TYPE_BFLOAT16, 2, (void*)x, gdim, gstr, box, estr, CU_TENSOR_MAP_INTERLEAVE_NONE,
        CU_TENSOR_MAP_SWIZZLE_128B, XPROMO, CU_TENSOR_MAP_FLOAT_OOB_FILL_NONE);
  }
  {
    cuuint64_t gdim[2] = {(cuuint64_t)F_DIM, (cuuint64_t)D_DIM};
    cuuint64_t gstr[1] = {(cuuint64_t)F_DIM * 4};
    cuuint32_t box[2] = {(cuuint32_t)BN, 8};
    enc(&tm_q, CU_TENSOR_MAP_DATA_TYPE_INT32, 2, (void*)qw, gdim, gstr, box, estr, CU_TENSOR_MAP_INTERLEAVE_NONE,
        CU_TENSOR_MAP_SWIZZLE_NONE, CU_TENSOR_MAP_L2_PROMOTION_NONE, CU_TENSOR_MAP_FLOAT_OOB_FILL_NONE);
  }
  fused_kernel<<<NI * NJ, 256, SMEM_TOTAL, cudaStreamPerThread>>>(qw, lut, scales, out, p_scr, tm_x, tm_q);
}
```

```cpp
#include <cuda_runtime.h>
#include <cuda_bf16.h>
#include <cuda.h>
#include <stdint.h>

namespace {

constexpr int S_DIM = 2048, D_DIM = 1024, F_DIM = 3584;
constexpr int BM = 256, BN = 224, BK = 64;
constexpr int NKB = D_DIM / BK;
constexpr int NJ = F_DIM / BN;
constexpr int NI = S_DIM / BM;
constexpr int WS = 4;
constexpr int XS = 5;
constexpr int ENDK = 4;
constexpr int NR = NKB - ENDK;
constexpr int X_SLICE = 64 * BK * 2;
constexpr int W_STAGE = BN * BK * 2;
constexpr int W_KC = BN * 16;

constexpr int REGION = 512 * 1024;
__device__ uint4 g_scratch[(NJ + 1) * REGION / 16];

__device__ __forceinline__ uint32_t smem_u32(const void* p) { return (uint32_t)__cvta_generic_to_shared(p); }
__device__ __forceinline__ unsigned clk32() {
  unsigned c;
  asm volatile("mov.u32 %0, %%clock;" : "=r"(c)::"memory");
  return c;
}
__device__ __forceinline__ bool elect_one() {
  uint32_t p;
  asm volatile("{\n.reg .pred P;\nelect.sync _|P, 0xffffffff;\nselp.b32 %0, 1, 0, P;\n}" : "=r"(p));
  return p != 0;
}
__device__ __forceinline__ void mbar_init(uint32_t bar, uint32_t cnt) {
  asm volatile("mbarrier.init.shared::cta.b64 [%0], %1;" ::"r"(bar), "r"(cnt) : "memory");
}
__device__ __forceinline__ void mbar_expect_tx(uint32_t bar, uint32_t bytes) {
  asm volatile("mbarrier.arrive.expect_tx.shared::cta.b64 _, [%0], %1;" ::"r"(bar), "r"(bytes) : "memory");
}
__device__ __forceinline__ void mbar_arrive(uint32_t bar) {
  asm volatile("mbarrier.arrive.shared::cta.b64 _, [%0];" ::"r"(bar) : "memory");
}
__device__ __forceinline__ bool mbar_test(uint32_t bar, uint32_t parity) {
  uint32_t ok;
  asm volatile(
      "{\n.reg .pred p;\nmbarrier.test_wait.parity.shared::cta.b64 p, [%1], %2;\nselp.b32 %0, 1, 0, p;\n}\n"
      : "=r"(ok) : "r"(bar), "r"(parity) : "memory");
  return ok != 0;
}
__device__ __forceinline__ void mbar_wait(uint32_t bar, uint32_t parity) {
  asm volatile(
      "{\n.reg .pred p;\n"
      "LAB_WAIT:\n"
      "mbarrier.try_wait.parity.shared::cta.b64 p, [%0], %1;\n"
      "@p bra LAB_DONE;\n"
      "bra LAB_WAIT;\n"
      "LAB_DONE:\n}\n" ::"r"(bar), "r"(parity) : "memory");
}
__device__ __forceinline__ uint32_t ring(uint32_t base, int i) { return base + 8 * (i & 7); }
__device__ __forceinline__ void ring_wait(uint32_t base, int i) { mbar_wait(ring(base, i), (i >> 3) & 1); }
__device__ __forceinline__ void tma_load_2d(uint32_t dst, const CUtensorMap* tm, int c0, int c1, uint32_t bar) {
  asm volatile(
      "cp.async.bulk.tensor.2d.shared::cluster.global.mbarrier::complete_tx::bytes [%0], [%1, {%3, %4}], [%2];"
      ::"r"(dst), "l"(tm), "r"(bar), "r"(c0), "r"(c1) : "memory");
}
__device__ __forceinline__ void tma_prefetch_2d(const CUtensorMap* tm, int c0, int c1) {
  asm volatile("cp.async.bulk.prefetch.tensor.2d.L2.global [%0, {%1, %2}];" ::"l"(tm), "r"(c0), "r"(c1) : "memory");
}
__device__ __forceinline__ void bulk_load(uint32_t dst, const void* src, uint32_t bytes, uint32_t bar) {
  asm volatile(
      "cp.async.bulk.shared::cluster.global.mbarrier::complete_tx::bytes [%0], [%1], %2, [%3];"
      ::"r"(dst), "l"(src), "r"(bytes), "r"(bar) : "memory");
}
__device__ __forceinline__ int ldg_stream(const int* p) {
  int v;
  asm volatile("ld.global.L1::no_allocate.b32 %0, [%1];" : "=r"(v) : "l"(p) : "memory");
  return v;
}
__device__ __forceinline__ uint32_t ldg_u16(const void* p) {
  uint32_t v;
  asm volatile("ld.global.u16 %0, [%1];" : "=r"(v) : "l"(p) : "memory");
  return v;
}
__device__ __forceinline__ int lds32(uint32_t addr) {
  int v;
  asm volatile("ld.shared.b32 %0, [%1];" : "=r"(v) : "r"(addr) : "memory");
  return v;
}
__device__ __forceinline__ void sts128(uint32_t addr, uint4 v) {
  asm volatile("st.shared.v4.u32 [%0], {%1, %2, %3, %4};" ::"r"(addr), "r"(v.x), "r"(v.y), "r"(v.z), "r"(v.w) : "memory");
}
__device__ __forceinline__ uint64_t make_desc(uint32_t lo, uint32_t hi) {
  uint64_t d;
  asm("mov.b64 %0, {%1, %2};" : "=l"(d) : "r"(lo), "r"(hi));
  return d;
}
__device__ __forceinline__ unsigned ld_strong(const void* p) {
  unsigned v;
  asm volatile("ld.relaxed.gpu.global.u32 %0, [%1];" : "=r"(v) : "l"(p) : "memory");
  return v;
}
__device__ __forceinline__ void st_strong128(void* p, uint4 v) {
  asm volatile("st.relaxed.gpu.global.v4.u32 [%0], {%1, %2, %3, %4};" ::"l"(p), "r"(v.x), "r"(v.y), "r"(v.z), "r"(v.w)
               : "memory");
}
__device__ __forceinline__ void wgmma_fence() { asm volatile("wgmma.fence.sync.aligned;" ::: "memory"); }
__device__ __forceinline__ void wgmma_commit() { asm volatile("wgmma.commit_group.sync.aligned;" ::: "memory"); }
template <int N>
__device__ __forceinline__ void wgmma_wait() { asm volatile("wgmma.wait_group.sync.aligned %0;" ::"n"(N) : "memory"); }
__device__ __forceinline__ void bar_sync(int id, int n) { asm volatile("bar.sync %0, %1;" ::"r"(id), "r"(n) : "memory"); }
__device__ __forceinline__ void bar_arrive(int id, int n) { asm volatile("bar.arrive %0, %1;" ::"r"(id), "r"(n) : "memory"); }

__device__ __forceinline__ void wgmma_m64n224k16(float (&d)[112], uint64_t da, uint64_t db, int scale_d) {
  asm volatile(
    "{\n.reg .pred p;\nsetp.ne.b32 p, %114, 0;\n"
    "wgmma.mma_async.sync.aligned.m64n224k16.f32.bf16.bf16 "
    "{%0, %1, %2, %3, %4, %5, %6, %7, %8, %9, %10, %11, %12, %13, %14, %15, "
    "%16, %17, %18, %19, %20, %21, %22, %23, %24, %25, %26, %27, %28, %29, %30, %31, "
    "%32, %33, %34, %35, %36, %37, %38, %39, %40, %41, %42, %43, %44, %45, %46, %47, "
    "%48, %49, %50, %51, %52, %53, %54, %55, %56, %57, %58, %59, %60, %61, %62, %63, "
    "%64, %65, %66, %67, %68, %69, %70, %71, %72, %73, %74, %75, %76, %77, %78, %79, "
    "%80, %81, %82, %83, %84, %85, %86, %87, %88, %89, %90, %91, %92, %93, %94, %95, "
    "%96, %97, %98, %99, %100, %101, %102, %103, %104, %105, %106, %107, %108, %109, %110, %111}, "
    "%112, %113, p, 1, 1, 0, 0;\n}\n"
    : "+f"(d[0]), "+f"(d[1]), "+f"(d[2]), "+f"(d[3]), "+f"(d[4]), "+f"(d[5]), "+f"(d[6]), "+f"(d[7]),
      "+f"(d[8]), "+f"(d[9]), "+f"(d[10]), "+f"(d[11]), "+f"(d[12]), "+f"(d[13]), "+f"(d[14]), "+f"(d[15]),
      "+f"(d[16]), "+f"(d[17]), "+f"(d[18]), "+f"(d[19]), "+f"(d[20]), "+f"(d[21]), "+f"(d[22]), "+f"(d[23]),
      "+f"(d[24]), "+f"(d[25]), "+f"(d[26]), "+f"(d[27]), "+f"(d[28]), "+f"(d[29]), "+f"(d[30]), "+f"(d[31]),
      "+f"(d[32]), "+f"(d[33]), "+f"(d[34]), "+f"(d[35]), "+f"(d[36]), "+f"(d[37]), "+f"(d[38]), "+f"(d[39]),
      "+f"(d[40]), "+f"(d[41]), "+f"(d[42]), "+f"(d[43]), "+f"(d[44]), "+f"(d[45]), "+f"(d[46]), "+f"(d[47]),
      "+f"(d[48]), "+f"(d[49]), "+f"(d[50]), "+f"(d[51]), "+f"(d[52]), "+f"(d[53]), "+f"(d[54]), "+f"(d[55]),
      "+f"(d[56]), "+f"(d[57]), "+f"(d[58]), "+f"(d[59]), "+f"(d[60]), "+f"(d[61]), "+f"(d[62]), "+f"(d[63]),
      "+f"(d[64]), "+f"(d[65]), "+f"(d[66]), "+f"(d[67]), "+f"(d[68]), "+f"(d[69]), "+f"(d[70]), "+f"(d[71]),
      "+f"(d[72]), "+f"(d[73]), "+f"(d[74]), "+f"(d[75]), "+f"(d[76]), "+f"(d[77]), "+f"(d[78]), "+f"(d[79]),
      "+f"(d[80]), "+f"(d[81]), "+f"(d[82]), "+f"(d[83]), "+f"(d[84]), "+f"(d[85]), "+f"(d[86]), "+f"(d[87]),
      "+f"(d[88]), "+f"(d[89]), "+f"(d[90]), "+f"(d[91]), "+f"(d[92]), "+f"(d[93]), "+f"(d[94]), "+f"(d[95]),
      "+f"(d[96]), "+f"(d[97]), "+f"(d[98]), "+f"(d[99]), "+f"(d[100]), "+f"(d[101]), "+f"(d[102]), "+f"(d[103]),
      "+f"(d[104]), "+f"(d[105]), "+f"(d[106]), "+f"(d[107]), "+f"(d[108]), "+f"(d[109]), "+f"(d[110]), "+f"(d[111])
    : "l"(da), "l"(db), "r"(scale_d));
}

__device__ __forceinline__ uint32_t pack_bf16(float lo, float hi) {
  uint32_t r;
  asm("cvt.rn.bf16x2.f32 %0, %1, %2;" : "=r"(r) : "f"(hi), "f"(lo));
  return r;
}

__device__ __forceinline__ int perm32(int n) { return (n & ~30) | ((n & 6) << 2) | ((n >> 2) & 6); }

constexpr int SMEM_X = 0;
constexpr int SMEM_W = 2 * XS * X_SLICE;
constexpr int SMEM_Q = SMEM_W + WS * W_STAGE;
constexpr int Q_UNIT = 8 * BN * 4;
constexpr int SMEM_BAR = SMEM_Q + W_STAGE;
constexpr int B_FULLW = 0, B_FULLQ = 8, B_FULLX = 16, B_DONE = 32, B_W0 = 48, B_RAW0 = 49, B_COUNT = 57;
constexpr int SMEM_TL = SMEM_BAR + B_COUNT * 8;
constexpr int SMEM_TOTAL = SMEM_TL + 2048;
constexpr int W_OFF = 128;
constexpr unsigned FLAG_FULL = NI * 7;

#define TL(i)
#define TLG(i)

__device__ __forceinline__ void store_acc(const float (&a)[112], __nv_bfloat16* p) {
#pragma unroll
  for (int J = 0; J < 7; J++) {
    uint4 v0, v1;
    v0.x = pack_bf16(a[16 * J + 0], a[16 * J + 1]);
    v0.y = pack_bf16(a[16 * J + 4], a[16 * J + 5]);
    v0.z = pack_bf16(a[16 * J + 8], a[16 * J + 9]);
    v0.w = pack_bf16(a[16 * J + 12], a[16 * J + 13]);
    v1.x = pack_bf16(a[16 * J + 2], a[16 * J + 3]);
    v1.y = pack_bf16(a[16 * J + 6], a[16 * J + 7]);
    v1.z = pack_bf16(a[16 * J + 10], a[16 * J + 11]);
    v1.w = pack_bf16(a[16 * J + 14], a[16 * J + 15]);
    *reinterpret_cast<uint4*>(p + 32 * J) = v0;
    *reinterpret_cast<uint4*>(p + 8 * F_DIM + 32 * J) = v1;
  }
}

__device__ __forceinline__ void load_unit(int (&q)[8], const int* p) {
#pragma unroll
  for (int i = 0; i < 8; i++) q[i] = ldg_stream(p + i * F_DIM);
}
__device__ __forceinline__ uint4 convert_unit(const int (&q)[8], float lutv, float sc) {
  float v[8];
#pragma unroll
  for (int i = 0; i < 8; i++) v[i] = __shfl_sync(0xffffffffu, lutv, q[i]) * sc;
  uint4 o;
  o.x = pack_bf16(v[0], v[1]);
  o.y = pack_bf16(v[2], v[3]);
  o.z = pack_bf16(v[4], v[5]);
  o.w = pack_bf16(v[6], v[7]);
  return o;
}

__device__ __forceinline__ void dequant_lookup(int (&q)[8], float lutv) {
  asm volatile(
      "shfl.sync.idx.b32 %0, %8, %0, 31, 0xffffffff;\n"
      "shfl.sync.idx.b32 %1, %8, %1, 31, 0xffffffff;\n"
      "shfl.sync.idx.b32 %2, %8, %2, 31, 0xffffffff;\n"
      "shfl.sync.idx.b32 %3, %8, %3, 31, 0xffffffff;\n"
      "shfl.sync.idx.b32 %4, %8, %4, 31, 0xffffffff;\n"
      "shfl.sync.idx.b32 %5, %8, %5, 31, 0xffffffff;\n"
      "shfl.sync.idx.b32 %6, %8, %6, 31, 0xffffffff;\n"
      "shfl.sync.idx.b32 %7, %8, %7, 31, 0xffffffff;\n"
      : "+r"(q[0]), "+r"(q[1]), "+r"(q[2]), "+r"(q[3]), "+r"(q[4]), "+r"(q[5]), "+r"(q[6]), "+r"(q[7])
      : "r"(__float_as_int(lutv)));
}
__device__ __forceinline__ void dequant_finish(int (&q)[8], unsigned& rb, uint4* wp, float sc, uint32_t qbar,
                                               uint32_t qpar, uint32_t qaddr) {
  asm volatile(
      "{\n.reg .pred W;\n.reg .b32 o0, o1, o2, o3;\n"
      "DQ_WAIT:\n"
      "mbarrier.try_wait.parity.shared::cta.b64 W, [%11], %13;\n"
      "@!W bra DQ_WAIT;\n"
      "mul.rn.f32 %0, %0, %10;\nmul.rn.f32 %1, %1, %10;\nmul.rn.f32 %2, %2, %10;\nmul.rn.f32 %3, %3, %10;\n"
      "mul.rn.f32 %4, %4, %10;\nmul.rn.f32 %5, %5, %10;\nmul.rn.f32 %6, %6, %10;\nmul.rn.f32 %7, %7, %10;\n"
      "cvt.rn.bf16x2.f32 o0, %1, %0;\ncvt.rn.bf16x2.f32 o1, %3, %2;\n"
      "cvt.rn.bf16x2.f32 o2, %5, %4;\ncvt.rn.bf16x2.f32 o3, %7, %6;\n"
      "ld.volatile.shared.b32 %0, [%12];\nld.volatile.shared.b32 %1, [%12+896];\n"
      "ld.volatile.shared.b32 %2, [%12+1792];\nld.volatile.shared.b32 %3, [%12+2688];\n"
      "ld.volatile.shared.b32 %4, [%12+3584];\nld.volatile.shared.b32 %5, [%12+4480];\n"
      "ld.volatile.shared.b32 %6, [%12+5376];\nld.volatile.shared.b32 %7, [%12+6272];\n"
      "st.relaxed.gpu.global.v4.u32 [%9], {o0, o1, o2, o3};\n"
      "ld.relaxed.gpu.global.u32 %8, [%9];\n}\n"
      : "+r"(q[0]), "+r"(q[1]), "+r"(q[2]), "+r"(q[3]), "+r"(q[4]), "+r"(q[5]), "+r"(q[6]), "+r"(q[7]), "=r"(rb)
      : "l"(wp), "r"(__float_as_int(sc)), "r"(qbar), "r"(qaddr), "r"(qpar)
      : "memory");
}

constexpr int PU = 3;
#define HEAVY 0xDB6DAu
__host__ __device__ constexpr int popc(unsigned v) { return v ? (v & 1) + popc(v >> 1) : 0; }
__host__ __device__ constexpr bool heavy(int n) { return n >= 0 && ((HEAVY >> n) & 1); }
__host__ __device__ constexpr int unit_at(int n) { return PU + popc(HEAVY & ((1u << n) - 1)); }
__host__ __device__ constexpr int emit_slot(int u) {
  if (u < PU) return -1;
  for (int n = 0; n < 24; n++)
    if (heavy(n) && unit_at(n) == u) return n;
  return 99;
}
__host__ __device__ constexpr int cmax(int a, int b) { return a > b ? a : b; }
__host__ __device__ constexpr int w_slot(int m) {
  return m == 15 ? cmax(emit_slot(15) + 3, 22) : cmax(2 * m - 5, emit_slot(m) + 3);
}
__host__ __device__ constexpr int q_slot(int u) {
  return u == 5 ? 0 : cmax(q_slot(u - 1) + 1, u - 5 < PU ? u - 5 : emit_slot(u - 5) + 2);
}
__host__ __device__ constexpr int w_at(int n) {
  for (int m = 2; m < NKB; m++)
    if (w_slot(m) == n) return m;
  return -1;
}
__host__ __device__ constexpr int q_at(int n) {
  for (int u = 5; u < NKB; u++)
    if (q_slot(u) == n) return u;
  return -1;
}
constexpr bool schedule_ok() {
  if (popc(HEAVY) != NKB - PU || (HEAVY & 1) || (HEAVY >> 20)) return false;
  for (int m = 2; m < NKB; m++) {
    if (w_at(w_slot(m)) != m || w_slot(m) > 23) return false;
    if (m < NR && w_slot(m) > 2 * m - 2) return false;
  }
  for (int u = 5; u < NKB; u++)
    if (q_slot(u) + 2 > emit_slot(u - 1)) return false;
  return true;
}
static_assert(schedule_ok(), "bad schedule");
template <int V>
struct IC {
  static constexpr int value = V;
};
template <int I, int N, class F>
__device__ __forceinline__ void static_for(F&& f) {
  if constexpr (I < N) {
    f(IC<I>{});
    static_for<I + 1, N>(f);
  }
}

#define U1_FIRST 1
#define PACE_L 0
#define STAG_L 70
#define PACE_INIT 650
#define PACE_U1 600
#define PACE_X 1400
#define PACE_Q2 1600
#define PACE_Q3 2600
#define STAG 60
#define EMIT_AT -1
#define PUB_AT 4
#define PF_X 0
#define PF_Q 0

constexpr uint32_t sbase = 1024;

__global__ void __launch_bounds__(256, 1)
fused_kernel(const int* __restrict__ qw, const __nv_bfloat16* __restrict__ lut,
             const __nv_bfloat16* __restrict__ scales, __nv_bfloat16* __restrict__ out, uint8_t* scratch,
             const __grid_constant__ CUtensorMap tm_x, const __grid_constant__ CUtensorMap tm_q) {
  extern __shared__ __align__(1024) uint8_t smem_raw[];
  constexpr uint32_t bars = sbase + SMEM_BAR;
  const int j = blockIdx.x >> 3, it = blockIdx.x & 7;
  const int warp = __shfl_sync(0xffffffffu, threadIdx.x >> 5, 0);
  const int wg = warp >> 2;
  int lane;
  asm volatile("mov.u32 %0, %%laneid;" : "=r"(lane));
  const unsigned t_start = clk32();
  auto pace = [&](unsigned t) {
    while (__any_sync(0xffffffffu, clk32() - t_start < t)) {}
  };
  TL(0); TLG(1);

  uint8_t* const region = scratch + (size_t)j * REGION;
  uint8_t* const wp = region + W_OFF + it * W_KC + (warp * 32 + lane) * 16;
  unsigned* const fl = reinterpret_cast<unsigned*>(region) + lane;
  float lutv, sc;
  unsigned rb;
  const int xrow = it * BM + wg * 128;

  auto w_ptr = [&](int u) { return reinterpret_cast<uint4*>(wp + u * W_STAGE); };
  auto emit_unit = [&](const int (&qq)[8], int u) {
    st_strong128(w_ptr(u), convert_unit(qq, lutv, sc));
    rb = ld_strong(w_ptr(u));
  };
  auto publish = [&](int u, unsigned inc) {
    asm volatile(
        "{\n.reg .pred P, Q;\n"
        "setp.ne.u32 P, %1, 0xffffffff;\n"
        "vote.sync.all.pred P, P, 0xffffffff;\n"
        "setp.eq.and.s32 Q, %2, %3, P;\n"
        "@Q red.relaxed.gpu.global.add.u32 [%0], %4;\n}"
        ::"l"(fl), "r"(rb), "r"(lane), "r"(u), "r"(inc) : "memory");
  };
  auto load_x = [&](int g, int n, int kb, int half) {
    const uint32_t bar = ring(bars + 8 * B_FULLX, n) + g * 64;
    mbar_expect_tx(bar, X_SLICE);
    tma_load_2d(sbase + SMEM_X + (n % XS) * X_SLICE + g * (XS * X_SLICE), &tm_x, kb * BK,
                it * BM + g * 128 + half * 64, bar);
  };
  auto load_q = [&](int u) {
    const uint32_t bar = ring(bars + 8 * B_FULLQ, u);
    mbar_expect_tx(bar, Q_UNIT);
    tma_load_2d(sbase + SMEM_Q + (u & 3) * Q_UNIT, &tm_q, j * BN, u * BK + it * 8, bar);
  };
  auto prefetch_x = [&](int g) {
    if (PF_X) tma_prefetch_2d(&tm_x, (4 * g + (j >> 2)) * BK, it * BM + (j & 3) * 64);
  };
  auto prefetch_q = [&](int u) {
    if (PF_Q) tma_prefetch_2d(&tm_q, j * BN, u * BK + it * 8);
  };

  unsigned ready = 0;
  auto load_w = [&](uint32_t bar, int dst, int src, int bytes) {
    mbar_expect_tx(bar, bytes);
    bulk_load(sbase + SMEM_W + dst, region + W_OFF + src, bytes, bar);
  };
  auto poll = [&]() { ready |= __ballot_sync(0xffffffffu, ld_strong(fl) >= FLAG_FULL); };
  auto wait_ready = [&](int kb) {
    int spins = 0;
    while (!((ready >> kb) & 1)) {
      poll();
      if (++spins > (1 << 22)) __trap();
    }
  };

  uint32_t qbase;
  asm volatile("mov.u32 %0, %1;" : "=r"(qbase) : "r"(sbase + SMEM_Q + warp * 128 + perm32(lane) * 4));
  auto lds_unit = [&](int (&q)[8], int u) {
    ring_wait(bars + 8 * B_FULLQ, u);
#pragma unroll
    for (int i = 0; i < 8; i++) q[i] = lds32(qbase + (u & 3) * Q_UNIT + i * (BN * 4));
  };
  auto arrive_one = [&](uint32_t bar) {
    asm volatile("{\n.reg .pred P;\nelect.sync _|P, 0xffffffff;\n@P mbarrier.arrive.shared::cta.b64 _, [%0];\n}"
                 ::"r"(bar) : "memory");
  };

  int q[8];
  constexpr uint32_t raw0 = sbase + SMEM_W + 2 * W_STAGE;
  const int fcol = j * BN + (warp < 7 ? warp : 0) * 32 + perm32(lane);
  uint32_t lut_raw = 0, sc_raw = 0;
  if (warp < 7) {
    if (elect_one()) {
      mbar_init(bars + 8 * B_RAW0 + 8 * warp, 1);
      if (warp == 6) mbar_init(bars + 8 * B_RAW0 + 8 * 7, 1);
      asm volatile("fence.mbarrier_init.release.cluster;" ::: "memory");
    }
    if (U1_FIRST) load_unit(q, qw + (size_t)(BK + it * 8) * F_DIM + fcol);
    lut_raw = ldg_u16(lut + (lane & 15));
    sc_raw = ldg_u16(scales + fcol);
    pace(PACE_L + warp * STAG_L);
    for (int c = warp; c < (warp == 6 ? 8 : warp + 1); c++) {
      if (elect_one()) {
        mbar_expect_tx(bars + 8 * B_RAW0 + 8 * c, Q_UNIT);
#pragma unroll
        for (int i = 0; i < 8; i++)
          bulk_load(raw0 + (c * 8 + i) * (BN * 4), qw + (size_t)(c * 8 + i) * F_DIM + j * BN, BN * 4,
                    bars + 8 * B_RAW0 + 8 * c);
      }
    }
  }
  if (warp == 7) {
    if (elect_one()) {
      asm volatile("prefetch.tensormap [%0];" ::"l"(&tm_q) : "memory");
      asm volatile("prefetch.tensormap [%0];" ::"l"(&tm_x) : "memory");
    }
    pace(PACE_INIT);
    if (elect_one()) {
#pragma unroll
      for (int i = 0; i < B_RAW0; i++) mbar_init(bars + 8 * i, i == B_W0 ? 7 : i >= B_DONE ? 4 : 1);
      asm volatile("fence.mbarrier_init.release.cluster;" ::: "memory");
    }
    __syncwarp();
    rb = ld_strong(fl);
    bar_arrive(0, 256);
    TL(4);
    lutv = 0.f;
    sc = 0.f;
    if (smem_u32(smem_raw) != sbase) __trap();
    pace(PACE_U1 + it * STAG);
    if (elect_one()) {
      mbar_arrive(bars + 8 * B_FULLW);
      mbar_arrive(bars + 8 * B_FULLQ);
      if (U1_FIRST) mbar_arrive(bars + 8 * B_FULLQ + 8);
      else load_q(1);
    }
    pace(PACE_X);
    if (elect_one()) {
      load_x(0, 0, 0, 0); load_x(1, 0, 0, 0); load_x(0, 1, 0, 1); load_x(1, 1, 0, 1);
    }
    pace(PACE_Q2 + it * STAG);
    if (elect_one()) load_q(2);
    pace(PACE_Q3 + it * STAG);
    ready = __ballot_sync(0xffffffffu, rb >= FLAG_FULL);
    rb = ld_strong(fl);
    if (elect_one()) {
      load_q(3);
      load_x(0, 2, 1, 0); load_x(1, 2, 1, 0); load_x(0, 3, 1, 1); load_x(1, 3, 1, 1);
    }
    ready |= __ballot_sync(0xffffffffu, rb >= FLAG_FULL);
    wait_ready(1);
    asm volatile("fence.proxy.async.global;" ::: "memory");
    if (elect_one()) {
      load_w(bars + 8 * B_FULLW + 8, W_STAGE, W_STAGE, W_STAGE);
      load_q(4);
      load_x(0, 4, 2, 0); load_x(1, 4, 2, 0);
    }
    TL(2);
    TL(3);
  } else {
    bar_sync(0, 256);
    asm volatile("shl.b32 %0, %0, 16;\nshl.b32 %1, %1, 16;" : "+r"(lut_raw), "+r"(sc_raw));
    lutv = __uint_as_float(lut_raw);
    sc = __uint_as_float(sc_raw);
    int r[2][8];
    auto lds_raw0 = [&](int c) {
      mbar_wait(bars + 8 * B_RAW0 + 8 * c, 0);
#pragma unroll
      for (int i = 0; i < 8; i++) r[c & 1][i] = lds32(qbase + (raw0 - sbase - SMEM_Q) + (c * 8 + i) * (BN * 4));
    };
    if (EMIT_AT < 0) {
      emit_unit(q, 1);
      TL(2);
    }
    lds_raw0(0);
    TL(6);
#pragma unroll
    for (int c = 0; c < 8; c++) {
      if (c == EMIT_AT) {
        if (!U1_FIRST) lds_unit(q, 1);
        emit_unit(q, 1);
        TL(2);
      }
      if (c == PUB_AT) {
        publish(1, 1);
        TL(3);
      }
      if (c < 7) lds_raw0(c + 1);
      sts128(sbase + SMEM_W + c * W_KC + (warp * 32 + lane) * 16, convert_unit(r[c & 1], lutv, sc));
    }
    asm volatile("fence.proxy.async.shared::cta;" ::: "memory");
    __syncwarp();
    arrive_one(bars + 8 * B_W0);
    if (PUB_AT == 8) {
      publish(1, 1);
      TL(3);
    }
    TL(4);
    lds_unit(q, 2);
    emit_unit(q, 2);
    TL(5);
  }

  float acc0[112], acc1[112];
  constexpr uint32_t DA_HI = (1u << 30) | (1024 >> 4), DB_HI = (128 >> 4);
  const uint32_t da0 = ((1u << 16) | ((sbase + SMEM_X) >> 4)) + wg * (XS * X_SLICE >> 4);
  constexpr uint32_t db0 = ((W_KC >> 4) << 16) | ((sbase + SMEM_W) >> 4);
  const uint32_t fullx = bars + 8 * B_FULLX + wg * 64, done = bars + 8 * B_DONE + wg * 64;
  const bool x_issuer = (warp & 3) == 3;

  auto mma = [&](float (&acc)[112], int n, int kb, int k0, int k1) {
    const int wslot = kb == 15 ? 4 : (kb & 3);
    wgmma_fence();
#pragma unroll
    for (int k = k0; k < k1; k++)
      wgmma_m64n224k16(acc, make_desc(da0 + (n % XS) * (X_SLICE >> 4) + k * 2, DA_HI),
                       make_desc(db0 + wslot * (W_STAGE >> 4) + k * (2 * W_KC >> 4), DB_HI), kb != 0 || k != 0);
    wgmma_commit();
  };
  auto end_slot = [&](int n) {
    wgmma_wait<1>();
    arrive_one(ring(done, n));
    if (x_issuer) {
      ring_wait(done, n);
      const int m = n + 4, e = (m - 2 * NR) & 3;
      if (n > 0 && elect_one())
        load_x(wg, m, m < 2 * NR ? m >> 1 : e < 2 ? NR + e : NR + 5 - e, m < 2 * NR ? m & 1 : (m - 2 * NR) >> 2);
    }
  };
  auto slot = [&](float (&acc)[112], auto N) {
    constexpr int n = decltype(N)::value;
    constexpr bool hv = heavy(n), pub = n == 0 || heavy(n - 1);
    ring_wait(fullx, n);
    mma(acc, n, n >> 1, 0, 4);
    if (hv && warp < 7) dequant_lookup(q, lutv);
    end_slot(n);
    if (warp < 7) {
      constexpr int u = unit_at(n);
      if (pub) publish(u - 1, 1);
      if (n == 0) lds_unit(q, PU);
      if (hv) {
        constexpr int un = u + 1 < NKB ? u + 1 : u;
        dequant_finish(q, rb, w_ptr(u), sc, ring(bars + 8 * B_FULLQ, un), un >> 3, qbase + (un & 3) * Q_UNIT);
      }
    } else {
      constexpr int m = w_at(n), u = q_at(n), m_next = w_at(n + 1);
      if (n > 0 && (m >= 0 || u >= 0)) ring_wait(bars + 8 * B_DONE, n - 1);
      if (m >= 0) {
        ready |= __ballot_sync(0xffffffffu, rb >= FLAG_FULL);
        wait_ready(m);
        asm volatile("fence.proxy.async.global;" ::: "memory");
      }
      if (m_next >= 0) rb = ld_strong(fl);
      if ((m >= 0 || u >= 0 || n == 4 || n == 10) && elect_one()) {
        if (m >= 0)
          load_w(ring(bars + 8 * B_FULLW, m), (m == 15 ? 4 : m & 3) * W_STAGE, m * W_STAGE, W_STAGE);
        if (u >= 0) load_q(u);
        if (u >= 0 && u + 2 < NKB) prefetch_q(u + 2);
        if (n == 4 || n == 10) prefetch_x(n == 4 ? 2 : 3);
      }
    }
  };

  static_for<0, NR>([&](auto R) {
    constexpr int r = decltype(R)::value;
    if (r == 0) mbar_wait(bars + 8 * B_W0, 0);
    else ring_wait(bars + 8 * B_FULLW, r);
    TL(8 + 2 * r);
    if (r == 0) TLG(46);
    slot(acc0, IC<2 * r>{});
    TL(9 + 2 * r);
    slot(acc1, IC<2 * r + 1>{});
  });

  __nv_bfloat16* op = out + (size_t)(xrow + (warp & 3) * 16 + (lane >> 2)) * F_DIM + j * BN + (lane & 3) * 8;
  TL(40); TLG(48);
  if (wg == 1) bar_sync(1, 256);
#pragma unroll
  for (int e = 0; e < ENDK; e++) {
    const int kb = e < 2 ? NR + e : NR + 5 - e;
    ring_wait(bars + 8 * B_FULLW, kb);
    ring_wait(fullx, 2 * NR + e);
    mma(acc0, 2 * NR + e, kb, 0, 4);
    if (e == ENDK - 1) bar_arrive(1 + wg, 256);
    end_slot(2 * NR + e);
  }
  wgmma_wait<0>();
  TL(41);
  store_acc(acc0, op);
  TL(42);
  bar_sync(2 + wg, 256);
#pragma unroll
  for (int e = 0; e < ENDK; e++) {
    ring_wait(fullx, 2 * NR + ENDK + e);
    mma(acc1, 2 * NR + ENDK + e, e < 2 ? NR + e : NR + 5 - e, 0, 4);
  }
  if (wg == 0) bar_arrive(3, 256);
  wgmma_wait<0>();
  TL(43); TLG(47);
  store_acc(acc1, op + 64 * F_DIM);
  TL(44);
  if (warp == 0 && lane == 0) {
    if (atomicAdd(fl + 17, 1u) == NI - 1) {
#pragma unroll
      for (int u = 0; u <= 17; u++) fl[u] = 0;
    }
  }
}

typedef CUresult (*EncodeTiledFn)(CUtensorMap*, CUtensorMapDataType, cuuint32_t, void*, const cuuint64_t*,
                                  const cuuint64_t*, const cuuint32_t*, const cuuint32_t*, CUtensorMapInterleave,
                                  CUtensorMapSwizzle, CUtensorMapL2promotion, CUtensorMapFloatOOBfill);

}

#define XPROMO CU_TENSOR_MAP_L2_PROMOTION_L2_128B
extern "C" void kernel_launch(void* const* d_in, const int* in_sizes, int n_in, void* d_out, int out_size) {
  const __nv_bfloat16* x = (const __nv_bfloat16*)d_in[0];
  const int* qw = (const int*)d_in[1];
  const __nv_bfloat16* lut = (const __nv_bfloat16*)d_in[2];
  const __nv_bfloat16* scales = (const __nv_bfloat16*)d_in[3];
  __nv_bfloat16* out = (__nv_bfloat16*)d_out;

  static EncodeTiledFn enc = nullptr;
  static uint8_t* p_scr = nullptr;
  if (!enc) {
    void* fn = nullptr;
    cudaDriverEntryPointQueryResult qr;
    cudaGetDriverEntryPoint("cuTensorMapEncodeTiled", &fn, cudaEnableDefault, &qr);
    enc = (EncodeTiledFn)fn;
    void* p = nullptr;
    cudaGetSymbolAddress(&p, g_scratch);
    p_scr = (uint8_t*)(((uintptr_t)p + REGION - 1) & ~(uintptr_t)(REGION - 1));
    cudaFuncSetAttribute(fused_kernel, cudaFuncAttributeMaxDynamicSharedMemorySize, SMEM_TOTAL);
  }
  CUtensorMap tm_x, tm_q;
  cuuint32_t estr[2] = {1, 1};
  {
    cuuint64_t gdim[2] = {(cuuint64_t)D_DIM, (cuuint64_t)S_DIM};
    cuuint64_t gstr[1] = {(cuuint64_t)D_DIM * 2};
    cuuint32_t box[2] = {(cuuint32_t)BK, 64};
    enc(&tm_x, CU_TENSOR_MAP_DATA_TYPE_BFLOAT16, 2, (void*)x, gdim, gstr, box, estr, CU_TENSOR_MAP_INTERLEAVE_NONE,
        CU_TENSOR_MAP_SWIZZLE_128B, XPROMO, CU_TENSOR_MAP_FLOAT_OOB_FILL_NONE);
  }
  {
    cuuint64_t gdim[2] = {(cuuint64_t)F_DIM, (cuuint64_t)D_DIM};
    cuuint64_t gstr[1] = {(cuuint64_t)F_DIM * 4};
    cuuint32_t box[2] = {(cuuint32_t)BN, 8};
    enc(&tm_q, CU_TENSOR_MAP_DATA_TYPE_INT32, 2, (void*)qw, gdim, gstr, box, estr, CU_TENSOR_MAP_INTERLEAVE_NONE,
        CU_TENSOR_MAP_SWIZZLE_NONE, CU_TENSOR_MAP_L2_PROMOTION_NONE, CU_TENSOR_MAP_FLOAT_OOB_FILL_NONE);
  }
  fused_kernel<<<NI * NJ, 256, SMEM_TOTAL, cudaStreamPerThread>>>(qw, lut, scales, out, p_scr, tm_x, tm_q);
}
```

```cpp
#include <cuda_runtime.h>
#include <cuda_bf16.h>
#include <cuda.h>
#include <stdint.h>

namespace {

constexpr int S_DIM = 2048, D_DIM = 1024, F_DIM = 3584;
constexpr int BM = 256, BN = 224, BK = 64;
constexpr int NKB = D_DIM / BK;
constexpr int NJ = F_DIM / BN;
constexpr int NI = S_DIM / BM;
constexpr int WS = 4;
constexpr int XS = 5;
constexpr int ENDK = 5;
constexpr int NR = NKB - ENDK;
constexpr int X_SLICE = 64 * BK * 2;
constexpr int W_STAGE = BN * BK * 2;
constexpr int W_KC = BN * 16;

constexpr int REGION = 512 * 1024;
__device__ uint4 g_scratch[(NJ + 1) * REGION / 16];

__device__ __forceinline__ uint32_t smem_u32(const void* p) { return (uint32_t)__cvta_generic_to_shared(p); }
__device__ __forceinline__ unsigned clk32() {
  unsigned c;
  asm volatile("mov.u32 %0, %%clock;" : "=r"(c)::"memory");
  return c;
}
__device__ __forceinline__ bool elect_one() {
  uint32_t p;
  asm volatile("{\n.reg .pred P;\nelect.sync _|P, 0xffffffff;\nselp.b32 %0, 1, 0, P;\n}" : "=r"(p));
  return p != 0;
}
__device__ __forceinline__ void mbar_init(uint32_t bar, uint32_t cnt) {
  asm volatile("mbarrier.init.shared::cta.b64 [%0], %1;" ::"r"(bar), "r"(cnt) : "memory");
}
__device__ __forceinline__ void mbar_expect_tx(uint32_t bar, uint32_t bytes) {
  asm volatile("mbarrier.arrive.expect_tx.shared::cta.b64 _, [%0], %1;" ::"r"(bar), "r"(bytes) : "memory");
}
__device__ __forceinline__ void mbar_arrive(uint32_t bar) {
  asm volatile("mbarrier.arrive.shared::cta.b64 _, [%0];" ::"r"(bar) : "memory");
}
__device__ __forceinline__ bool mbar_test(uint32_t bar, uint32_t parity) {
  uint32_t ok;
  asm volatile(
      "{\n.reg .pred p;\nmbarrier.test_wait.parity.shared::cta.b64 p, [%1], %2;\nselp.b32 %0, 1, 0, p;\n}\n"
      : "=r"(ok) : "r"(bar), "r"(parity) : "memory");
  return ok != 0;
}
__device__ __forceinline__ void mbar_wait(uint32_t bar, uint32_t parity) {
  asm volatile(
      "{\n.reg .pred p;\n"
      "LAB_WAIT:\n"
      "mbarrier.try_wait.parity.shared::cta.b64 p, [%0], %1;\n"
      "@p bra LAB_DONE;\n"
      "bra LAB_WAIT;\n"
      "LAB_DONE:\n}\n" ::"r"(bar), "r"(parity) : "memory");
}
__device__ __forceinline__ uint32_t ring(uint32_t base, int i) { return base + 8 * (i & 7); }
__device__ __forceinline__ void ring_wait(uint32_t base, int i) { mbar_wait(ring(base, i), (i >> 3) & 1); }
__device__ __forceinline__ void tma_load_2d(uint32_t dst, const CUtensorMap* tm, int c0, int c1, uint32_t bar) {
  asm volatile(
      "cp.async.bulk.tensor.2d.shared::cluster.global.mbarrier::complete_tx::bytes [%0], [%1, {%3, %4}], [%2];"
      ::"r"(dst), "l"(tm), "r"(bar), "r"(c0), "r"(c1) : "memory");
}
__device__ __forceinline__ void tma_prefetch_2d(const CUtensorMap* tm, int c0, int c1) {
  asm volatile("cp.async.bulk.prefetch.tensor.2d.L2.global [%0, {%1, %2}];" ::"l"(tm), "r"(c0), "r"(c1) : "memory");
}
__device__ __forceinline__ void bulk_load(uint32_t dst, const void* src, uint32_t bytes, uint32_t bar) {
  asm volatile(
      "cp.async.bulk.shared::cluster.global.mbarrier::complete_tx::bytes [%0], [%1], %2, [%3];"
      ::"r"(dst), "l"(src), "r"(bytes), "r"(bar) : "memory");
}
__device__ __forceinline__ int ldg_stream(const int* p) {
  int v;
  asm volatile("ld.global.L1::no_allocate.b32 %0, [%1];" : "=r"(v) : "l"(p) : "memory");
  return v;
}
__device__ __forceinline__ uint32_t ldg_u16(const void* p) {
  uint32_t v;
  asm volatile("ld.global.u16 %0, [%1];" : "=r"(v) : "l"(p) : "memory");
  return v;
}
__device__ __forceinline__ int lds32(uint32_t addr) {
  int v;
  asm volatile("ld.shared.b32 %0, [%1];" : "=r"(v) : "r"(addr) : "memory");
  return v;
}
__device__ __forceinline__ void sts128(uint32_t addr, uint4 v) {
  asm volatile("st.shared.v4.u32 [%0], {%1, %2, %3, %4};" ::"r"(addr), "r"(v.x), "r"(v.y), "r"(v.z), "r"(v.w) : "memory");
}
__device__ __forceinline__ uint64_t make_desc(uint32_t lo, uint32_t hi) {
  uint64_t d;
  asm("mov.b64 %0, {%1, %2};" : "=l"(d) : "r"(lo), "r"(hi));
  return d;
}
__device__ __forceinline__ unsigned ld_strong(const void* p) {
  unsigned v;
  asm volatile("ld.relaxed.gpu.global.u32 %0, [%1];" : "=r"(v) : "l"(p) : "memory");
  return v;
}
__device__ __forceinline__ void st_strong128(void* p, uint4 v) {
  asm volatile("st.relaxed.gpu.global.v4.u32 [%0], {%1, %2, %3, %4};" ::"l"(p), "r"(v.x), "r"(v.y), "r"(v.z), "r"(v.w)
               : "memory");
}
__device__ __forceinline__ void wgmma_fence() { asm volatile("wgmma.fence.sync.aligned;" ::: "memory"); }
__device__ __forceinline__ void wgmma_commit() { asm volatile("wgmma.commit_group.sync.aligned;" ::: "memory"); }
template <int N>
__device__ __forceinline__ void wgmma_wait() { asm volatile("wgmma.wait_group.sync.aligned %0;" ::"n"(N) : "memory"); }
__device__ __forceinline__ void bar_sync(int id, int n) { asm volatile("bar.sync %0, %1;" ::"r"(id), "r"(n) : "memory"); }
__device__ __forceinline__ void bar_arrive(int id, int n) { asm volatile("bar.arrive %0, %1;" ::"r"(id), "r"(n) : "memory"); }

__device__ __forceinline__ void wgmma_m64n224k16(float (&d)[112], uint64_t da, uint64_t db, int scale_d) {
  asm volatile(
    "{\n.reg .pred p;\nsetp.ne.b32 p, %114, 0;\n"
    "wgmma.mma_async.sync.aligned.m64n224k16.f32.bf16.bf16 "
    "{%0, %1, %2, %3, %4, %5, %6, %7, %8, %9, %10, %11, %12, %13, %14, %15, "
    "%16, %17, %18, %19, %20, %21, %22, %23, %24, %25, %26, %27, %28, %29, %30, %31, "
    "%32, %33, %34, %35, %36, %37, %38, %39, %40, %41, %42, %43, %44, %45, %46, %47, "
    "%48, %49, %50, %51, %52, %53, %54, %55, %56, %57, %58, %59, %60, %61, %62, %63, "
    "%64, %65, %66, %67, %68, %69, %70, %71, %72, %73, %74, %75, %76, %77, %78, %79, "
    "%80, %81, %82, %83, %84, %85, %86, %87, %88, %89, %90, %91, %92, %93, %94, %95, "
    "%96, %97, %98, %99, %100, %101, %102, %103, %104, %105, %106, %107, %108, %109, %110, %111}, "
    "%112, %113, p, 1, 1, 0, 0;\n}\n"
    : "+f"(d[0]), "+f"(d[1]), "+f"(d[2]), "+f"(d[3]), "+f"(d[4]), "+f"(d[5]), "+f"(d[6]), "+f"(d[7]),
      "+f"(d[8]), "+f"(d[9]), "+f"(d[10]), "+f"(d[11]), "+f"(d[12]), "+f"(d[13]), "+f"(d[14]), "+f"(d[15]),
      "+f"(d[16]), "+f"(d[17]), "+f"(d[18]), "+f"(d[19]), "+f"(d[20]), "+f"(d[21]), "+f"(d[22]), "+f"(d[23]),
      "+f"(d[24]), "+f"(d[25]), "+f"(d[26]), "+f"(d[27]), "+f"(d[28]), "+f"(d[29]), "+f"(d[30]), "+f"(d[31]),
      "+f"(d[32]), "+f"(d[33]), "+f"(d[34]), "+f"(d[35]), "+f"(d[36]), "+f"(d[37]), "+f"(d[38]), "+f"(d[39]),
      "+f"(d[40]), "+f"(d[41]), "+f"(d[42]), "+f"(d[43]), "+f"(d[44]), "+f"(d[45]), "+f"(d[46]), "+f"(d[47]),
      "+f"(d[48]), "+f"(d[49]), "+f"(d[50]), "+f"(d[51]), "+f"(d[52]), "+f"(d[53]), "+f"(d[54]), "+f"(d[55]),
      "+f"(d[56]), "+f"(d[57]), "+f"(d[58]), "+f"(d[59]), "+f"(d[60]), "+f"(d[61]), "+f"(d[62]), "+f"(d[63]),
      "+f"(d[64]), "+f"(d[65]), "+f"(d[66]), "+f"(d[67]), "+f"(d[68]), "+f"(d[69]), "+f"(d[70]), "+f"(d[71]),
      "+f"(d[72]), "+f"(d[73]), "+f"(d[74]), "+f"(d[75]), "+f"(d[76]), "+f"(d[77]), "+f"(d[78]), "+f"(d[79]),
      "+f"(d[80]), "+f"(d[81]), "+f"(d[82]), "+f"(d[83]), "+f"(d[84]), "+f"(d[85]), "+f"(d[86]), "+f"(d[87]),
      "+f"(d[88]), "+f"(d[89]), "+f"(d[90]), "+f"(d[91]), "+f"(d[92]), "+f"(d[93]), "+f"(d[94]), "+f"(d[95]),
      "+f"(d[96]), "+f"(d[97]), "+f"(d[98]), "+f"(d[99]), "+f"(d[100]), "+f"(d[101]), "+f"(d[102]), "+f"(d[103]),
      "+f"(d[104]), "+f"(d[105]), "+f"(d[106]), "+f"(d[107]), "+f"(d[108]), "+f"(d[109]), "+f"(d[110]), "+f"(d[111])
    : "l"(da), "l"(db), "r"(scale_d));
}
__device__ __forceinline__ void wgmma_m64n128k16(float (&d)[112], uint64_t da, uint64_t db) {
  asm volatile(
    "wgmma.mma_async.sync.aligned.m64n128k16.f32.bf16.bf16 "
    "{%0, %1, %2, %3, %4, %5, %6, %7, %8, %9, %10, %11, %12, %13, %14, %15, "
    "%16, %17, %18, %19, %20, %21, %22, %23, %24, %25, %26, %27, %28, %29, %30, %31, "
    "%32, %33, %34, %35, %36, %37, %38, %39, %40, %41, %42, %43, %44, %45, %46, %47, "
    "%48, %49, %50, %51, %52, %53, %54, %55, %56, %57, %58, %59, %60, %61, %62, %63}, "
    "%64, %65, 1, 1, 1, 0, 0;\n"
    : "+f"(d[0]), "+f"(d[1]), "+f"(d[2]), "+f"(d[3]), "+f"(d[4]), "+f"(d[5]), "+f"(d[6]), "+f"(d[7]),
      "+f"(d[8]), "+f"(d[9]), "+f"(d[10]), "+f"(d[11]), "+f"(d[12]), "+f"(d[13]), "+f"(d[14]), "+f"(d[15]),
      "+f"(d[16]), "+f"(d[17]), "+f"(d[18]), "+f"(d[19]), "+f"(d[20]), "+f"(d[21]), "+f"(d[22]), "+f"(d[23]),
      "+f"(d[24]), "+f"(d[25]), "+f"(d[26]), "+f"(d[27]), "+f"(d[28]), "+f"(d[29]), "+f"(d[30]), "+f"(d[31]),
      "+f"(d[32]), "+f"(d[33]), "+f"(d[34]), "+f"(d[35]), "+f"(d[36]), "+f"(d[37]), "+f"(d[38]), "+f"(d[39]),
      "+f"(d[40]), "+f"(d[41]), "+f"(d[42]), "+f"(d[43]), "+f"(d[44]), "+f"(d[45]), "+f"(d[46]), "+f"(d[47]),
      "+f"(d[48]), "+f"(d[49]), "+f"(d[50]), "+f"(d[51]), "+f"(d[52]), "+f"(d[53]), "+f"(d[54]), "+f"(d[55]),
      "+f"(d[56]), "+f"(d[57]), "+f"(d[58]), "+f"(d[59]), "+f"(d[60]), "+f"(d[61]), "+f"(d[62]), "+f"(d[63])
    : "l"(da), "l"(db));
}
__device__ __forceinline__ void wgmma_m64n96k16(float (&d)[112], uint64_t da, uint64_t db) {
  asm volatile(
    "wgmma.mma_async.sync.aligned.m64n96k16.f32.bf16.bf16 "
    "{%0, %1, %2, %3, %4, %5, %6, %7, %8, %9, %10, %11, %12, %13, %14, %15, "
    "%16, %17, %18, %19, %20, %21, %22, %23, %24, %25, %26, %27, %28, %29, %30, %31, "
    "%32, %33, %34, %35, %36, %37, %38, %39, %40, %41, %42, %43, %44, %45, %46, %47}, "
    "%48, %49, 1, 1, 1, 0, 0;\n"
    : "+f"(d[64]), "+f"(d[65]), "+f"(d[66]), "+f"(d[67]), "+f"(d[68]), "+f"(d[69]), "+f"(d[70]), "+f"(d[71]),
      "+f"(d[72]), "+f"(d[73]), "+f"(d[74]), "+f"(d[75]), "+f"(d[76]), "+f"(d[77]), "+f"(d[78]), "+f"(d[79]),
      "+f"(d[80]), "+f"(d[81]), "+f"(d[82]), "+f"(d[83]), "+f"(d[84]), "+f"(d[85]), "+f"(d[86]), "+f"(d[87]),
      "+f"(d[88]), "+f"(d[89]), "+f"(d[90]), "+f"(d[91]), "+f"(d[92]), "+f"(d[93]), "+f"(d[94]), "+f"(d[95]),
      "+f"(d[96]), "+f"(d[97]), "+f"(d[98]), "+f"(d[99]), "+f"(d[100]), "+f"(d[101]), "+f"(d[102]), "+f"(d[103]),
      "+f"(d[104]), "+f"(d[105]), "+f"(d[106]), "+f"(d[107]), "+f"(d[108]), "+f"(d[109]), "+f"(d[110]), "+f"(d[111])
    : "l"(da), "l"(db));
}

__device__ __forceinline__ uint32_t pack_bf16(float lo, float hi) {
  uint32_t r;
  asm("cvt.rn.bf16x2.f32 %0, %1, %2;" : "=r"(r) : "f"(hi), "f"(lo));
  return r;
}

__device__ __forceinline__ int perm32(int n) { return (n & ~30) | ((n & 6) << 2) | ((n >> 2) & 6); }

constexpr int SMEM_X = 0;
constexpr int SMEM_W = 2 * XS * X_SLICE;
constexpr int SMEM_Q = SMEM_W + WS * W_STAGE;
constexpr int Q_UNIT = 8 * BN * 4;
constexpr int SMEM_BAR = SMEM_Q + W_STAGE;
constexpr int B_FULLW = 0, B_FULLQ = 8, B_FULLX = 16, B_DONE = 32, B_W0 = 48, B_RAW0 = 49, B_COUNT = 57;
constexpr int SMEM_TL = SMEM_BAR + B_COUNT * 8;
constexpr int SMEM_TOTAL = SMEM_TL + 2048;
constexpr int W_OFF = 128;
constexpr unsigned FLAG_FULL = NI * 7;

#define TL(i)
#define TLG(i)

__device__ __forceinline__ void store_acc(const float (&a)[112], __nv_bfloat16* p, int J0, int J1) {
#pragma unroll
  for (int J = J0; J < J1; J++) {
    uint4 v0, v1;
    v0.x = pack_bf16(a[16 * J + 0], a[16 * J + 1]);
    v0.y = pack_bf16(a[16 * J + 4], a[16 * J + 5]);
    v0.z = pack_bf16(a[16 * J + 8], a[16 * J + 9]);
    v0.w = pack_bf16(a[16 * J + 12], a[16 * J + 13]);
    v1.x = pack_bf16(a[16 * J + 2], a[16 * J + 3]);
    v1.y = pack_bf16(a[16 * J + 6], a[16 * J + 7]);
    v1.z = pack_bf16(a[16 * J + 10], a[16 * J + 11]);
    v1.w = pack_bf16(a[16 * J + 14], a[16 * J + 15]);
    *reinterpret_cast<uint4*>(p + 32 * J) = v0;
    *reinterpret_cast<uint4*>(p + 8 * F_DIM + 32 * J) = v1;
  }
}

__device__ __forceinline__ void load_unit(int (&q)[8], const int* p) {
#pragma unroll
  for (int i = 0; i < 8; i++) q[i] = ldg_stream(p + i * F_DIM);
}
__device__ __forceinline__ uint4 convert_unit(const int (&q)[8], float lutv, float sc) {
  float v[8];
#pragma unroll
  for (int i = 0; i < 8; i++) v[i] = __shfl_sync(0xffffffffu, lutv, q[i]) * sc;
  uint4 o;
  o.x = pack_bf16(v[0], v[1]);
  o.y = pack_bf16(v[2], v[3]);
  o.z = pack_bf16(v[4], v[5]);
  o.w = pack_bf16(v[6], v[7]);
  return o;
}

__device__ __forceinline__ void dequant_lookup(int (&q)[8], float lutv) {
  asm volatile(
      "shfl.sync.idx.b32 %0, %8, %0, 31, 0xffffffff;\n"
      "shfl.sync.idx.b32 %1, %8, %1, 31, 0xffffffff;\n"
      "shfl.sync.idx.b32 %2, %8, %2, 31, 0xffffffff;\n"
      "shfl.sync.idx.b32 %3, %8, %3, 31, 0xffffffff;\n"
      "shfl.sync.idx.b32 %4, %8, %4, 31, 0xffffffff;\n"
      "shfl.sync.idx.b32 %5, %8, %5, 31, 0xffffffff;\n"
      "shfl.sync.idx.b32 %6, %8, %6, 31, 0xffffffff;\n"
      "shfl.sync.idx.b32 %7, %8, %7, 31, 0xffffffff;\n"
      : "+r"(q[0]), "+r"(q[1]), "+r"(q[2]), "+r"(q[3]), "+r"(q[4]), "+r"(q[5]), "+r"(q[6]), "+r"(q[7])
      : "r"(__float_as_int(lutv)));
}
__device__ __forceinline__ void dequant_finish(int (&q)[8], unsigned& rb, uint4* wp, float sc, uint32_t qbar,
                                               uint32_t qpar, uint32_t qaddr) {
  asm volatile(
      "{\n.reg .pred W;\n.reg .b32 o0, o1, o2, o3;\n"
      "DQ_WAIT:\n"
      "mbarrier.try_wait.parity.shared::cta.b64 W, [%11], %13;\n"
      "@!W bra DQ_WAIT;\n"
      "mul.rn.f32 %0, %0, %10;\nmul.rn.f32 %1, %1, %10;\nmul.rn.f32 %2, %2, %10;\nmul.rn.f32 %3, %3, %10;\n"
      "mul.rn.f32 %4, %4, %10;\nmul.rn.f32 %5, %5, %10;\nmul.rn.f32 %6, %6, %10;\nmul.rn.f32 %7, %7, %10;\n"
      "cvt.rn.bf16x2.f32 o0, %1, %0;\ncvt.rn.bf16x2.f32 o1, %3, %2;\n"
      "cvt.rn.bf16x2.f32 o2, %5, %4;\ncvt.rn.bf16x2.f32 o3, %7, %6;\n"
      "ld.volatile.shared.b32 %0, [%12];\nld.volatile.shared.b32 %1, [%12+896];\n"
      "ld.volatile.shared.b32 %2, [%12+1792];\nld.volatile.shared.b32 %3, [%12+2688];\n"
      "ld.volatile.shared.b32 %4, [%12+3584];\nld.volatile.shared.b32 %5, [%12+4480];\n"
      "ld.volatile.shared.b32 %6, [%12+5376];\nld.volatile.shared.b32 %7, [%12+6272];\n"
      "st.relaxed.gpu.global.v4.u32 [%9], {o0, o1, o2, o3};\n"
      "ld.relaxed.gpu.global.u32 %8, [%9];\n}\n"
      : "+r"(q[0]), "+r"(q[1]), "+r"(q[2]), "+r"(q[3]), "+r"(q[4]), "+r"(q[5]), "+r"(q[6]), "+r"(q[7]), "=r"(rb)
      : "l"(wp), "r"(__float_as_int(sc)), "r"(qbar), "r"(qaddr), "r"(qpar)
      : "memory");
}

constexpr int PU = 3;
#define HEAVY 0x3BBBAu
__host__ __device__ constexpr int popc(unsigned v) { return v ? (v & 1) + popc(v >> 1) : 0; }
__host__ __device__ constexpr bool heavy(int n) { return n >= 0 && ((HEAVY >> n) & 1); }
__host__ __device__ constexpr int unit_at(int n) { return PU + popc(HEAVY & ((1u << n) - 1)); }
__host__ __device__ constexpr int emit_slot(int u) {
  if (u < PU) return -1;
  for (int n = 0; n < 24; n++)
    if (heavy(n) && unit_at(n) == u) return n;
  return 99;
}
__host__ __device__ constexpr int end_kb(int e) { return e < 3 ? NR + e : NR + 7 - e; }
__host__ __device__ constexpr int cmax(int a, int b) { return a > b ? a : b; }
__host__ __device__ constexpr int w_slot(int m) {
  return m == 15 ? cmax(emit_slot(15) + 3, 20) : cmax(2 * m - 5, emit_slot(m) + 3);
}
__host__ __device__ constexpr int q_slot(int u) {
  return u == 5 ? 0 : cmax(q_slot(u - 1) + 1, u - 5 < PU ? u - 5 : emit_slot(u - 5) + 2);
}
__host__ __device__ constexpr int w_at(int n) {
  for (int m = 2; m < NKB; m++)
    if (w_slot(m) == n) return m;
  return -1;
}
__host__ __device__ constexpr int q_at(int n) {
  for (int u = 5; u < NKB; u++)
    if (q_slot(u) == n) return u;
  return -1;
}
constexpr bool schedule_ok() {
  if (popc(HEAVY) != NKB - PU || (HEAVY & 1) || (HEAVY >> 20)) return false;
  for (int m = 2; m < NKB; m++) {
    if (w_at(w_slot(m)) != m || (m != 14 && w_slot(m) >= 2 * NR)) return false;
    if (m < NR && w_slot(m) > 2 * m - 2) return false;
  }
  for (int u = 5; u < NKB; u++)
    if (q_slot(u) + 2 > emit_slot(u - 1)) return false;
  return true;
}
static_assert(schedule_ok(), "bad schedule");
template <int V>
struct IC {
  static constexpr int value = V;
};
template <int I, int N, class F>
__device__ __forceinline__ void static_for(F&& f) {
  if constexpr (I < N) {
    f(IC<I>{});
    static_for<I + 1, N>(f);
  }
}

#define U1_FIRST 1
#define PACE_L 0
#define STAG_L 70
#define SPLIT_END 0
#define PACE_INIT 650
#define PACE_U1 600
#define PACE_X 1400
#define PACE_Q2 1600
#define PACE_Q3 2600
#define STAG 60
#define EMIT_AT -1
#define PUB_AT 4
#define PF_X 0
#define PF_Q 0

constexpr uint32_t sbase = 1024;

__global__ void __launch_bounds__(256, 1)
fused_kernel(const int* __restrict__ qw, const __nv_bfloat16* __restrict__ lut,
             const __nv_bfloat16* __restrict__ scales, __nv_bfloat16* __restrict__ out, uint8_t* scratch,
             const __grid_constant__ CUtensorMap tm_x, const __grid_constant__ CUtensorMap tm_q) {
  extern __shared__ __align__(1024) uint8_t smem_raw[];
  constexpr uint32_t bars = sbase + SMEM_BAR;
  const int j = blockIdx.x >> 3, it = blockIdx.x & 7;
  const int warp = __shfl_sync(0xffffffffu, threadIdx.x >> 5, 0);
  const int wg = warp >> 2;
  int lane;
  asm volatile("mov.u32 %0, %%laneid;" : "=r"(lane));
  const unsigned t_start = clk32();
  auto pace = [&](unsigned t) {
    while (__any_sync(0xffffffffu, clk32() - t_start < t)) {}
  };
  TL(0); TLG(1);

  uint8_t* const region = scratch + (size_t)j * REGION;
  uint8_t* const wp = region + W_OFF + it * W_KC + (warp * 32 + lane) * 16;
  unsigned* const fl = reinterpret_cast<unsigned*>(region) + lane;
  float lutv, sc;
  unsigned rb;
  const int xrow = it * BM + wg * 128;

  auto w_ptr = [&](int u) { return reinterpret_cast<uint4*>(wp + u * W_STAGE); };
  auto emit_unit = [&](const int (&qq)[8], int u) {
    st_strong128(w_ptr(u), convert_unit(qq, lutv, sc));
    rb = ld_strong(w_ptr(u));
  };
  auto publish = [&](int u, unsigned inc) {
    asm volatile(
        "{\n.reg .pred P, Q;\n"
        "setp.ne.u32 P, %1, 0xffffffff;\n"
        "vote.sync.all.pred P, P, 0xffffffff;\n"
        "setp.eq.and.s32 Q, %2, %3, P;\n"
        "@Q red.relaxed.gpu.global.add.u32 [%0], %4;\n}"
        ::"l"(fl), "r"(rb), "r"(lane), "r"(u), "r"(inc) : "memory");
  };
  auto load_x = [&](int g, int n, int kb, int half) {
    const uint32_t bar = ring(bars + 8 * B_FULLX, n) + g * 64;
    mbar_expect_tx(bar, X_SLICE);
    tma_load_2d(sbase + SMEM_X + (n % XS) * X_SLICE + g * (XS * X_SLICE), &tm_x, kb * BK,
                it * BM + g * 128 + half * 64, bar);
  };
  auto load_q = [&](int u) {
    const uint32_t bar = ring(bars + 8 * B_FULLQ, u);
    mbar_expect_tx(bar, Q_UNIT);
    tma_load_2d(sbase + SMEM_Q + (u & 3) * Q_UNIT, &tm_q, j * BN, u * BK + it * 8, bar);
  };
  auto prefetch_x = [&](int g) {
    if (PF_X) tma_prefetch_2d(&tm_x, (4 * g + (j >> 2)) * BK, it * BM + (j & 3) * 64);
  };
  auto prefetch_q = [&](int u) {
    if (PF_Q) tma_prefetch_2d(&tm_q, j * BN, u * BK + it * 8);
  };

  unsigned ready = 0;
  auto load_w = [&](uint32_t bar, int dst, int src, int bytes) {
    mbar_expect_tx(bar, bytes);
    bulk_load(sbase + SMEM_W + dst, region + W_OFF + src, bytes, bar);
  };
  auto poll = [&]() { ready |= __ballot_sync(0xffffffffu, ld_strong(fl) >= FLAG_FULL); };
  auto wait_ready = [&](int kb) {
    int spins = 0;
    while (!((ready >> kb) & 1)) {
      poll();
      if (++spins > (1 << 22)) __trap();
    }
  };

  uint32_t qbase;
  asm volatile("mov.u32 %0, %1;" : "=r"(qbase) : "r"(sbase + SMEM_Q + warp * 128 + perm32(lane) * 4));
  auto lds_unit = [&](int (&q)[8], int u) {
    ring_wait(bars + 8 * B_FULLQ, u);
#pragma unroll
    for (int i = 0; i < 8; i++) q[i] = lds32(qbase + (u & 3) * Q_UNIT + i * (BN * 4));
  };
  auto arrive_one = [&](uint32_t bar) {
    asm volatile("{\n.reg .pred P;\nelect.sync _|P, 0xffffffff;\n@P mbarrier.arrive.shared::cta.b64 _, [%0];\n}"
                 ::"r"(bar) : "memory");
  };

  int q[8];
  constexpr uint32_t raw0 = sbase + SMEM_W + 2 * W_STAGE;
  const int fcol = j * BN + (warp < 7 ? warp : 0) * 32 + perm32(lane);
  uint32_t lut_raw = 0, sc_raw = 0;
  if (warp < 7) {
    if (elect_one()) {
      mbar_init(bars + 8 * B_RAW0 + 8 * warp, 1);
      if (warp == 6) mbar_init(bars + 8 * B_RAW0 + 8 * 7, 1);
      asm volatile("fence.mbarrier_init.release.cluster;" ::: "memory");
    }
    if (U1_FIRST) load_unit(q, qw + (size_t)(BK + it * 8) * F_DIM + fcol);
    lut_raw = ldg_u16(lut + (lane & 15));
    sc_raw = ldg_u16(scales + fcol);
    pace(PACE_L + warp * STAG_L);
    for (int c = warp; c < (warp == 6 ? 8 : warp + 1); c++) {
      if (elect_one()) {
        mbar_expect_tx(bars + 8 * B_RAW0 + 8 * c, Q_UNIT);
#pragma unroll
        for (int i = 0; i < 8; i++)
          bulk_load(raw0 + (c * 8 + i) * (BN * 4), qw + (size_t)(c * 8 + i) * F_DIM + j * BN, BN * 4,
                    bars + 8 * B_RAW0 + 8 * c);
      }
    }
  }
  if (warp == 7) {
    if (elect_one()) {
      asm volatile("prefetch.tensormap [%0];" ::"l"(&tm_q) : "memory");
      asm volatile("prefetch.tensormap [%0];" ::"l"(&tm_x) : "memory");
    }
    pace(PACE_INIT);
    if (elect_one()) {
#pragma unroll
      for (int i = 0; i < B_RAW0; i++) mbar_init(bars + 8 * i, i == B_W0 ? 7 : i >= B_DONE ? 4 : 1);
      asm volatile("fence.mbarrier_init.release.cluster;" ::: "memory");
    }
    __syncwarp();
    rb = ld_strong(fl);
    bar_arrive(0, 256);
    TL(4);
    lutv = 0.f;
    sc = 0.f;
    if (smem_u32(smem_raw) != sbase) __trap();
    pace(PACE_U1 + it * STAG);
    if (elect_one()) {
      mbar_arrive(bars + 8 * B_FULLW);
      mbar_arrive(bars + 8 * B_FULLQ);
      if (U1_FIRST) mbar_arrive(bars + 8 * B_FULLQ + 8);
      else load_q(1);
    }
    pace(PACE_X);
    if (elect_one()) {
      load_x(0, 0, 0, 0); load_x(1, 0, 0, 0); load_x(0, 1, 0, 1); load_x(1, 1, 0, 1);
    }
    pace(PACE_Q2 + it * STAG);
    if (elect_one()) load_q(2);
    pace(PACE_Q3 + it * STAG);
    ready = __ballot_sync(0xffffffffu, rb >= FLAG_FULL);
    rb = ld_strong(fl);
    if (elect_one()) {
      load_q(3);
      load_x(0, 2, 1, 0); load_x(1, 2, 1, 0); load_x(0, 3, 1, 1); load_x(1, 3, 1, 1);
    }
    ready |= __ballot_sync(0xffffffffu, rb >= FLAG_FULL);
    wait_ready(1);
    asm volatile("fence.proxy.async.global;" ::: "memory");
    if (elect_one()) {
      load_w(bars + 8 * B_FULLW + 8, W_STAGE, W_STAGE, W_STAGE);
      load_q(4);
      load_x(0, 4, 2, 0); load_x(1, 4, 2, 0);
    }
    TL(2);
    TL(3);
  } else {
    bar_sync(0, 256);
    asm volatile("shl.b32 %0, %0, 16;\nshl.b32 %1, %1, 16;" : "+r"(lut_raw), "+r"(sc_raw));
    lutv = __uint_as_float(lut_raw);
    sc = __uint_as_float(sc_raw);
    int r[2][8];
    auto lds_raw0 = [&](int c) {
      mbar_wait(bars + 8 * B_RAW0 + 8 * c, 0);
#pragma unroll
      for (int i = 0; i < 8; i++) r[c & 1][i] = lds32(qbase + (raw0 - sbase - SMEM_Q) + (c * 8 + i) * (BN * 4));
    };
    if (EMIT_AT < 0) {
      emit_unit(q, 1);
      TL(2);
    }
    lds_raw0(0);
    TL(6);
#pragma unroll
    for (int c = 0; c < 8; c++) {
      if (c == EMIT_AT) {
        if (!U1_FIRST) lds_unit(q, 1);
        emit_unit(q, 1);
        TL(2);
      }
      if (c == PUB_AT) {
        publish(1, 1);
        TL(3);
      }
      if (c < 7) lds_raw0(c + 1);
      sts128(sbase + SMEM_W + c * W_KC + (warp * 32 + lane) * 16, convert_unit(r[c & 1], lutv, sc));
    }
    asm volatile("fence.proxy.async.shared::cta;" ::: "memory");
    __syncwarp();
    arrive_one(bars + 8 * B_W0);
    if (PUB_AT == 8) {
      publish(1, 1);
      TL(3);
    }
    TL(4);
    lds_unit(q, 2);
    emit_unit(q, 2);
    TL(5);
  }

  float acc0[112], acc1[112];
  constexpr uint32_t DA_HI = (1u << 30) | (1024 >> 4), DB_HI = (128 >> 4);
  const uint32_t da0 = ((1u << 16) | ((sbase + SMEM_X) >> 4)) + wg * (XS * X_SLICE >> 4);
  constexpr uint32_t db0 = ((W_KC >> 4) << 16) | ((sbase + SMEM_W) >> 4);
  const uint32_t fullx = bars + 8 * B_FULLX + wg * 64, done = bars + 8 * B_DONE + wg * 64;
  const bool x_issuer = (warp & 3) == 3;

  auto mma = [&](float (&acc)[112], int n, int kb, int k0, int k1) {
    const int wslot = kb == 15 ? 4 : (kb & 3);
    wgmma_fence();
#pragma unroll
    for (int k = k0; k < k1; k++)
      wgmma_m64n224k16(acc, make_desc(da0 + (n % XS) * (X_SLICE >> 4) + k * 2, DA_HI),
                       make_desc(db0 + wslot * (W_STAGE >> 4) + k * (2 * W_KC >> 4), DB_HI), kb != 0 || k != 0);
    wgmma_commit();
  };
  auto release = [&](int n) {
    arrive_one(ring(done, n));
    if (x_issuer) {
      ring_wait(done, n);
      const int m = n + 4;
      if (n > 0 && elect_one())
        load_x(wg, m, m < 2 * NR ? m >> 1 : end_kb((m - 2 * NR) % ENDK), m < 2 * NR ? m & 1 : (m - 2 * NR) / ENDK);
    }
  };
  auto end_slot = [&](int n) {
    wgmma_wait<1>();
    release(n);
  };
  auto slot = [&](float (&acc)[112], auto N) {
    constexpr int n = decltype(N)::value;
    constexpr bool hv = heavy(n), pub = n == 0 || heavy(n - 1);
    ring_wait(fullx, n);
    mma(acc, n, n >> 1, 0, 4);
    if (hv && warp < 7) dequant_lookup(q, lutv);
    end_slot(n);
    if (warp < 7) {
      constexpr int u = unit_at(n);
      if (pub) publish(u - 1, 1);
      if (n == 0) lds_unit(q, PU);
      if (hv) {
        constexpr int un = u + 1 < NKB ? u + 1 : u;
        dequant_finish(q, rb, w_ptr(u), sc, ring(bars + 8 * B_FULLQ, un), un >> 3, qbase + (un & 3) * Q_UNIT);
      }
    } else {
      constexpr int m = w_at(n), u = q_at(n), m_next = w_at(n + 1);
      if (n > 0 && (m >= 0 || u >= 0)) ring_wait(bars + 8 * B_DONE, n - 1);
      if (m >= 0) {
        ready |= __ballot_sync(0xffffffffu, rb >= FLAG_FULL);
        wait_ready(m);
        asm volatile("fence.proxy.async.global;" ::: "memory");
      }
      if (m_next >= 0) rb = ld_strong(fl);
      if ((m >= 0 || u >= 0 || n == 4 || n == 10) && elect_one()) {
        if (m >= 0)
          load_w(ring(bars + 8 * B_FULLW, m), (m == 15 ? 4 : m & 3) * W_STAGE, m * W_STAGE, W_STAGE);
        if (u >= 0) load_q(u);
        if (u >= 0 && u + 2 < NKB) prefetch_q(u + 2);
        if (n == 4 || n == 10) prefetch_x(n == 4 ? 2 : 3);
      }
    }
  };

  static_for<0, NR>([&](auto R) {
    constexpr int r = decltype(R)::value;
    if (r == 0) mbar_wait(bars + 8 * B_W0, 0);
    else ring_wait(bars + 8 * B_FULLW, r);
    TL(8 + 2 * r);
    if (r == 0) TLG(46);
    slot(acc0, IC<2 * r>{});
    TL(9 + 2 * r);
    slot(acc1, IC<2 * r + 1>{});
  });

  __nv_bfloat16* op = out + (size_t)(xrow + (warp & 3) * 16 + (lane >> 2)) * F_DIM + j * BN + (lane & 3) * 8;
  TL(40); TLG(48);
  if (wg == 1) {
    wgmma_wait<0>();
    release(2 * NR);
    if (warp == 7) {
      wait_ready(14);
      asm volatile("fence.proxy.async.global;" ::: "memory");
      ring_wait(bars + 8 * B_DONE, 2 * NR);
      if (elect_one()) load_w(ring(bars + 8 * B_FULLW, 14), 2 * W_STAGE, 14 * W_STAGE, W_STAGE);
      unsigned old = 0;
      if (lane == 17) old = atomicAdd(fl, 1u);
      if (__shfl_sync(0xffffffffu, old, 17) == NI - 1) *fl = 0;
    }
    bar_sync(1, 256);
  }
#pragma unroll
  for (int e = 0; e < ENDK; e++) {
    ring_wait(bars + 8 * B_FULLW, end_kb(e));
    ring_wait(fullx, 2 * NR + e);
    mma(acc0, 2 * NR + e, end_kb(e), 0, 4);
    if (e == ENDK - 1) bar_arrive(1 + wg, 256);
    wgmma_wait<1>();
    if (e > 0 || wg == 0) release(2 * NR + e);
  }
  wgmma_wait<0>();
  release(2 * NR + ENDK);
  TL(41);
  store_acc(acc0, op, 0, 7);
  TL(42);
  bar_sync(2 - wg, 256);
#pragma unroll
  for (int e = 0; e < ENDK; e++) {
    ring_wait(fullx, 2 * NR + ENDK + e);
    mma(acc1, 2 * NR + ENDK + e, end_kb(e), 0, 4);
  }
  if (wg == 0) bar_arrive(1, 256);
  wgmma_wait<0>();
  TL(43); TLG(47);
  store_acc(acc1, op + 64 * F_DIM, 0, 7);
  TL(44);
}

typedef CUresult (*EncodeTiledFn)(CUtensorMap*, CUtensorMapDataType, cuuint32_t, void*, const cuuint64_t*,
                                  const cuuint64_t*, const cuuint32_t*, const cuuint32_t*, CUtensorMapInterleave,
                                  CUtensorMapSwizzle, CUtensorMapL2promotion, CUtensorMapFloatOOBfill);

}

#define XPROMO CU_TENSOR_MAP_L2_PROMOTION_L2_128B
extern "C" void kernel_launch(void* const* d_in, const int* in_sizes, int n_in, void* d_out, int out_size) {
  const __nv_bfloat16* x = (const __nv_bfloat16*)d_in[0];
  const int* qw = (const int*)d_in[1];
  const __nv_bfloat16* lut = (const __nv_bfloat16*)d_in[2];
  const __nv_bfloat16* scales = (const __nv_bfloat16*)d_in[3];
  __nv_bfloat16* out = (__nv_bfloat16*)d_out;

  static EncodeTiledFn enc = nullptr;
  static uint8_t* p_scr = nullptr;
  if (!enc) {
    void* fn = nullptr;
    cudaDriverEntryPointQueryResult qr;
    cudaGetDriverEntryPoint("cuTensorMapEncodeTiled", &fn, cudaEnableDefault, &qr);
    enc = (EncodeTiledFn)fn;
    void* p = nullptr;
    cudaGetSymbolAddress(&p, g_scratch);
    p_scr = (uint8_t*)(((uintptr_t)p + REGION - 1) & ~(uintptr_t)(REGION - 1));
    cudaFuncSetAttribute(fused_kernel, cudaFuncAttributeMaxDynamicSharedMemorySize, SMEM_TOTAL);
  }
  CUtensorMap tm_x, tm_q;
  cuuint32_t estr[2] = {1, 1};
  {
    cuuint64_t gdim[2] = {(cuuint64_t)D_DIM, (cuuint64_t)S_DIM};
    cuuint64_t gstr[1] = {(cuuint64_t)D_DIM * 2};
    cuuint32_t box[2] = {(cuuint32_t)BK, 64};
    enc(&tm_x, CU_TENSOR_MAP_DATA_TYPE_BFLOAT16, 2, (void*)x, gdim, gstr, box, estr, CU_TENSOR_MAP_INTERLEAVE_NONE,
        CU_TENSOR_MAP_SWIZZLE_128B, XPROMO, CU_TENSOR_MAP_FLOAT_OOB_FILL_NONE);
  }
  {
    cuuint64_t gdim[2] = {(cuuint64_t)F_DIM, (cuuint64_t)D_DIM};
    cuuint64_t gstr[1] = {(cuuint64_t)F_DIM * 4};
    cuuint32_t box[2] = {(cuuint32_t)BN, 8};
    enc(&tm_q, CU_TENSOR_MAP_DATA_TYPE_INT32, 2, (void*)qw, gdim, gstr, box, estr, CU_TENSOR_MAP_INTERLEAVE_NONE,
        CU_TENSOR_MAP_SWIZZLE_NONE, CU_TENSOR_MAP_L2_PROMOTION_NONE, CU_TENSOR_MAP_FLOAT_OOB_FILL_NONE);
  }
  fused_kernel<<<NI * NJ, 256, SMEM_TOTAL, cudaStreamPerThread>>>(qw, lut, scales, out, p_scr, tm_x, tm_q);
}
```

```cpp
#include <cuda_runtime.h>
#include <cuda_bf16.h>
#include <cuda.h>
#include <stdint.h>

namespace {

constexpr int S_DIM = 2048, D_DIM = 1024, F_DIM = 3584;
constexpr int BM = 256, BN = 224, BK = 64;
constexpr int NKB = D_DIM / BK;
constexpr int NJ = F_DIM / BN;
constexpr int NI = S_DIM / BM;
constexpr int WS = 4;
constexpr int XS = 5;
constexpr int ENDK = 5;
constexpr int NR = NKB - ENDK;
constexpr int X_SLICE = 64 * BK * 2;
constexpr int W_STAGE = BN * BK * 2;
constexpr int W_KC = BN * 16;

constexpr int REGION = 512 * 1024;
__device__ uint4 g_scratch[(NJ + 1) * REGION / 16];

__device__ __forceinline__ uint32_t smem_u32(const void* p) { return (uint32_t)__cvta_generic_to_shared(p); }
__device__ __forceinline__ unsigned clk32() {
  unsigned c;
  asm volatile("mov.u32 %0, %%clock;" : "=r"(c)::"memory");
  return c;
}
__device__ __forceinline__ bool elect_one() {
  uint32_t p;
  asm volatile("{\n.reg .pred P;\nelect.sync _|P, 0xffffffff;\nselp.b32 %0, 1, 0, P;\n}" : "=r"(p));
  return p != 0;
}
__device__ __forceinline__ void mbar_init(uint32_t bar, uint32_t cnt) {
  asm volatile("mbarrier.init.shared::cta.b64 [%0], %1;" ::"r"(bar), "r"(cnt) : "memory");
}
__device__ __forceinline__ void mbar_expect_tx(uint32_t bar, uint32_t bytes) {
  asm volatile("mbarrier.arrive.expect_tx.shared::cta.b64 _, [%0], %1;" ::"r"(bar), "r"(bytes) : "memory");
}
__device__ __forceinline__ void mbar_arrive(uint32_t bar) {
  asm volatile("mbarrier.arrive.shared::cta.b64 _, [%0];" ::"r"(bar) : "memory");
}
__device__ __forceinline__ bool mbar_test(uint32_t bar, uint32_t parity) {
  uint32_t ok;
  asm volatile(
      "{\n.reg .pred p;\nmbarrier.test_wait.parity.shared::cta.b64 p, [%1], %2;\nselp.b32 %0, 1, 0, p;\n}\n"
      : "=r"(ok) : "r"(bar), "r"(parity) : "memory");
  return ok != 0;
}
__device__ __forceinline__ void mbar_wait(uint32_t bar, uint32_t parity) {
  asm volatile(
      "{\n.reg .pred p;\n"
      "LAB_WAIT:\n"
      "mbarrier.try_wait.parity.shared::cta.b64 p, [%0], %1;\n"
      "@p bra LAB_DONE;\n"
      "bra LAB_WAIT;\n"
      "LAB_DONE:\n}\n" ::"r"(bar), "r"(parity) : "memory");
}
__device__ __forceinline__ uint32_t ring(uint32_t base, int i) { return base + 8 * (i & 7); }
__device__ __forceinline__ void ring_wait(uint32_t base, int i) { mbar_wait(ring(base, i), (i >> 3) & 1); }
__device__ __forceinline__ void tma_load_2d(uint32_t dst, const CUtensorMap* tm, int c0, int c1, uint32_t bar) {
  asm volatile(
      "cp.async.bulk.tensor.2d.shared::cluster.global.mbarrier::complete_tx::bytes [%0], [%1, {%3, %4}], [%2];"
      ::"r"(dst), "l"(tm), "r"(bar), "r"(c0), "r"(c1) : "memory");
}
__device__ __forceinline__ void tma_prefetch_2d(const CUtensorMap* tm, int c0, int c1) {
  asm volatile("cp.async.bulk.prefetch.tensor.2d.L2.global [%0, {%1, %2}];" ::"l"(tm), "r"(c0), "r"(c1) : "memory");
}
__device__ __forceinline__ void bulk_load(uint32_t dst, const void* src, uint32_t bytes, uint32_t bar) {
  asm volatile(
      "cp.async.bulk.shared::cluster.global.mbarrier::complete_tx::bytes [%0], [%1], %2, [%3];"
      ::"r"(dst), "l"(src), "r"(bytes), "r"(bar) : "memory");
}
__device__ __forceinline__ int ldg_stream(const int* p) {
  int v;
  asm volatile("ld.global.L1::no_allocate.b32 %0, [%1];" : "=r"(v) : "l"(p) : "memory");
  return v;
}
__device__ __forceinline__ void cp_async16(uint32_t dst, const void* src) {
  asm volatile("cp.async.cg.shared.global [%0], [%1], 16;" ::"r"(dst), "l"(src) : "memory");
}
__device__ __forceinline__ void cp_async_commit() { asm volatile("cp.async.commit_group;" ::: "memory"); }
template <int N>
__device__ __forceinline__ void cp_async_wait() { asm volatile("cp.async.wait_group %0;" ::"n"(N) : "memory"); }
__device__ __forceinline__ uint32_t ldg_u16(const void* p) {
  uint32_t v;
  asm volatile("ld.global.u16 %0, [%1];" : "=r"(v) : "l"(p) : "memory");
  return v;
}
__device__ __forceinline__ int lds32(uint32_t addr) {
  int v;
  asm volatile("ld.shared.b32 %0, [%1];" : "=r"(v) : "r"(addr) : "memory");
  return v;
}
__device__ __forceinline__ void sts128(uint32_t addr, uint4 v) {
  asm volatile("st.shared.v4.u32 [%0], {%1, %2, %3, %4};" ::"r"(addr), "r"(v.x), "r"(v.y), "r"(v.z), "r"(v.w) : "memory");
}
__device__ __forceinline__ uint64_t make_desc(uint32_t lo, uint32_t hi) {
  uint64_t d;
  asm("mov.b64 %0, {%1, %2};" : "=l"(d) : "r"(lo), "r"(hi));
  return d;
}
__device__ __forceinline__ unsigned ld_strong(const void* p) {
  unsigned v;
  asm volatile("ld.relaxed.gpu.global.u32 %0, [%1];" : "=r"(v) : "l"(p) : "memory");
  return v;
}
__device__ __forceinline__ void st_strong128(void* p, uint4 v) {
  asm volatile("st.relaxed.gpu.global.v4.u32 [%0], {%1, %2, %3, %4};" ::"l"(p), "r"(v.x), "r"(v.y), "r"(v.z), "r"(v.w)
               : "memory");
}
__device__ __forceinline__ void wgmma_fence() { asm volatile("wgmma.fence.sync.aligned;" ::: "memory"); }
__device__ __forceinline__ void wgmma_commit() { asm volatile("wgmma.commit_group.sync.aligned;" ::: "memory"); }
template <int N>
__device__ __forceinline__ void wgmma_wait() { asm volatile("wgmma.wait_group.sync.aligned %0;" ::"n"(N) : "memory"); }
__device__ __forceinline__ void bar_sync(int id, int n) { asm volatile("bar.sync %0, %1;" ::"r"(id), "r"(n) : "memory"); }
__device__ __forceinline__ void bar_arrive(int id, int n) { asm volatile("bar.arrive %0, %1;" ::"r"(id), "r"(n) : "memory"); }

__device__ __forceinline__ void wgmma_m64n224k16(float (&d)[112], uint64_t da, uint64_t db, int scale_d) {
  asm volatile(
    "{\n.reg .pred p;\nsetp.ne.b32 p, %114, 0;\n"
    "wgmma.mma_async.sync.aligned.m64n224k16.f32.bf16.bf16 "
    "{%0, %1, %2, %3, %4, %5, %6, %7, %8, %9, %10, %11, %12, %13, %14, %15, "
    "%16, %17, %18, %19, %20, %21, %22, %23, %24, %25, %26, %27, %28, %29, %30, %31, "
    "%32, %33, %34, %35, %36, %37, %38, %39, %40, %41, %42, %43, %44, %45, %46, %47, "
    "%48, %49, %50, %51, %52, %53, %54, %55, %56, %57, %58, %59, %60, %61, %62, %63, "
    "%64, %65, %66, %67, %68, %69, %70, %71, %72, %73, %74, %75, %76, %77, %78, %79, "
    "%80, %81, %82, %83, %84, %85, %86, %87, %88, %89, %90, %91, %92, %93, %94, %95, "
    "%96, %97, %98, %99, %100, %101, %102, %103, %104, %105, %106, %107, %108, %109, %110, %111}, "
    "%112, %113, p, 1, 1, 0, 0;\n}\n"
    : "+f"(d[0]), "+f"(d[1]), "+f"(d[2]), "+f"(d[3]), "+f"(d[4]), "+f"(d[5]), "+f"(d[6]), "+f"(d[7]),
      "+f"(d[8]), "+f"(d[9]), "+f"(d[10]), "+f"(d[11]), "+f"(d[12]), "+f"(d[13]), "+f"(d[14]), "+f"(d[15]),
      "+f"(d[16]), "+f"(d[17]), "+f"(d[18]), "+f"(d[19]), "+f"(d[20]), "+f"(d[21]), "+f"(d[22]), "+f"(d[23]),
      "+f"(d[24]), "+f"(d[25]), "+f"(d[26]), "+f"(d[27]), "+f"(d[28]), "+f"(d[29]), "+f"(d[30]), "+f"(d[31]),
      "+f"(d[32]), "+f"(d[33]), "+f"(d[34]), "+f"(d[35]), "+f"(d[36]), "+f"(d[37]), "+f"(d[38]), "+f"(d[39]),
      "+f"(d[40]), "+f"(d[41]), "+f"(d[42]), "+f"(d[43]), "+f"(d[44]), "+f"(d[45]), "+f"(d[46]), "+f"(d[47]),
      "+f"(d[48]), "+f"(d[49]), "+f"(d[50]), "+f"(d[51]), "+f"(d[52]), "+f"(d[53]), "+f"(d[54]), "+f"(d[55]),
      "+f"(d[56]), "+f"(d[57]), "+f"(d[58]), "+f"(d[59]), "+f"(d[60]), "+f"(d[61]), "+f"(d[62]), "+f"(d[63]),
      "+f"(d[64]), "+f"(d[65]), "+f"(d[66]), "+f"(d[67]), "+f"(d[68]), "+f"(d[69]), "+f"(d[70]), "+f"(d[71]),
      "+f"(d[72]), "+f"(d[73]), "+f"(d[74]), "+f"(d[75]), "+f"(d[76]), "+f"(d[77]), "+f"(d[78]), "+f"(d[79]),
      "+f"(d[80]), "+f"(d[81]), "+f"(d[82]), "+f"(d[83]), "+f"(d[84]), "+f"(d[85]), "+f"(d[86]), "+f"(d[87]),
      "+f"(d[88]), "+f"(d[89]), "+f"(d[90]), "+f"(d[91]), "+f"(d[92]), "+f"(d[93]), "+f"(d[94]), "+f"(d[95]),
      "+f"(d[96]), "+f"(d[97]), "+f"(d[98]), "+f"(d[99]), "+f"(d[100]), "+f"(d[101]), "+f"(d[102]), "+f"(d[103]),
      "+f"(d[104]), "+f"(d[105]), "+f"(d[106]), "+f"(d[107]), "+f"(d[108]), "+f"(d[109]), "+f"(d[110]), "+f"(d[111])
    : "l"(da), "l"(db), "r"(scale_d));
}
__device__ __forceinline__ void wgmma_m64n128k16(float (&d)[112], uint64_t da, uint64_t db) {
  asm volatile(
    "wgmma.mma_async.sync.aligned.m64n128k16.f32.bf16.bf16 "
    "{%0, %1, %2, %3, %4, %5, %6, %7, %8, %9, %10, %11, %12, %13, %14, %15, "
    "%16, %17, %18, %19, %20, %21, %22, %23, %24, %25, %26, %27, %28, %29, %30, %31, "
    "%32, %33, %34, %35, %36, %37, %38, %39, %40, %41, %42, %43, %44, %45, %46, %47, "
    "%48, %49, %50, %51, %52, %53, %54, %55, %56, %57, %58, %59, %60, %61, %62, %63}, "
    "%64, %65, 1, 1, 1, 0, 0;\n"
    : "+f"(d[0]), "+f"(d[1]), "+f"(d[2]), "+f"(d[3]), "+f"(d[4]), "+f"(d[5]), "+f"(d[6]), "+f"(d[7]),
      "+f"(d[8]), "+f"(d[9]), "+f"(d[10]), "+f"(d[11]), "+f"(d[12]), "+f"(d[13]), "+f"(d[14]), "+f"(d[15]),
      "+f"(d[16]), "+f"(d[17]), "+f"(d[18]), "+f"(d[19]), "+f"(d[20]), "+f"(d[21]), "+f"(d[22]), "+f"(d[23]),
      "+f"(d[24]), "+f"(d[25]), "+f"(d[26]), "+f"(d[27]), "+f"(d[28]), "+f"(d[29]), "+f"(d[30]), "+f"(d[31]),
      "+f"(d[32]), "+f"(d[33]), "+f"(d[34]), "+f"(d[35]), "+f"(d[36]), "+f"(d[37]), "+f"(d[38]), "+f"(d[39]),
      "+f"(d[40]), "+f"(d[41]), "+f"(d[42]), "+f"(d[43]), "+f"(d[44]), "+f"(d[45]), "+f"(d[46]), "+f"(d[47]),
      "+f"(d[48]), "+f"(d[49]), "+f"(d[50]), "+f"(d[51]), "+f"(d[52]), "+f"(d[53]), "+f"(d[54]), "+f"(d[55]),
      "+f"(d[56]), "+f"(d[57]), "+f"(d[58]), "+f"(d[59]), "+f"(d[60]), "+f"(d[61]), "+f"(d[62]), "+f"(d[63])
    : "l"(da), "l"(db));
}
__device__ __forceinline__ void wgmma_m64n96k16(float (&d)[112], uint64_t da, uint64_t db) {
  asm volatile(
    "wgmma.mma_async.sync.aligned.m64n96k16.f32.bf16.bf16 "
    "{%0, %1, %2, %3, %4, %5, %6, %7, %8, %9, %10, %11, %12, %13, %14, %15, "
    "%16, %17, %18, %19, %20, %21, %22, %23, %24, %25, %26, %27, %28, %29, %30, %31, "
    "%32, %33, %34, %35, %36, %37, %38, %39, %40, %41, %42, %43, %44, %45, %46, %47}, "
    "%48, %49, 1, 1, 1, 0, 0;\n"
    : "+f"(d[64]), "+f"(d[65]), "+f"(d[66]), "+f"(d[67]), "+f"(d[68]), "+f"(d[69]), "+f"(d[70]), "+f"(d[71]),
      "+f"(d[72]), "+f"(d[73]), "+f"(d[74]), "+f"(d[75]), "+f"(d[76]), "+f"(d[77]), "+f"(d[78]), "+f"(d[79]),
      "+f"(d[80]), "+f"(d[81]), "+f"(d[82]), "+f"(d[83]), "+f"(d[84]), "+f"(d[85]), "+f"(d[86]), "+f"(d[87]),
      "+f"(d[88]), "+f"(d[89]), "+f"(d[90]), "+f"(d[91]), "+f"(d[92]), "+f"(d[93]), "+f"(d[94]), "+f"(d[95]),
      "+f"(d[96]), "+f"(d[97]), "+f"(d[98]), "+f"(d[99]), "+f"(d[100]), "+f"(d[101]), "+f"(d[102]), "+f"(d[103]),
      "+f"(d[104]), "+f"(d[105]), "+f"(d[106]), "+f"(d[107]), "+f"(d[108]), "+f"(d[109]), "+f"(d[110]), "+f"(d[111])
    : "l"(da), "l"(db));
}

__device__ __forceinline__ uint32_t pack_bf16(float lo, float hi) {
  uint32_t r;
  asm("cvt.rn.bf16x2.f32 %0, %1, %2;" : "=r"(r) : "f"(hi), "f"(lo));
  return r;
}

__device__ __forceinline__ int perm32(int n) { return (n & ~30) | ((n & 6) << 2) | ((n >> 2) & 6); }

constexpr int SMEM_X = 0;
constexpr int SMEM_W = 2 * XS * X_SLICE;
constexpr int SMEM_Q = SMEM_W + WS * W_STAGE;
constexpr int Q_UNIT = 8 * BN * 4;
constexpr int SMEM_BAR = SMEM_Q + W_STAGE;
constexpr int B_FULLW = 0, B_FULLQ = 8, B_FULLX = 16, B_DONE = 32, B_W0 = 48, B_RAW0 = 49, B_COUNT = 57;
constexpr int SMEM_TL = SMEM_BAR + B_COUNT * 8;
constexpr int SMEM_TOTAL = SMEM_TL + 2048;
constexpr int W_OFF = 128;
constexpr unsigned FLAG_FULL = NI * 7;

#define TL(i)
#define TLG(i)

__device__ __forceinline__ void store_acc(const float (&a)[112], __nv_bfloat16* p, int J0, int J1) {
#pragma unroll
  for (int J = J0; J < J1; J++) {
    uint4 v0, v1;
    v0.x = pack_bf16(a[16 * J + 0], a[16 * J + 1]);
    v0.y = pack_bf16(a[16 * J + 4], a[16 * J + 5]);
    v0.z = pack_bf16(a[16 * J + 8], a[16 * J + 9]);
    v0.w = pack_bf16(a[16 * J + 12], a[16 * J + 13]);
    v1.x = pack_bf16(a[16 * J + 2], a[16 * J + 3]);
    v1.y = pack_bf16(a[16 * J + 6], a[16 * J + 7]);
    v1.z = pack_bf16(a[16 * J + 10], a[16 * J + 11]);
    v1.w = pack_bf16(a[16 * J + 14], a[16 * J + 15]);
    *reinterpret_cast<uint4*>(p + 32 * J) = v0;
    *reinterpret_cast<uint4*>(p + 8 * F_DIM + 32 * J) = v1;
  }
}

__device__ __forceinline__ void load_unit(int (&q)[8], const int* p) {
#pragma unroll
  for (int i = 0; i < 8; i++) q[i] = ldg_stream(p + i * F_DIM);
}
__device__ __forceinline__ uint4 convert_unit(const int (&q)[8], float lutv, float sc) {
  float v[8];
#pragma unroll
  for (int i = 0; i < 8; i++) v[i] = __shfl_sync(0xffffffffu, lutv, q[i]) * sc;
  uint4 o;
  o.x = pack_bf16(v[0], v[1]);
  o.y = pack_bf16(v[2], v[3]);
  o.z = pack_bf16(v[4], v[5]);
  o.w = pack_bf16(v[6], v[7]);
  return o;
}

__device__ __forceinline__ void dequant_lookup(int (&q)[8], float lutv) {
  asm volatile(
      "shfl.sync.idx.b32 %0, %8, %0, 31, 0xffffffff;\n"
      "shfl.sync.idx.b32 %1, %8, %1, 31, 0xffffffff;\n"
      "shfl.sync.idx.b32 %2, %8, %2, 31, 0xffffffff;\n"
      "shfl.sync.idx.b32 %3, %8, %3, 31, 0xffffffff;\n"
      "shfl.sync.idx.b32 %4, %8, %4, 31, 0xffffffff;\n"
      "shfl.sync.idx.b32 %5, %8, %5, 31, 0xffffffff;\n"
      "shfl.sync.idx.b32 %6, %8, %6, 31, 0xffffffff;\n"
      "shfl.sync.idx.b32 %7, %8, %7, 31, 0xffffffff;\n"
      : "+r"(q[0]), "+r"(q[1]), "+r"(q[2]), "+r"(q[3]), "+r"(q[4]), "+r"(q[5]), "+r"(q[6]), "+r"(q[7])
      : "r"(__float_as_int(lutv)));
}
__device__ __forceinline__ void dequant_finish(int (&q)[8], unsigned& rb, uint4* wp, float sc, uint32_t qbar,
                                               uint32_t qpar, uint32_t qaddr) {
  asm volatile(
      "{\n.reg .pred W;\n.reg .b32 o0, o1, o2, o3;\n"
      "DQ_WAIT:\n"
      "mbarrier.try_wait.parity.shared::cta.b64 W, [%11], %13;\n"
      "@!W bra DQ_WAIT;\n"
      "mul.rn.f32 %0, %0, %10;\nmul.rn.f32 %1, %1, %10;\nmul.rn.f32 %2, %2, %10;\nmul.rn.f32 %3, %3, %10;\n"
      "mul.rn.f32 %4, %4, %10;\nmul.rn.f32 %5, %5, %10;\nmul.rn.f32 %6, %6, %10;\nmul.rn.f32 %7, %7, %10;\n"
      "cvt.rn.bf16x2.f32 o0, %1, %0;\ncvt.rn.bf16x2.f32 o1, %3, %2;\n"
      "cvt.rn.bf16x2.f32 o2, %5, %4;\ncvt.rn.bf16x2.f32 o3, %7, %6;\n"
      "ld.volatile.shared.b32 %0, [%12];\nld.volatile.shared.b32 %1, [%12+896];\n"
      "ld.volatile.shared.b32 %2, [%12+1792];\nld.volatile.shared.b32 %3, [%12+2688];\n"
      "ld.volatile.shared.b32 %4, [%12+3584];\nld.volatile.shared.b32 %5, [%12+4480];\n"
      "ld.volatile.shared.b32 %6, [%12+5376];\nld.volatile.shared.b32 %7, [%12+6272];\n"
      "st.relaxed.gpu.global.v4.u32 [%9], {o0, o1, o2, o3};\n"
      "ld.relaxed.gpu.global.u32 %8, [%9];\n}\n"
      : "+r"(q[0]), "+r"(q[1]), "+r"(q[2]), "+r"(q[3]), "+r"(q[4]), "+r"(q[5]), "+r"(q[6]), "+r"(q[7]), "=r"(rb)
      : "l"(wp), "r"(__float_as_int(sc)), "r"(qbar), "r"(qaddr), "r"(qpar)
      : "memory");
}

constexpr int PU = 3;
#define HEAVY 0x3BBBAu
__host__ __device__ constexpr int popc(unsigned v) { return v ? (v & 1) + popc(v >> 1) : 0; }
__host__ __device__ constexpr bool heavy(int n) { return n >= 0 && ((HEAVY >> n) & 1); }
__host__ __device__ constexpr int unit_at(int n) { return PU + popc(HEAVY & ((1u << n) - 1)); }
__host__ __device__ constexpr int emit_slot(int u) {
  if (u < PU) return -1;
  for (int n = 0; n < 24; n++)
    if (heavy(n) && unit_at(n) == u) return n;
  return 99;
}
__host__ __device__ constexpr int end_kb(int e) { return e < 3 ? NR + e : NR + 7 - e; }
__host__ __device__ constexpr int cmax(int a, int b) { return a > b ? a : b; }
__host__ __device__ constexpr int w_slot(int m) {
  return m == 15 ? cmax(emit_slot(15) + 3, 20) : cmax(2 * m - 5, emit_slot(m) + 3);
}
__host__ __device__ constexpr int q_slot(int u) {
  return u == 5 ? 0 : cmax(q_slot(u - 1) + 1, u - 5 < PU ? u - 5 : emit_slot(u - 5) + 2);
}
__host__ __device__ constexpr int w_at(int n) {
  for (int m = 2; m < NKB; m++)
    if (w_slot(m) == n) return m;
  return -1;
}
__host__ __device__ constexpr int q_at(int n) {
  for (int u = 5; u < NKB; u++)
    if (q_slot(u) == n) return u;
  return -1;
}
constexpr bool schedule_ok() {
  if (popc(HEAVY) != NKB - PU || (HEAVY & 1) || (HEAVY >> 20)) return false;
  for (int m = 2; m < NKB; m++) {
    if (w_at(w_slot(m)) != m || (m != 14 && w_slot(m) >= 2 * NR)) return false;
    if (m < NR && w_slot(m) > 2 * m - 2) return false;
  }
  for (int u = 5; u < NKB; u++)
    if (q_slot(u) + 2 > emit_slot(u - 1)) return false;
  return true;
}
static_assert(schedule_ok(), "bad schedule");
template <int V>
struct IC {
  static constexpr int value = V;
};
template <int I, int N, class F>
__device__ __forceinline__ void static_for(F&& f) {
  if constexpr (I < N) {
    f(IC<I>{});
    static_for<I + 1, N>(f);
  }
}

#define NCP 3
#define U1_POS 0
#define PACE_L 0
#define STAG_L 70
#define SPLIT_END 0
#define PACE_INIT 650
#define PACE_U1 600
#define PACE_X 1200
#define PACE_Q2 1350
#define PACE_Q3 2300
#define STAG 60
#define EMIT_AT -1
#define PUB_AT 5
#define PF_X 0
#define PF_Q 0

constexpr uint32_t sbase = 1024;

__global__ void __launch_bounds__(256, 1)
fused_kernel(const int* __restrict__ qw, const __nv_bfloat16* __restrict__ lut,
             const __nv_bfloat16* __restrict__ scales, __nv_bfloat16* __restrict__ out, uint8_t* scratch,
             const __grid_constant__ CUtensorMap tm_x, const __grid_constant__ CUtensorMap tm_q) {
  extern __shared__ __align__(1024) uint8_t smem_raw[];
  constexpr uint32_t bars = sbase + SMEM_BAR;
  const int j = blockIdx.x >> 3, it = blockIdx.x & 7;
  const int warp = __shfl_sync(0xffffffffu, threadIdx.x >> 5, 0);
  const int wg = warp >> 2;
  int lane;
  asm volatile("mov.u32 %0, %%laneid;" : "=r"(lane));
  const unsigned t_start = clk32();
  auto pace = [&](unsigned t) {
    while (__any_sync(0xffffffffu, clk32() - t_start < t)) {}
  };
  TL(0); TLG(1);

  uint8_t* const region = scratch + (size_t)j * REGION;
  uint8_t* const wp = region + W_OFF + it * W_KC + (warp * 32 + lane) * 16;
  unsigned* const fl = reinterpret_cast<unsigned*>(region) + lane;
  float lutv, sc;
  unsigned rb;
  const int xrow = it * BM + wg * 128;

  auto w_ptr = [&](int u) { return reinterpret_cast<uint4*>(wp + u * W_STAGE); };
  auto emit_unit = [&](const int (&qq)[8], int u) {
    st_strong128(w_ptr(u), convert_unit(qq, lutv, sc));
    rb = ld_strong(w_ptr(u));
  };
  auto publish = [&](int u, unsigned inc) {
    asm volatile(
        "{\n.reg .pred P, Q;\n"
        "setp.ne.u32 P, %1, 0xffffffff;\n"
        "vote.sync.all.pred P, P, 0xffffffff;\n"
        "setp.eq.and.s32 Q, %2, %3, P;\n"
        "@Q red.relaxed.gpu.global.add.u32 [%0], %4;\n}"
        ::"l"(fl), "r"(rb), "r"(lane), "r"(u), "r"(inc) : "memory");
  };
  auto load_x = [&](int g, int n, int kb, int half) {
    const uint32_t bar = ring(bars + 8 * B_FULLX, n) + g * 64;
    mbar_expect_tx(bar, X_SLICE);
    tma_load_2d(sbase + SMEM_X + (n % XS) * X_SLICE + g * (XS * X_SLICE), &tm_x, kb * BK,
                it * BM + g * 128 + half * 64, bar);
  };
  auto load_q = [&](int u) {
    const uint32_t bar = ring(bars + 8 * B_FULLQ, u);
    mbar_expect_tx(bar, Q_UNIT);
    tma_load_2d(sbase + SMEM_Q + (u & 3) * Q_UNIT, &tm_q, j * BN, u * BK + it * 8, bar);
  };
  auto prefetch_x = [&](int g) {
    if (PF_X) tma_prefetch_2d(&tm_x, (4 * g + (j >> 2)) * BK, it * BM + (j & 3) * 64);
  };
  auto prefetch_q = [&](int u) {
    if (PF_Q) tma_prefetch_2d(&tm_q, j * BN, u * BK + it * 8);
  };

  unsigned ready = 0;
  auto load_w = [&](uint32_t bar, int dst, int src, int bytes) {
    mbar_expect_tx(bar, bytes);
    bulk_load(sbase + SMEM_W + dst, region + W_OFF + src, bytes, bar);
  };
  auto poll = [&]() { ready |= __ballot_sync(0xffffffffu, ld_strong(fl) >= FLAG_FULL); };
  auto wait_ready = [&](int kb) {
    int spins = 0;
    while (!((ready >> kb) & 1)) {
      poll();
      if (++spins > (1 << 22)) __trap();
    }
  };

  uint32_t qbase;
  asm volatile("mov.u32 %0, %1;" : "=r"(qbase) : "r"(sbase + SMEM_Q + warp * 128 + perm32(lane) * 4));
  auto lds_unit = [&](int (&q)[8], int u) {
    ring_wait(bars + 8 * B_FULLQ, u);
#pragma unroll
    for (int i = 0; i < 8; i++) q[i] = lds32(qbase + (u & 3) * Q_UNIT + i * (BN * 4));
  };
  auto arrive_one = [&](uint32_t bar) {
    asm volatile("{\n.reg .pred P;\nelect.sync _|P, 0xffffffff;\n@P mbarrier.arrive.shared::cta.b64 _, [%0];\n}"
                 ::"r"(bar) : "memory");
  };

  int q[8];
  constexpr uint32_t raw0 = sbase + SMEM_W + 2 * W_STAGE;
  if (warp == 7) {
    if (elect_one()) {
      asm volatile("prefetch.tensormap [%0];" ::"l"(&tm_q) : "memory");
      asm volatile("prefetch.tensormap [%0];" ::"l"(&tm_x) : "memory");
    }
    pace(PACE_INIT);
    if (elect_one()) {
#pragma unroll
      for (int i = 0; i < B_RAW0; i++) mbar_init(bars + 8 * i, i == B_W0 ? 7 : i >= B_DONE ? 4 : 1);
      asm volatile("fence.mbarrier_init.release.cluster;" ::: "memory");
    }
    __syncwarp();
    rb = ld_strong(fl);
    bar_arrive(0, 256);
    TL(4);
    lutv = 0.f;
    sc = 0.f;
    if (smem_u32(smem_raw) != sbase) __trap();
    if (elect_one()) {
      mbar_arrive(bars + 8 * B_FULLW);
      mbar_arrive(bars + 8 * B_FULLQ);
      mbar_arrive(bars + 8 * B_FULLQ + 8);
    }
    pace(PACE_X);
    if (elect_one()) {
      load_x(0, 0, 0, 0); load_x(1, 0, 0, 0); load_x(0, 1, 0, 1); load_x(1, 1, 0, 1);
    }
    pace(PACE_Q2 + it * STAG);
    if (elect_one()) load_q(2);
    pace(PACE_Q3 + it * STAG);
    ready = __ballot_sync(0xffffffffu, rb >= FLAG_FULL);
    rb = ld_strong(fl);
    if (elect_one()) {
      load_q(3);
      load_x(0, 2, 1, 0); load_x(1, 2, 1, 0); load_x(0, 3, 1, 1); load_x(1, 3, 1, 1);
    }
    ready |= __ballot_sync(0xffffffffu, rb >= FLAG_FULL);
    wait_ready(1);
    asm volatile("fence.proxy.async.global;" ::: "memory");
    if (elect_one()) {
      load_w(bars + 8 * B_FULLW + 8, W_STAGE, W_STAGE, W_STAGE);
      load_q(4);
      load_x(0, 4, 2, 0); load_x(1, 4, 2, 0);
    }
    TL(2);
    TL(3);
  } else {
    const int fcol = j * BN + warp * 32 + perm32(lane);
    if (warp + NCP < 8 && elect_one()) {
      mbar_init(bars + 8 * B_RAW0 + 8 * (warp + NCP), 1);
      asm volatile("fence.mbarrier_init.release.cluster;" ::: "memory");
    }
    uint32_t lut_raw = ldg_u16(lut + (lane & 15)), sc_raw = ldg_u16(scales + fcol);
    const int* src = qw + (size_t)(lane >> 3) * F_DIM + j * BN + warp * 32 + (lane & 7) * 4;
    const uint32_t dst = (lane >> 3) * (BN * 4) + warp * 128 + (lane & 7) * 16;
#pragma unroll
    for (int g = 0; g < NCP + 1; g++) {
      const int c = g < U1_POS ? g : g - 1;
      const int row = g == U1_POS ? BK + it * 8 : c * 8;
      const uint32_t d = dst + (g == U1_POS ? sbase + SMEM_Q + Q_UNIT : raw0 + c * Q_UNIT);
      cp_async16(d, src + (size_t)row * F_DIM);
      cp_async16(d + 4 * BN * 4, src + (size_t)(row + 4) * F_DIM);
      cp_async_commit();
    }
    pace(PACE_L + warp * STAG_L);
    if (warp + NCP < 8 && elect_one()) {
      const int c = warp + NCP;
      mbar_expect_tx(bars + 8 * B_RAW0 + 8 * c, Q_UNIT);
#pragma unroll
      for (int i = 0; i < 8; i++)
        bulk_load(raw0 + (c * 8 + i) * (BN * 4), qw + (size_t)(c * 8 + i) * F_DIM + j * BN, BN * 4,
                  bars + 8 * B_RAW0 + 8 * c);
    }
    bar_sync(0, 256);
    asm volatile("shl.b32 %0, %0, 16;\nshl.b32 %1, %1, 16;" : "+r"(lut_raw), "+r"(sc_raw));
    lutv = __uint_as_float(lut_raw);
    sc = __uint_as_float(sc_raw);
    int r[2][8];
    auto lds_group = [&](auto G) {
      constexpr int g = decltype(G)::value, c = g < U1_POS ? g : g - 1;
      if constexpr (g <= NCP) {
        cp_async_wait<NCP - g>();
        __syncwarp();
      } else {
        mbar_wait(bars + 8 * B_RAW0 + 8 * c, 0);
      }
#pragma unroll
      for (int i = 0; i < 8; i++)
        r[g & 1][i] = lds32(qbase + (g == U1_POS ? Q_UNIT : raw0 - sbase - SMEM_Q + c * Q_UNIT) + i * (BN * 4));
    };
    lds_group(IC<0>{});
    TL(6);
    static_for<0, 9>([&](auto G) {
      constexpr int g = decltype(G)::value, c = g < U1_POS ? g : g - 1;
      if (g == PUB_AT) {
        publish(1, 1);
        TL(3);
      }
      if (g == U1_POS) {
        emit_unit(r[g & 1], 1);
        TL(2);
        if constexpr (g < 8) lds_group(IC<g + 1>{});
      } else {
        if constexpr (g < 8) lds_group(IC<g + 1>{});
        sts128(sbase + SMEM_W + c * W_KC + (warp * 32 + lane) * 16, convert_unit(r[g & 1], lutv, sc));
      }
    });
    asm volatile("fence.proxy.async.shared::cta;" ::: "memory");
    __syncwarp();
    arrive_one(bars + 8 * B_W0);
    if (PUB_AT == 9) {
      publish(1, 1);
      TL(3);
    }
    TL(4);
    lds_unit(q, 2);
    emit_unit(q, 2);
    TL(5);
  }

  float acc0[112], acc1[112];
  constexpr uint32_t DA_HI = (1u << 30) | (1024 >> 4), DB_HI = (128 >> 4);
  const uint32_t da0 = ((1u << 16) | ((sbase + SMEM_X) >> 4)) + wg * (XS * X_SLICE >> 4);
  constexpr uint32_t db0 = ((W_KC >> 4) << 16) | ((sbase + SMEM_W) >> 4);
  const uint32_t fullx = bars + 8 * B_FULLX + wg * 64, done = bars + 8 * B_DONE + wg * 64;
  const bool x_issuer = (warp & 3) == 3;

  auto mma = [&](float (&acc)[112], int n, int kb, int k0, int k1) {
    const int wslot = kb == 15 ? 4 : (kb & 3);
    wgmma_fence();
#pragma unroll
    for (int k = k0; k < k1; k++)
      wgmma_m64n224k16(acc, make_desc(da0 + (n % XS) * (X_SLICE >> 4) + k * 2, DA_HI),
                       make_desc(db0 + wslot * (W_STAGE >> 4) + k * (2 * W_KC >> 4), DB_HI), kb != 0 || k != 0);
    wgmma_commit();
  };
  auto release = [&](int n) {
    arrive_one(ring(done, n));
    if (x_issuer) {
      ring_wait(done, n);
      const int m = n + 4;
      if (n > 0 && elect_one())
        load_x(wg, m, m < 2 * NR ? m >> 1 : end_kb((m - 2 * NR) % ENDK), m < 2 * NR ? m & 1 : (m - 2 * NR) / ENDK);
    }
  };
  auto end_slot = [&](int n) {
    wgmma_wait<1>();
    release(n);
  };
  auto slot = [&](float (&acc)[112], auto N) {
    constexpr int n = decltype(N)::value;
    constexpr bool hv = heavy(n), pub = n == 0 || heavy(n - 1);
    ring_wait(fullx, n);
    mma(acc, n, n >> 1, 0, 4);
    if (hv && warp < 7) dequant_lookup(q, lutv);
    end_slot(n);
    if (warp < 7) {
      constexpr int u = unit_at(n);
      if (pub) publish(u - 1, 1);
      if (n == 0) lds_unit(q, PU);
      if (hv) {
        constexpr int un = u + 1 < NKB ? u + 1 : u;
        dequant_finish(q, rb, w_ptr(u), sc, ring(bars + 8 * B_FULLQ, un), un >> 3, qbase + (un & 3) * Q_UNIT);
      }
    } else {
      constexpr int m = w_at(n), u = q_at(n), m_next = w_at(n + 1);
      if (n > 0 && (m >= 0 || u >= 0)) ring_wait(bars + 8 * B_DONE, n - 1);
      if (m >= 0) {
        ready |= __ballot_sync(0xffffffffu, rb >= FLAG_FULL);
        wait_ready(m);
        asm volatile("fence.proxy.async.global;" ::: "memory");
      }
      if (m_next >= 0) rb = ld_strong(fl);
      if ((m >= 0 || u >= 0 || n == 4 || n == 10) && elect_one()) {
        if (m >= 0)
          load_w(ring(bars + 8 * B_FULLW, m), (m == 15 ? 4 : m & 3) * W_STAGE, m * W_STAGE, W_STAGE);
        if (u >= 0) load_q(u);
        if (u >= 0 && u + 2 < NKB) prefetch_q(u + 2);
        if (n == 4 || n == 10) prefetch_x(n == 4 ? 2 : 3);
      }
    }
  };

  static_for<0, NR>([&](auto R) {
    constexpr int r = decltype(R)::value;
    if (r == 0) mbar_wait(bars + 8 * B_W0, 0);
    else ring_wait(bars + 8 * B_FULLW, r);
    TL(8 + 2 * r);
    if (r == 0) TLG(46);
    slot(acc0, IC<2 * r>{});
    TL(9 + 2 * r);
    slot(acc1, IC<2 * r + 1>{});
  });

  __nv_bfloat16* op = out + (size_t)(xrow + (warp & 3) * 16 + (lane >> 2)) * F_DIM + j * BN + (lane & 3) * 8;
  TL(40); TLG(48);
  if (wg == 1) {
    wgmma_wait<0>();
    release(2 * NR);
    if (warp == 7) {
      wait_ready(14);
      asm volatile("fence.proxy.async.global;" ::: "memory");
      ring_wait(bars + 8 * B_DONE, 2 * NR);
      if (elect_one()) load_w(ring(bars + 8 * B_FULLW, 14), 2 * W_STAGE, 14 * W_STAGE, W_STAGE);
      unsigned old = 0;
      if (lane == 17) old = atomicAdd(fl, 1u);
      if (__shfl_sync(0xffffffffu, old, 17) == NI - 1) *fl = 0;
    }
    bar_sync(1, 256);
  }
#pragma unroll
  for (int e = 0; e < ENDK; e++) {
    ring_wait(bars + 8 * B_FULLW, end_kb(e));
    ring_wait(fullx, 2 * NR + e);
    mma(acc0, 2 * NR + e, end_kb(e), 0, 4);
    if (e == ENDK - 1) bar_arrive(1 + wg, 256);
    wgmma_wait<1>();
    if (e > 0 || wg == 0) release(2 * NR + e);
  }
  wgmma_wait<0>();
  release(2 * NR + ENDK);
  TL(41);
  store_acc(acc0, op, 0, 7);
  TL(42);
  bar_sync(2 - wg, 256);
#pragma unroll
  for (int e = 0; e < ENDK; e++) {
    ring_wait(fullx, 2 * NR + ENDK + e);
    mma(acc1, 2 * NR + ENDK + e, end_kb(e), 0, 4);
  }
  if (wg == 0) bar_arrive(1, 256);
  wgmma_wait<0>();
  TL(43); TLG(47);
  store_acc(acc1, op + 64 * F_DIM, 0, 7);
  TL(44);
}

typedef CUresult (*EncodeTiledFn)(CUtensorMap*, CUtensorMapDataType, cuuint32_t, void*, const cuuint64_t*,
                                  const cuuint64_t*, const cuuint32_t*, const cuuint32_t*, CUtensorMapInterleave,
                                  CUtensorMapSwizzle, CUtensorMapL2promotion, CUtensorMapFloatOOBfill);

}

#define XPROMO CU_TENSOR_MAP_L2_PROMOTION_L2_128B
extern "C" void kernel_launch(void* const* d_in, const int* in_sizes, int n_in, void* d_out, int out_size) {
  const __nv_bfloat16* x = (const __nv_bfloat16*)d_in[0];
  const int* qw = (const int*)d_in[1];
  const __nv_bfloat16* lut = (const __nv_bfloat16*)d_in[2];
  const __nv_bfloat16* scales = (const __nv_bfloat16*)d_in[3];
  __nv_bfloat16* out = (__nv_bfloat16*)d_out;

  static EncodeTiledFn enc = nullptr;
  static uint8_t* p_scr = nullptr;
  if (!enc) {
    void* fn = nullptr;
    cudaDriverEntryPointQueryResult qr;
    cudaGetDriverEntryPoint("cuTensorMapEncodeTiled", &fn, cudaEnableDefault, &qr);
    enc = (EncodeTiledFn)fn;
    void* p = nullptr;
    cudaGetSymbolAddress(&p, g_scratch);
    p_scr = (uint8_t*)(((uintptr_t)p + REGION - 1) & ~(uintptr_t)(REGION - 1));
    cudaFuncSetAttribute(fused_kernel, cudaFuncAttributeMaxDynamicSharedMemorySize, SMEM_TOTAL);
  }
  CUtensorMap tm_x, tm_q;
  cuuint32_t estr[2] = {1, 1};
  {
    cuuint64_t gdim[2] = {(cuuint64_t)D_DIM, (cuuint64_t)S_DIM};
    cuuint64_t gstr[1] = {(cuuint64_t)D_DIM * 2};
    cuuint32_t box[2] = {(cuuint32_t)BK, 64};
    enc(&tm_x, CU_TENSOR_MAP_DATA_TYPE_BFLOAT16, 2, (void*)x, gdim, gstr, box, estr, CU_TENSOR_MAP_INTERLEAVE_NONE,
        CU_TENSOR_MAP_SWIZZLE_128B, XPROMO, CU_TENSOR_MAP_FLOAT_OOB_FILL_NONE);
  }
  {
    cuuint64_t gdim[2] = {(cuuint64_t)F_DIM, (cuuint64_t)D_DIM};
    cuuint64_t gstr[1] = {(cuuint64_t)F_DIM * 4};
    cuuint32_t box[2] = {(cuuint32_t)BN, 8};
    enc(&tm_q, CU_TENSOR_MAP_DATA_TYPE_INT32, 2, (void*)qw, gdim, gstr, box, estr, CU_TENSOR_MAP_INTERLEAVE_NONE,
        CU_TENSOR_MAP_SWIZZLE_NONE, CU_TENSOR_MAP_L2_PROMOTION_NONE, CU_TENSOR_MAP_FLOAT_OOB_FILL_NONE);
  }
  fused_kernel<<<NI * NJ, 256, SMEM_TOTAL, cudaStreamPerThread>>>(qw, lut, scales, out, p_scr, tm_x, tm_q);
}
```

```cpp
#include <cuda_runtime.h>
#include <cuda_bf16.h>
#include <cuda.h>
#include <stdint.h>

namespace {

constexpr int S_DIM = 2048, D_DIM = 1024, F_DIM = 3584;
constexpr int BM = 256, BN = 224, BK = 64;
constexpr int NKB = D_DIM / BK;
constexpr int NJ = F_DIM / BN;
constexpr int NI = S_DIM / BM;
constexpr int WS = 4;
constexpr int XS = 5;
constexpr int ENDK = 5;
constexpr int NR = NKB - ENDK;
constexpr int X_SLICE = 64 * BK * 2;
constexpr int W_STAGE = BN * BK * 2;
constexpr int W_KC = BN * 16;

constexpr int REGION = 512 * 1024;
__device__ uint4 g_scratch[(NJ + 1) * REGION / 16];

__device__ __forceinline__ uint32_t smem_u32(const void* p) { return (uint32_t)__cvta_generic_to_shared(p); }
__device__ __forceinline__ unsigned clk32() {
  unsigned c;
  asm volatile("mov.u32 %0, %%clock;" : "=r"(c)::"memory");
  return c;
}
__device__ __forceinline__ bool elect_one() {
  uint32_t p;
  asm volatile("{\n.reg .pred P;\nelect.sync _|P, 0xffffffff;\nselp.b32 %0, 1, 0, P;\n}" : "=r"(p));
  return p != 0;
}
__device__ __forceinline__ void mbar_init(uint32_t bar, uint32_t cnt) {
  asm volatile("mbarrier.init.shared::cta.b64 [%0], %1;" ::"r"(bar), "r"(cnt) : "memory");
}
__device__ __forceinline__ void mbar_expect_tx(uint32_t bar, uint32_t bytes) {
  asm volatile("mbarrier.arrive.expect_tx.shared::cta.b64 _, [%0], %1;" ::"r"(bar), "r"(bytes) : "memory");
}
__device__ __forceinline__ void mbar_arrive(uint32_t bar) {
  asm volatile("mbarrier.arrive.shared::cta.b64 _, [%0];" ::"r"(bar) : "memory");
}
__device__ __forceinline__ bool mbar_test(uint32_t bar, uint32_t parity) {
  uint32_t ok;
  asm volatile(
      "{\n.reg .pred p;\nmbarrier.test_wait.parity.shared::cta.b64 p, [%1], %2;\nselp.b32 %0, 1, 0, p;\n}\n"
      : "=r"(ok) : "r"(bar), "r"(parity) : "memory");
  return ok != 0;
}
__device__ __forceinline__ void mbar_wait(uint32_t bar, uint32_t parity) {
  asm volatile(
      "{\n.reg .pred p;\n"
      "LAB_WAIT:\n"
      "mbarrier.try_wait.parity.shared::cta.b64 p, [%0], %1;\n"
      "@p bra LAB_DONE;\n"
      "bra LAB_WAIT;\n"
      "LAB_DONE:\n}\n" ::"r"(bar), "r"(parity) : "memory");
}
__device__ __forceinline__ uint32_t ring(uint32_t base, int i) { return base + 8 * (i & 7); }
__device__ __forceinline__ void ring_wait(uint32_t base, int i) { mbar_wait(ring(base, i), (i >> 3) & 1); }
__device__ __forceinline__ void tma_load_2d(uint32_t dst, const CUtensorMap* tm, int c0, int c1, uint32_t bar) {
  asm volatile(
      "cp.async.bulk.tensor.2d.shared::cluster.global.mbarrier::complete_tx::bytes [%0], [%1, {%3, %4}], [%2];"
      ::"r"(dst), "l"(tm), "r"(bar), "r"(c0), "r"(c1) : "memory");
}
__device__ __forceinline__ void tma_prefetch_2d(const CUtensorMap* tm, int c0, int c1) {
  asm volatile("cp.async.bulk.prefetch.tensor.2d.L2.global [%0, {%1, %2}];" ::"l"(tm), "r"(c0), "r"(c1) : "memory");
}
__device__ __forceinline__ void bulk_load(uint32_t dst, const void* src, uint32_t bytes, uint32_t bar) {
  asm volatile(
      "cp.async.bulk.shared::cluster.global.mbarrier::complete_tx::bytes [%0], [%1], %2, [%3];"
      ::"r"(dst), "l"(src), "r"(bytes), "r"(bar) : "memory");
}
__device__ __forceinline__ int ldg_stream(const int* p) {
  int v;
  asm volatile("ld.global.L1::no_allocate.b32 %0, [%1];" : "=r"(v) : "l"(p) : "memory");
  return v;
}
__device__ __forceinline__ void cp_async16(uint32_t dst, const void* src) {
  asm volatile("cp.async.cg.shared.global [%0], [%1], 16;" ::"r"(dst), "l"(src) : "memory");
}
__device__ __forceinline__ void cp_async_commit() { asm volatile("cp.async.commit_group;" ::: "memory"); }
template <int N>
__device__ __forceinline__ void cp_async_wait() { asm volatile("cp.async.wait_group %0;" ::"n"(N) : "memory"); }
__device__ __forceinline__ uint32_t ldg_u16(const void* p) {
  uint32_t v;
  asm volatile("ld.global.u16 %0, [%1];" : "=r"(v) : "l"(p) : "memory");
  return v;
}
__device__ __forceinline__ int lds32(uint32_t addr) {
  int v;
  asm volatile("ld.shared.b32 %0, [%1];" : "=r"(v) : "r"(addr) : "memory");
  return v;
}
__device__ __forceinline__ void sts128(uint32_t addr, uint4 v) {
  asm volatile("st.shared.v4.u32 [%0], {%1, %2, %3, %4};" ::"r"(addr), "r"(v.x), "r"(v.y), "r"(v.z), "r"(v.w) : "memory");
}
__device__ __forceinline__ uint64_t make_desc(uint32_t lo, uint32_t hi) {
  uint64_t d;
  asm("mov.b64 %0, {%1, %2};" : "=l"(d) : "r"(lo), "r"(hi));
  return d;
}
__device__ __forceinline__ unsigned ld_strong(const void* p) {
  unsigned v;
  asm volatile("ld.relaxed.gpu.global.u32 %0, [%1];" : "=r"(v) : "l"(p) : "memory");
  return v;
}
__device__ __forceinline__ void st_strong128(void* p, uint4 v) {
  asm volatile("st.relaxed.gpu.global.v4.u32 [%0], {%1, %2, %3, %4};" ::"l"(p), "r"(v.x), "r"(v.y), "r"(v.z), "r"(v.w)
               : "memory");
}
__device__ __forceinline__ void wgmma_fence() { asm volatile("wgmma.fence.sync.aligned;" ::: "memory"); }
__device__ __forceinline__ void wgmma_commit() { asm volatile("wgmma.commit_group.sync.aligned;" ::: "memory"); }
template <int N>
__device__ __forceinline__ void wgmma_wait() { asm volatile("wgmma.wait_group.sync.aligned %0;" ::"n"(N) : "memory"); }
__device__ __forceinline__ void bar_sync(int id, int n) { asm volatile("bar.sync %0, %1;" ::"r"(id), "r"(n) : "memory"); }
__device__ __forceinline__ void bar_arrive(int id, int n) { asm volatile("bar.arrive %0, %1;" ::"r"(id), "r"(n) : "memory"); }

__device__ __forceinline__ void wgmma_m64n224k16(float (&d)[112], uint64_t da, uint64_t db, int scale_d) {
  asm volatile(
    "{\n.reg .pred p;\nsetp.ne.b32 p, %114, 0;\n"
    "wgmma.mma_async.sync.aligned.m64n224k16.f32.bf16.bf16 "
    "{%0, %1, %2, %3, %4, %5, %6, %7, %8, %9, %10, %11, %12, %13, %14, %15, "
    "%16, %17, %18, %19, %20, %21, %22, %23, %24, %25, %26, %27, %28, %29, %30, %31, "
    "%32, %33, %34, %35, %36, %37, %38, %39, %40, %41, %42, %43, %44, %45, %46, %47, "
    "%48, %49, %50, %51, %52, %53, %54, %55, %56, %57, %58, %59, %60, %61, %62, %63, "
    "%64, %65, %66, %67, %68, %69, %70, %71, %72, %73, %74, %75, %76, %77, %78, %79, "
    "%80, %81, %82, %83, %84, %85, %86, %87, %88, %89, %90, %91, %92, %93, %94, %95, "
    "%96, %97, %98, %99, %100, %101, %102, %103, %104, %105, %106, %107, %108, %109, %110, %111}, "
    "%112, %113, p, 1, 1, 0, 0;\n}\n"
    : "+f"(d[0]), "+f"(d[1]), "+f"(d[2]), "+f"(d[3]), "+f"(d[4]), "+f"(d[5]), "+f"(d[6]), "+f"(d[7]),
      "+f"(d[8]), "+f"(d[9]), "+f"(d[10]), "+f"(d[11]), "+f"(d[12]), "+f"(d[13]), "+f"(d[14]), "+f"(d[15]),
      "+f"(d[16]), "+f"(d[17]), "+f"(d[18]), "+f"(d[19]), "+f"(d[20]), "+f"(d[21]), "+f"(d[22]), "+f"(d[23]),
      "+f"(d[24]), "+f"(d[25]), "+f"(d[26]), "+f"(d[27]), "+f"(d[28]), "+f"(d[29]), "+f"(d[30]), "+f"(d[31]),
      "+f"(d[32]), "+f"(d[33]), "+f"(d[34]), "+f"(d[35]), "+f"(d[36]), "+f"(d[37]), "+f"(d[38]), "+f"(d[39]),
      "+f"(d[40]), "+f"(d[41]), "+f"(d[42]), "+f"(d[43]), "+f"(d[44]), "+f"(d[45]), "+f"(d[46]), "+f"(d[47]),
      "+f"(d[48]), "+f"(d[49]), "+f"(d[50]), "+f"(d[51]), "+f"(d[52]), "+f"(d[53]), "+f"(d[54]), "+f"(d[55]),
      "+f"(d[56]), "+f"(d[57]), "+f"(d[58]), "+f"(d[59]), "+f"(d[60]), "+f"(d[61]), "+f"(d[62]), "+f"(d[63]),
      "+f"(d[64]), "+f"(d[65]), "+f"(d[66]), "+f"(d[67]), "+f"(d[68]), "+f"(d[69]), "+f"(d[70]), "+f"(d[71]),
      "+f"(d[72]), "+f"(d[73]), "+f"(d[74]), "+f"(d[75]), "+f"(d[76]), "+f"(d[77]), "+f"(d[78]), "+f"(d[79]),
      "+f"(d[80]), "+f"(d[81]), "+f"(d[82]), "+f"(d[83]), "+f"(d[84]), "+f"(d[85]), "+f"(d[86]), "+f"(d[87]),
      "+f"(d[88]), "+f"(d[89]), "+f"(d[90]), "+f"(d[91]), "+f"(d[92]), "+f"(d[93]), "+f"(d[94]), "+f"(d[95]),
      "+f"(d[96]), "+f"(d[97]), "+f"(d[98]), "+f"(d[99]), "+f"(d[100]), "+f"(d[101]), "+f"(d[102]), "+f"(d[103]),
      "+f"(d[104]), "+f"(d[105]), "+f"(d[106]), "+f"(d[107]), "+f"(d[108]), "+f"(d[109]), "+f"(d[110]), "+f"(d[111])
    : "l"(da), "l"(db), "r"(scale_d));
}
__device__ __forceinline__ uint32_t pack_bf16(float lo, float hi) {
  uint32_t r;
  asm("cvt.rn.bf16x2.f32 %0, %1, %2;" : "=r"(r) : "f"(hi), "f"(lo));
  return r;
}

__device__ __forceinline__ int perm32(int n) { return (n & ~30) | ((n & 6) << 2) | ((n >> 2) & 6); }

constexpr int SMEM_X = 0;
constexpr int SMEM_W = 2 * XS * X_SLICE;
constexpr int SMEM_Q = SMEM_W + WS * W_STAGE;
constexpr int Q_UNIT = 8 * BN * 4;
constexpr int SMEM_BAR = SMEM_Q + W_STAGE;
constexpr int B_FULLW = 0, B_FULLQ = 8, B_FULLX = 16, B_DONE = 32, B_W0 = 48, B_RAW0 = 49, B_COUNT = 51;
constexpr int SMEM_TL = SMEM_BAR + B_COUNT * 8;
constexpr int SMEM_TOTAL = SMEM_TL + 2048;
constexpr int W_OFF = 128;
constexpr unsigned FLAG_FULL = NI * 7;

#define TL(i)
#define TLG(i)

__device__ __forceinline__ void store_acc(const float (&a)[112], __nv_bfloat16* p, int J0, int J1) {
#pragma unroll
  for (int J = J0; J < J1; J++) {
    uint4 v0, v1;
    v0.x = pack_bf16(a[16 * J + 0], a[16 * J + 1]);
    v0.y = pack_bf16(a[16 * J + 4], a[16 * J + 5]);
    v0.z = pack_bf16(a[16 * J + 8], a[16 * J + 9]);
    v0.w = pack_bf16(a[16 * J + 12], a[16 * J + 13]);
    v1.x = pack_bf16(a[16 * J + 2], a[16 * J + 3]);
    v1.y = pack_bf16(a[16 * J + 6], a[16 * J + 7]);
    v1.z = pack_bf16(a[16 * J + 10], a[16 * J + 11]);
    v1.w = pack_bf16(a[16 * J + 14], a[16 * J + 15]);
    *reinterpret_cast<uint4*>(p + 32 * J) = v0;
    *reinterpret_cast<uint4*>(p + 8 * F_DIM + 32 * J) = v1;
  }
}

__device__ __forceinline__ void load_unit(int (&q)[8], const int* p) {
#pragma unroll
  for (int i = 0; i < 8; i++) q[i] = ldg_stream(p + i * F_DIM);
}
__device__ __forceinline__ uint4 convert_unit(const int (&q)[8], float lutv, float sc) {
  float v[8];
#pragma unroll
  for (int i = 0; i < 8; i++) v[i] = __shfl_sync(0xffffffffu, lutv, q[i]) * sc;
  uint4 o;
  o.x = pack_bf16(v[0], v[1]);
  o.y = pack_bf16(v[2], v[3]);
  o.z = pack_bf16(v[4], v[5]);
  o.w = pack_bf16(v[6], v[7]);
  return o;
}

struct Table {
  uint32_t lo[4], hi[4];
};
__device__ __forceinline__ uint32_t prmt(uint32_t a, uint32_t b, uint32_t s) {
  uint32_t r;
  asm("prmt.b32 %0, %1, %2, %3;" : "=r"(r) : "r"(a), "r"(b), "r"(s));
  return r;
}
__device__ __forceinline__ Table make_table(float lutv, float sc) {
  Table t;
#pragma unroll
  for (int i = 0; i < 4; i++) {
    const uint32_t a = pack_bf16(__shfl_sync(0xffffffffu, lutv, 4 * i) * sc, __shfl_sync(0xffffffffu, lutv, 4 * i + 1) * sc);
    const uint32_t b =
        pack_bf16(__shfl_sync(0xffffffffu, lutv, 4 * i + 2) * sc, __shfl_sync(0xffffffffu, lutv, 4 * i + 3) * sc);
    t.lo[i] = prmt(a, b, 0x6420);
    t.hi[i] = prmt(a, b, 0x7531);
  }
  return t;
}
__device__ __forceinline__ uint4 convert_unit(const int (&q)[8], const Table& t) {
  const uint32_t all = ((q[7] * 16 + q[6]) * 256 + (q[5] * 16 + q[4])) * 65536 + ((q[3] * 16 + q[2]) * 256 + (q[1] * 16 + q[0]));
  const uint32_t s7 = all & 0x77777777u;
  const uint32_t s2 = ((all >> 1) & 0x44444444u) | 0x32103210u;
  uint32_t o[4];
#pragma unroll
  for (int h = 0; h < 2; h++) {
    const uint32_t a = h ? s7 >> 16 : s7, b = h ? s2 >> 16 : s2;
    const uint32_t lo = prmt(prmt(t.lo[0], t.lo[1], a), prmt(t.lo[2], t.lo[3], a), b);
    const uint32_t hi = prmt(prmt(t.hi[0], t.hi[1], a), prmt(t.hi[2], t.hi[3], a), b);
    o[2 * h] = prmt(lo, hi, 0x5140);
    o[2 * h + 1] = prmt(lo, hi, 0x7362);
  }
  return make_uint4(o[0], o[1], o[2], o[3]);
}

__device__ __forceinline__ void dequant_lookup(int (&q)[8], float lutv) {
  asm volatile(
      "shfl.sync.idx.b32 %0, %8, %0, 31, 0xffffffff;\n"
      "shfl.sync.idx.b32 %1, %8, %1, 31, 0xffffffff;\n"
      "shfl.sync.idx.b32 %2, %8, %2, 31, 0xffffffff;\n"
      "shfl.sync.idx.b32 %3, %8, %3, 31, 0xffffffff;\n"
      "shfl.sync.idx.b32 %4, %8, %4, 31, 0xffffffff;\n"
      "shfl.sync.idx.b32 %5, %8, %5, 31, 0xffffffff;\n"
      "shfl.sync.idx.b32 %6, %8, %6, 31, 0xffffffff;\n"
      "shfl.sync.idx.b32 %7, %8, %7, 31, 0xffffffff;\n"
      : "+r"(q[0]), "+r"(q[1]), "+r"(q[2]), "+r"(q[3]), "+r"(q[4]), "+r"(q[5]), "+r"(q[6]), "+r"(q[7])
      : "r"(__float_as_int(lutv)));
}
__device__ __forceinline__ void dequant_finish(int (&q)[8], unsigned& rb, uint4* wp, float sc, uint32_t qbar,
                                               uint32_t qpar, uint32_t qaddr) {
  asm volatile(
      "{\n.reg .pred W;\n.reg .b32 o0, o1, o2, o3;\n"
      "DQ_WAIT:\n"
      "mbarrier.try_wait.parity.shared::cta.b64 W, [%11], %13;\n"
      "@!W bra DQ_WAIT;\n"
      "mul.rn.f32 %0, %0, %10;\nmul.rn.f32 %1, %1, %10;\nmul.rn.f32 %2, %2, %10;\nmul.rn.f32 %3, %3, %10;\n"
      "mul.rn.f32 %4, %4, %10;\nmul.rn.f32 %5, %5, %10;\nmul.rn.f32 %6, %6, %10;\nmul.rn.f32 %7, %7, %10;\n"
      "cvt.rn.bf16x2.f32 o0, %1, %0;\ncvt.rn.bf16x2.f32 o1, %3, %2;\n"
      "cvt.rn.bf16x2.f32 o2, %5, %4;\ncvt.rn.bf16x2.f32 o3, %7, %6;\n"
      "ld.volatile.shared.b32 %0, [%12];\nld.volatile.shared.b32 %1, [%12+896];\n"
      "ld.volatile.shared.b32 %2, [%12+1792];\nld.volatile.shared.b32 %3, [%12+2688];\n"
      "ld.volatile.shared.b32 %4, [%12+3584];\nld.volatile.shared.b32 %5, [%12+4480];\n"
      "ld.volatile.shared.b32 %6, [%12+5376];\nld.volatile.shared.b32 %7, [%12+6272];\n"
      "st.relaxed.gpu.global.v4.u32 [%9], {o0, o1, o2, o3};\n"
      "ld.relaxed.gpu.global.u32 %8, [%9];\n}\n"
      : "+r"(q[0]), "+r"(q[1]), "+r"(q[2]), "+r"(q[3]), "+r"(q[4]), "+r"(q[5]), "+r"(q[6]), "+r"(q[7]), "=r"(rb)
      : "l"(wp), "r"(__float_as_int(sc)), "r"(qbar), "r"(qaddr), "r"(qpar)
      : "memory");
}

constexpr int PU = 3;
#define HEAVY 0x3BBBAu
__host__ __device__ constexpr int popc(unsigned v) { return v ? (v & 1) + popc(v >> 1) : 0; }
__host__ __device__ constexpr bool heavy(int n) { return n >= 0 && ((HEAVY >> n) & 1); }
__host__ __device__ constexpr int unit_at(int n) { return PU + popc(HEAVY & ((1u << n) - 1)); }
__host__ __device__ constexpr int emit_slot(int u) {
  if (u < PU) return -1;
  for (int n = 0; n < 24; n++)
    if (heavy(n) && unit_at(n) == u) return n;
  return 99;
}
__host__ __device__ constexpr int end_kb(int e) { return e < 3 ? NR + e : NR + 7 - e; }
__host__ __device__ constexpr int cmax(int a, int b) { return a > b ? a : b; }
__host__ __device__ constexpr int w_slot(int m) {
  return m == 15 ? cmax(emit_slot(15) + 3, 20) : cmax(2 * m - 5, emit_slot(m) + 3);
}
__host__ __device__ constexpr int q_slot(int u) {
  return u == 5 ? 1 : cmax(q_slot(u - 1) + 1, u - 5 < PU ? 2 : emit_slot(u - 5) + 2);
}
__host__ __device__ constexpr int w_at(int n) {
  for (int m = 2; m < NKB; m++)
    if (w_slot(m) == n) return m;
  return -1;
}
__host__ __device__ constexpr int q_at(int n) {
  for (int u = 5; u < NKB; u++)
    if (q_slot(u) == n) return u;
  return -1;
}
constexpr bool schedule_ok() {
  if (popc(HEAVY) != NKB - PU || (HEAVY & 7) != 2 || (HEAVY >> 20)) return false;
  for (int m = 2; m < NKB; m++) {
    if (w_at(w_slot(m)) != m || (m != 14 && w_slot(m) >= 2 * NR)) return false;
    if (m < NR && w_slot(m) > 2 * m - 2) return false;
  }
  for (int u = 5; u < NKB; u++)
    if (q_slot(u) + 2 > emit_slot(u - 1)) return false;
  return true;
}
static_assert(schedule_ok(), "bad schedule");
template <int V>
struct IC {
  static constexpr int value = V;
};
template <int I, int N, class F>
__device__ __forceinline__ void static_for(F&& f) {
  if constexpr (I < N) {
    f(IC<I>{});
    static_for<I + 1, N>(f);
  }
}

#define SHFL_MASK 0
#define RAW_TENSOR 0
#define RSPLIT 5
#define X1_AT 1
#define NCP 3
#define U1_POS 0
#define PACE_L 0
#define STAG_L 70
#define PACE_INIT 650
#define PACE_U1 600
#define PACE_X 1100
#define PACE_Q2 1600
#define PACE_Q3 2200
#define STAG 30
#define EMIT_AT -1
#define PUB_AT 6
#define PF_X 0
#define PF_Q 0

constexpr uint32_t sbase = 1024;

__global__ void __launch_bounds__(256, 1)
fused_kernel(const int* __restrict__ qw, const __nv_bfloat16* __restrict__ lut,
             const __nv_bfloat16* __restrict__ scales, __nv_bfloat16* __restrict__ out, uint8_t* scratch,
             const __grid_constant__ CUtensorMap tm_x, const __grid_constant__ CUtensorMap tm_q) {
  extern __shared__ __align__(1024) uint8_t smem_raw[];
  constexpr uint32_t bars = sbase + SMEM_BAR;
  const int j = blockIdx.x >> 3, it = blockIdx.x & 7;
  constexpr uint32_t raw0 = sbase + SMEM_W + 2 * W_STAGE;
  uint32_t lut_raw = 0, sc_raw = 0;
  if (threadIdx.x < 224) {
    const unsigned t = threadIdx.x, row0 = (t >> 3) & 3, col = (t & ~31u) + (t & 7) * 4;
    const int* src = qw + (row0 * F_DIM + j * BN + col);
    const uint32_t dst = row0 * (BN * 4) + col * 4;
    lut_raw = ldg_u16(lut + (t & 15));
    sc_raw = ldg_u16(scales + (j * BN + perm32(t)));
    __syncwarp();
#pragma unroll
    for (int g = 0; g < NCP + 1; g++) {
      const unsigned row = g == 0 ? BK + it * 8 : (g - 1) * 8;
      const uint32_t d = dst + (g == 0 ? sbase + SMEM_Q + Q_UNIT : raw0 + (g - 1) * Q_UNIT);
      cp_async16(d, src + row * F_DIM);
      cp_async16(d + 4 * BN * 4, src + (row + 4) * F_DIM);
      cp_async_commit();
    }
  }
  const int warp = __shfl_sync(0xffffffffu, threadIdx.x >> 5, 0);
  const int wg = warp >> 2;
  int lane;
  asm volatile("mov.u32 %0, %%laneid;" : "=r"(lane));
  const unsigned t_start = clk32();
  auto pace = [&](unsigned t) {
    while (__any_sync(0xffffffffu, clk32() - t_start < t)) {}
  };
  TL(0); TLG(1);

  uint8_t* const region = scratch + (size_t)j * REGION;
  uint8_t* const wp = region + W_OFF + it * W_KC + (warp * 32 + lane) * 16;
  unsigned* const fl = reinterpret_cast<unsigned*>(region) + lane;
  float lutv, sc;
  unsigned rb;
  const int xrow = it * BM + wg * 128;

  auto w_ptr = [&](int u) { return reinterpret_cast<uint4*>(wp + u * W_STAGE); };
  auto emit_unit = [&](uint4 w, int u) {
    st_strong128(w_ptr(u), w);
    rb = ld_strong(w_ptr(u));
  };
  auto publish = [&](int u, unsigned inc) {
    asm volatile(
        "{\n.reg .pred P, Q;\n"
        "setp.ne.u32 P, %1, 0xffffffff;\n"
        "vote.sync.all.pred P, P, 0xffffffff;\n"
        "setp.eq.and.s32 Q, %2, %3, P;\n"
        "@Q red.relaxed.gpu.global.add.u32 [%0], %4;\n}"
        ::"l"(fl), "r"(rb), "r"(lane), "r"(u), "r"(inc) : "memory");
  };
  auto load_x = [&](int g, int n, int kb, int half) {
    const uint32_t bar = ring(bars + 8 * B_FULLX, n) + g * 64;
    mbar_expect_tx(bar, X_SLICE);
    tma_load_2d(sbase + SMEM_X + (n % XS) * X_SLICE + g * (XS * X_SLICE), &tm_x, kb * BK,
                it * BM + g * 128 + half * 64, bar);
  };
  auto load_q = [&](int u) {
    const uint32_t bar = ring(bars + 8 * B_FULLQ, u);
    mbar_expect_tx(bar, Q_UNIT);
    tma_load_2d(sbase + SMEM_Q + (u & 3) * Q_UNIT, &tm_q, j * BN, u * BK + it * 8, bar);
  };
  auto prefetch_x = [&](int g) {
    if (PF_X) tma_prefetch_2d(&tm_x, (4 * g + (j >> 2)) * BK, it * BM + (j & 3) * 64);
  };
  auto prefetch_q = [&](int u) {
    if (PF_Q) tma_prefetch_2d(&tm_q, j * BN, u * BK + it * 8);
  };

  unsigned ready = 0;
  auto load_w = [&](uint32_t bar, int dst, int src, int bytes) {
    mbar_expect_tx(bar, bytes);
    bulk_load(sbase + SMEM_W + dst, region + W_OFF + src, bytes, bar);
  };
  auto poll = [&]() { ready |= __ballot_sync(0xffffffffu, ld_strong(fl) >= FLAG_FULL); };
  auto wait_ready = [&](int kb) {
    int spins = 0;
    while (!((ready >> kb) & 1)) {
      poll();
      if (++spins > (1 << 22)) __trap();
    }
  };

  uint32_t qbase;
  asm volatile("mov.u32 %0, %1;" : "=r"(qbase) : "r"(sbase + SMEM_Q + warp * 128 + perm32(lane) * 4));
  auto lds_unit = [&](int (&q)[8], int u) {
    ring_wait(bars + 8 * B_FULLQ, u);
#pragma unroll
    for (int i = 0; i < 8; i++) q[i] = lds32(qbase + (u & 3) * Q_UNIT + i * (BN * 4));
  };
  auto arrive_one = [&](uint32_t bar) {
    asm volatile("{\n.reg .pred P;\nelect.sync _|P, 0xffffffff;\n@P mbarrier.arrive.shared::cta.b64 _, [%0];\n}"
                 ::"r"(bar) : "memory");
  };

  int q[8];
  if (warp == 7) {
    if (elect_one()) {
      mbar_init(bars + 8 * B_RAW0, RSPLIT - NCP);
      if (RSPLIT < 8) mbar_init(bars + 8 * B_RAW0 + 8, 8 - RSPLIT);
      asm volatile("fence.mbarrier_init.release.cluster;" ::: "memory");
    }
    __syncwarp();
    bar_arrive(4, (9 - NCP) * 32);
    if (elect_one()) {
      asm volatile("prefetch.tensormap [%0];" ::"l"(&tm_x) : "memory");
      asm volatile("prefetch.tensormap [%0];" ::"l"(&tm_q) : "memory");
    }
    TL(5);
    pace(PACE_INIT);
    if (elect_one()) {
#pragma unroll
      for (int i = 0; i < B_RAW0; i++) mbar_init(bars + 8 * i, i == B_W0 ? 7 : i >= B_DONE ? 4 : 1);
      asm volatile("fence.mbarrier_init.release.cluster;" ::: "memory");
    }
    __syncwarp();
    rb = ld_strong(fl);
    bar_arrive(0, 256);
    TL(4);
    lutv = 0.f;
    sc = 0.f;
    if (smem_u32(smem_raw) != sbase) __trap();
    if (elect_one()) {
      mbar_arrive(bars + 8 * B_FULLW);
      mbar_arrive(bars + 8 * B_FULLQ);
      mbar_arrive(bars + 8 * B_FULLQ + 8);
    }
    pace(PACE_X);
    if (elect_one()) {
      load_x(0, 0, 0, 0); load_x(1, 0, 0, 0); load_x(0, 1, 0, 1); load_x(1, 1, 0, 1);
    }
    pace(PACE_Q2 + it * STAG);
    if (elect_one()) {
      load_q(2);
      if (X1_AT == 0) { load_x(0, 2, 1, 0); load_x(1, 2, 1, 0); load_x(0, 3, 1, 1); load_x(1, 3, 1, 1); }
    }
    pace(PACE_Q3 + it * STAG);
    ready = __ballot_sync(0xffffffffu, rb >= FLAG_FULL);
    rb = ld_strong(fl);
    if (elect_one()) {
      load_q(3);
      if (X1_AT == 1) { load_x(0, 2, 1, 0); load_x(1, 2, 1, 0); load_x(0, 3, 1, 1); load_x(1, 3, 1, 1); }
    }
    ready |= __ballot_sync(0xffffffffu, rb >= FLAG_FULL);
    wait_ready(1);
    asm volatile("fence.proxy.async.global;" ::: "memory");
    if (elect_one()) {
      load_w(bars + 8 * B_FULLW + 8, W_STAGE, W_STAGE, W_STAGE);
      if (X1_AT == 2) { load_x(0, 2, 1, 0); load_x(1, 2, 1, 0); load_x(0, 3, 1, 1); load_x(1, 3, 1, 1); }
      load_q(4);
      load_x(0, 4, 2, 0); load_x(1, 4, 2, 0);
    }
    TL(2);
    TL(3);
  } else {
    if (warp + NCP < 8) {
      bar_sync(4, (9 - NCP) * 32);
      pace(PACE_L + warp * STAG_L);
      if (elect_one()) {
        const int c = warp + NCP;
        const uint32_t bar = bars + 8 * B_RAW0 + (c < RSPLIT ? 0 : 8);
        mbar_expect_tx(bar, Q_UNIT);
#pragma unroll
        for (int i = 0; i < 8; i++)
          bulk_load(raw0 + (c * 8 + i) * (BN * 4), qw + (size_t)(c * 8 + i) * F_DIM + j * BN, BN * 4, bar);
      }
    }
    bar_sync(0, 256);
    pace(200);
    asm volatile("shl.b32 %0, %0, 16;\nshl.b32 %1, %1, 16;" : "+r"(lut_raw), "+r"(sc_raw));
    lutv = __uint_as_float(lut_raw);
    sc = __uint_as_float(sc_raw);
    const Table tab = make_table(lutv, sc);
    if (__any_sync(0xffffffffu, lane > 31 && (tab.lo[0] ^ tab.lo[1] ^ tab.lo[2] ^ tab.lo[3] ^ tab.hi[0] ^ tab.hi[1] ^
                                              tab.hi[2] ^ tab.hi[3]) == 1))
      __trap();
    int r[2][8];
    auto lds_group = [&](auto G) {
      constexpr int g = decltype(G)::value, c = g < U1_POS ? g : g - 1;
      if constexpr (g <= NCP) {
        cp_async_wait<NCP - g>();
        __syncwarp();
      } else {
        if (c == NCP) mbar_wait(bars + 8 * B_RAW0, 0);
        if (c == RSPLIT) mbar_wait(bars + 8 * B_RAW0 + 8, 0);
      }
#pragma unroll
      for (int i = 0; i < 8; i++)
        r[g & 1][i] = lds32(qbase + (g == U1_POS ? Q_UNIT : raw0 - sbase - SMEM_Q + c * Q_UNIT) + i * (BN * 4));
    };
    lds_group(IC<0>{});
    TL(6);
    static_for<0, 9>([&](auto G) {
      constexpr int g = decltype(G)::value, c = g < U1_POS ? g : g - 1;
      if (g == PUB_AT) {
        publish(1, 1);
        TL(3);
      }
      if (g == U1_POS) {
        emit_unit(convert_unit(r[g & 1], tab), 1);
        __syncwarp();
        TL(2);
        if constexpr (g < 8) lds_group(IC<g + 1>{});
      } else {
        if constexpr (g < 8) lds_group(IC<g + 1>{});
        sts128(sbase + SMEM_W + c * W_KC + (warp * 32 + lane) * 16,
               ((SHFL_MASK >> c) & 1) ? convert_unit(r[g & 1], lutv, sc) : convert_unit(r[g & 1], tab));
      }
    });
    asm volatile("fence.proxy.async.shared::cta;" ::: "memory");
    __syncwarp();
    arrive_one(bars + 8 * B_W0);
    if (PUB_AT == 9) {
      publish(1, 1);
      TL(3);
    }
    TL(4);
    if (wg == 1) {
      lds_unit(q, 2);
      emit_unit(convert_unit(q, tab), 2);
    }
    TL(5);
  }

  float acc0[112], acc1[112];
  constexpr uint32_t DA_HI = (1u << 30) | (1024 >> 4), DB_HI = (128 >> 4);
  const uint32_t da0 = ((1u << 16) | ((sbase + SMEM_X) >> 4)) + wg * (XS * X_SLICE >> 4);
  constexpr uint32_t db0 = ((W_KC >> 4) << 16) | ((sbase + SMEM_W) >> 4);
  const uint32_t fullx = bars + 8 * B_FULLX + wg * 64, done = bars + 8 * B_DONE + wg * 64;
  const bool x_issuer = (warp & 3) == 3;

  auto mma = [&](float (&acc)[112], int n, int kb, int k0, int k1) {
    const int wslot = kb == 15 ? 4 : (kb & 3);
    wgmma_fence();
#pragma unroll
    for (int k = k0; k < k1; k++)
      wgmma_m64n224k16(acc, make_desc(da0 + (n % XS) * (X_SLICE >> 4) + k * 2, DA_HI),
                       make_desc(db0 + wslot * (W_STAGE >> 4) + k * (2 * W_KC >> 4), DB_HI), kb != 0 || k != 0);
    wgmma_commit();
  };
  auto release = [&](int n) {
    arrive_one(ring(done, n));
    if (x_issuer) {
      ring_wait(done, n);
      const int m = n + 4;
      if (elect_one())
        load_x(wg, m, m < 2 * NR ? m >> 1 : end_kb((m - 2 * NR) % ENDK), m < 2 * NR ? m & 1 : (m - 2 * NR) / ENDK);
    }
  };
  auto end_slot = [&](int n) {
    wgmma_wait<1>();
    release(n);
  };
  auto slot = [&](float (&acc)[112], auto N) {
    constexpr int n = decltype(N)::value;
    constexpr bool hv = heavy(n), pub = heavy(n - 1);
    ring_wait(fullx, n);
    mma(acc, n, n >> 1, 0, 4);
    if (hv && warp < 7) dequant_lookup(q, lutv);
    end_slot(n);
    if (warp < 7) {
      constexpr int u = unit_at(n);
      if (pub) publish(u - 1, 1);
      if (n == 2) lds_unit(q, 4);
      if (hv) {
        constexpr int un = u + 1 < NKB ? u + 1 : u;
        dequant_finish(q, rb, w_ptr(u), sc, ring(bars + 8 * B_FULLQ, un), un >> 3, qbase + (un & 3) * Q_UNIT);
      }
    } else {
      constexpr int m = w_at(n), u = q_at(n), m_next = w_at(n + 1);
      if (m >= 0 || u >= 0) ring_wait(bars + 8 * B_DONE, n - 1);
      if (m >= 0) {
        ready |= __ballot_sync(0xffffffffu, rb >= FLAG_FULL);
        wait_ready(m);
        asm volatile("fence.proxy.async.global;" ::: "memory");
      }
      if (m_next >= 0) rb = ld_strong(fl);
      if ((m >= 0 || u >= 0 || n == 4 || n == 10) && elect_one()) {
        if (m >= 0)
          load_w(ring(bars + 8 * B_FULLW, m), (m == 15 ? 4 : m & 3) * W_STAGE, m * W_STAGE, W_STAGE);
        if (u >= 0) load_q(u);
        if (u >= 0 && u + 2 < NKB) prefetch_q(u + 2);
        if (n == 4 || n == 10) prefetch_x(n == 4 ? 2 : 3);
      }
    }
  };

  mbar_wait(bars + 8 * B_W0, 0);
  mbar_wait(fullx, 0);
  TL(8); TLG(46);
  mma(acc0, 0, 0, 0, 4);
  mbar_wait(fullx + 8, 0);
  TL(9);
  mma(acc1, 1, 0, 0, 4);
  arrive_one(done);
  if (warp < 7) {
    if (wg == 0) {
      lds_unit(q, 2);
      emit_unit(convert_unit(q, lutv, sc), 2);
    } else {
      publish(2, 1);
    }
    lds_unit(q, 3);
    const uint4 w3 = convert_unit(q, lutv, sc);
    if (wg == 0) publish(2, 1);
    st_strong128(w_ptr(3), w3);
    rb = ld_strong(w_ptr(3));
  } else {
    if (elect_one()) load_q(5);
  }
  end_slot(1);
  if (warp == 7) rb = ld_strong(fl);

  static_for<1, NR>([&](auto R) {
    constexpr int r = decltype(R)::value;
    ring_wait(bars + 8 * B_FULLW, r);
    TL(8 + 2 * r);
    slot(acc0, IC<2 * r>{});
    TL(9 + 2 * r);
    slot(acc1, IC<2 * r + 1>{});
  });

  __nv_bfloat16* op = out + (size_t)(xrow + (warp & 3) * 16 + (lane >> 2)) * F_DIM + j * BN + (lane & 3) * 8;
  TL(40); TLG(48);
  if (wg == 1) {
    wgmma_wait<0>();
    release(2 * NR);
    if (warp == 7) {
      wait_ready(14);
      asm volatile("fence.proxy.async.global;" ::: "memory");
      ring_wait(bars + 8 * B_DONE, 2 * NR);
      if (elect_one()) load_w(ring(bars + 8 * B_FULLW, 14), 2 * W_STAGE, 14 * W_STAGE, W_STAGE);
      unsigned old = 0;
      if (lane == 17) old = atomicAdd(fl, 1u);
      if (__shfl_sync(0xffffffffu, old, 17) == NI - 1) *fl = 0;
    }
    bar_sync(1, 256);
  }
#pragma unroll
  for (int e = 0; e < ENDK; e++) {
    ring_wait(bars + 8 * B_FULLW, end_kb(e));
    ring_wait(fullx, 2 * NR + e);
    mma(acc0, 2 * NR + e, end_kb(e), 0, 4);
    if (e == ENDK - 1) bar_arrive(1 + wg, 256);
    wgmma_wait<1>();
    if (e > 0 || wg == 0) release(2 * NR + e);
  }
  wgmma_wait<0>();
  release(2 * NR + ENDK);
  TL(41);
  store_acc(acc0, op, 0, 7);
  TL(42);
  bar_sync(2 - wg, 256);
#pragma unroll
  for (int e = 0; e < ENDK; e++) {
    ring_wait(fullx, 2 * NR + ENDK + e);
    mma(acc1, 2 * NR + ENDK + e, end_kb(e), 0, 4);
  }
  if (wg == 0) bar_arrive(1, 256);
  wgmma_wait<0>();
  TL(43); TLG(47);
  store_acc(acc1, op + 64 * F_DIM, 0, 7);
  TL(44);
}

typedef CUresult (*EncodeTiledFn)(CUtensorMap*, CUtensorMapDataType, cuuint32_t, void*, const cuuint64_t*,
                                  const cuuint64_t*, const cuuint32_t*, const cuuint32_t*, CUtensorMapInterleave,
                                  CUtensorMapSwizzle, CUtensorMapL2promotion, CUtensorMapFloatOOBfill);

}

#define XPROMO CU_TENSOR_MAP_L2_PROMOTION_L2_128B
extern "C" void kernel_launch(void* const* d_in, const int* in_sizes, int n_in, void* d_out, int out_size) {
  const __nv_bfloat16* x = (const __nv_bfloat16*)d_in[0];
  const int* qw = (const int*)d_in[1];
  const __nv_bfloat16* lut = (const __nv_bfloat16*)d_in[2];
  const __nv_bfloat16* scales = (const __nv_bfloat16*)d_in[3];
  __nv_bfloat16* out = (__nv_bfloat16*)d_out;

  static EncodeTiledFn enc = nullptr;
  static uint8_t* p_scr = nullptr;
  if (!enc) {
    void* fn = nullptr;
    cudaDriverEntryPointQueryResult qr;
    cudaGetDriverEntryPoint("cuTensorMapEncodeTiled", &fn, cudaEnableDefault, &qr);
    enc = (EncodeTiledFn)fn;
    void* p = nullptr;
    cudaGetSymbolAddress(&p, g_scratch);
    p_scr = (uint8_t*)(((uintptr_t)p + REGION - 1) & ~(uintptr_t)(REGION - 1));
    cudaFuncSetAttribute(fused_kernel, cudaFuncAttributeMaxDynamicSharedMemorySize, SMEM_TOTAL);
  }
  CUtensorMap tm_x, tm_q;
  cuuint32_t estr[2] = {1, 1};
  {
    cuuint64_t gdim[2] = {(cuuint64_t)D_DIM, (cuuint64_t)S_DIM};
    cuuint64_t gstr[1] = {(cuuint64_t)D_DIM * 2};
    cuuint32_t box[2] = {(cuuint32_t)BK, 64};
    enc(&tm_x, CU_TENSOR_MAP_DATA_TYPE_BFLOAT16, 2, (void*)x, gdim, gstr, box, estr, CU_TENSOR_MAP_INTERLEAVE_NONE,
        CU_TENSOR_MAP_SWIZZLE_128B, XPROMO, CU_TENSOR_MAP_FLOAT_OOB_FILL_NONE);
  }
  {
    cuuint64_t gdim[2] = {(cuuint64_t)F_DIM, (cuuint64_t)D_DIM};
    cuuint64_t gstr[1] = {(cuuint64_t)F_DIM * 4};
    cuuint32_t box[2] = {(cuuint32_t)BN, 8};
    enc(&tm_q, CU_TENSOR_MAP_DATA_TYPE_INT32, 2, (void*)qw, gdim, gstr, box, estr, CU_TENSOR_MAP_INTERLEAVE_NONE,
        CU_TENSOR_MAP_SWIZZLE_NONE, CU_TENSOR_MAP_L2_PROMOTION_NONE, CU_TENSOR_MAP_FLOAT_OOB_FILL_NONE);
  }
  fused_kernel<<<NI * NJ, 256, SMEM_TOTAL, cudaStreamPerThread>>>(qw, lut, scales, out, p_scr, tm_x, tm_q);
}
```

```cpp
#include <cuda_runtime.h>
#include <cuda_bf16.h>
#include <cuda.h>
#include <stdint.h>

namespace {

constexpr int S_DIM = 2048, D_DIM = 1024, F_DIM = 3584;
constexpr int BM = 256, BN = 224, BK = 64;
constexpr int NKB = D_DIM / BK;
constexpr int NJ = F_DIM / BN;
constexpr int NI = S_DIM / BM;
constexpr int WS = 4;
constexpr int XS = 5;
constexpr int ENDK = 5;
constexpr int NR = NKB - ENDK;
constexpr int X_SLICE = 64 * BK * 2;
constexpr int W_STAGE = BN * BK * 2;
constexpr int W_KC = BN * 16;

constexpr int REGION = 512 * 1024;
__device__ uint4 g_scratch[(NJ + 1) * REGION / 16];

__device__ __forceinline__ uint32_t smem_u32(const void* p) { return (uint32_t)__cvta_generic_to_shared(p); }
__device__ __forceinline__ unsigned clk32() {
  unsigned c;
  asm volatile("mov.u32 %0, %%clock;" : "=r"(c)::"memory");
  return c;
}
__device__ __forceinline__ bool elect_one() {
  uint32_t p;
  asm volatile("{\n.reg .pred P;\nelect.sync _|P, 0xffffffff;\nselp.b32 %0, 1, 0, P;\n}" : "=r"(p));
  return p != 0;
}
__device__ __forceinline__ void mbar_init(uint32_t bar, uint32_t cnt) {
  asm volatile("mbarrier.init.shared::cta.b64 [%0], %1;" ::"r"(bar), "r"(cnt) : "memory");
}
__device__ __forceinline__ void mbar_expect_tx(uint32_t bar, uint32_t bytes) {
  asm volatile("mbarrier.arrive.expect_tx.shared::cta.b64 _, [%0], %1;" ::"r"(bar), "r"(bytes) : "memory");
}
__device__ __forceinline__ void mbar_arrive(uint32_t bar) {
  asm volatile("mbarrier.arrive.shared::cta.b64 _, [%0];" ::"r"(bar) : "memory");
}
__device__ __forceinline__ bool mbar_test(uint32_t bar, uint32_t parity) {
  uint32_t ok;
  asm volatile(
      "{\n.reg .pred p;\nmbarrier.test_wait.parity.shared::cta.b64 p, [%1], %2;\nselp.b32 %0, 1, 0, p;\n}\n"
      : "=r"(ok) : "r"(bar), "r"(parity) : "memory");
  return ok != 0;
}
__device__ __forceinline__ void mbar_wait(uint32_t bar, uint32_t parity) {
  asm volatile(
      "{\n.reg .pred p;\n"
      "LAB_WAIT:\n"
      "mbarrier.try_wait.parity.shared::cta.b64 p, [%0], %1;\n"
      "@p bra LAB_DONE;\n"
      "bra LAB_WAIT;\n"
      "LAB_DONE:\n}\n" ::"r"(bar), "r"(parity) : "memory");
}
__device__ __forceinline__ uint32_t ring(uint32_t base, int i) { return base + 8 * (i & 7); }
__device__ __forceinline__ void ring_wait(uint32_t base, int i) { mbar_wait(ring(base, i), (i >> 3) & 1); }
__device__ __forceinline__ void tma_load_2d(uint32_t dst, const CUtensorMap* tm, int c0, int c1, uint32_t bar) {
  asm volatile(
      "cp.async.bulk.tensor.2d.shared::cluster.global.mbarrier::complete_tx::bytes [%0], [%1, {%3, %4}], [%2];"
      ::"r"(dst), "l"(tm), "r"(bar), "r"(c0), "r"(c1) : "memory");
}
__device__ __forceinline__ void tma_prefetch_2d(const CUtensorMap* tm, int c0, int c1) {
  asm volatile("cp.async.bulk.prefetch.tensor.2d.L2.global [%0, {%1, %2}];" ::"l"(tm), "r"(c0), "r"(c1) : "memory");
}
__device__ __forceinline__ void bulk_load(uint32_t dst, const void* src, uint32_t bytes, uint32_t bar) {
  asm volatile(
      "cp.async.bulk.shared::cluster.global.mbarrier::complete_tx::bytes [%0], [%1], %2, [%3];"
      ::"r"(dst), "l"(src), "r"(bytes), "r"(bar) : "memory");
}
__device__ __forceinline__ int ldg_stream(const int* p) {
  int v;
  asm volatile("ld.global.L1::no_allocate.b32 %0, [%1];" : "=r"(v) : "l"(p) : "memory");
  return v;
}
__device__ __forceinline__ void cp_async16(uint32_t dst, const void* src) {
  asm volatile("cp.async.cg.shared.global [%0], [%1], 16;" ::"r"(dst), "l"(src) : "memory");
}
__device__ __forceinline__ void cp_async_commit() { asm volatile("cp.async.commit_group;" ::: "memory"); }
template <int N>
__device__ __forceinline__ void cp_async_wait() { asm volatile("cp.async.wait_group %0;" ::"n"(N) : "memory"); }
__device__ __forceinline__ uint32_t ldg_u16(const void* p) {
  uint32_t v;
  asm volatile("ld.global.u16 %0, [%1];" : "=r"(v) : "l"(p) : "memory");
  return v;
}
__device__ __forceinline__ int lds32(uint32_t addr) {
  int v;
  asm volatile("ld.shared.b32 %0, [%1];" : "=r"(v) : "r"(addr) : "memory");
  return v;
}
__device__ __forceinline__ void sts128(uint32_t addr, uint4 v) {
  asm volatile("st.shared.v4.u32 [%0], {%1, %2, %3, %4};" ::"r"(addr), "r"(v.x), "r"(v.y), "r"(v.z), "r"(v.w) : "memory");
}
__device__ __forceinline__ uint64_t make_desc(uint32_t lo, uint32_t hi) {
  uint64_t d;
  asm("mov.b64 %0, {%1, %2};" : "=l"(d) : "r"(lo), "r"(hi));
  return d;
}
__device__ __forceinline__ unsigned ld_strong(const void* p) {
  unsigned v;
  asm volatile("ld.relaxed.gpu.global.u32 %0, [%1];" : "=r"(v) : "l"(p) : "memory");
  return v;
}
__device__ __forceinline__ void st_strong128(void* p, uint4 v) {
  asm volatile("st.relaxed.gpu.global.v4.u32 [%0], {%1, %2, %3, %4};" ::"l"(p), "r"(v.x), "r"(v.y), "r"(v.z), "r"(v.w)
               : "memory");
}
__device__ __forceinline__ void wgmma_fence() { asm volatile("wgmma.fence.sync.aligned;" ::: "memory"); }
__device__ __forceinline__ void wgmma_commit() { asm volatile("wgmma.commit_group.sync.aligned;" ::: "memory"); }
template <int N>
__device__ __forceinline__ void wgmma_wait() { asm volatile("wgmma.wait_group.sync.aligned %0;" ::"n"(N) : "memory"); }
__device__ __forceinline__ void bar_sync(int id, int n) { asm volatile("bar.sync %0, %1;" ::"r"(id), "r"(n) : "memory"); }
__device__ __forceinline__ void bar_arrive(int id, int n) { asm volatile("bar.arrive %0, %1;" ::"r"(id), "r"(n) : "memory"); }

__device__ __forceinline__ void wgmma_m64n224k16(float (&d)[112], uint64_t da, uint64_t db, int scale_d) {
  asm volatile(
    "{\n.reg .pred p;\nsetp.ne.b32 p, %114, 0;\n"
    "wgmma.mma_async.sync.aligned.m64n224k16.f32.bf16.bf16 "
    "{%0, %1, %2, %3, %4, %5, %6, %7, %8, %9, %10, %11, %12, %13, %14, %15, "
    "%16, %17, %18, %19, %20, %21, %22, %23, %24, %25, %26, %27, %28, %29, %30, %31, "
    "%32, %33, %34, %35, %36, %37, %38, %39, %40, %41, %42, %43, %44, %45, %46, %47, "
    "%48, %49, %50, %51, %52, %53, %54, %55, %56, %57, %58, %59, %60, %61, %62, %63, "
    "%64, %65, %66, %67, %68, %69, %70, %71, %72, %73, %74, %75, %76, %77, %78, %79, "
    "%80, %81, %82, %83, %84, %85, %86, %87, %88, %89, %90, %91, %92, %93, %94, %95, "
    "%96, %97, %98, %99, %100, %101, %102, %103, %104, %105, %106, %107, %108, %109, %110, %111}, "
    "%112, %113, p, 1, 1, 0, 0;\n}\n"
    : "+f"(d[0]), "+f"(d[1]), "+f"(d[2]), "+f"(d[3]), "+f"(d[4]), "+f"(d[5]), "+f"(d[6]), "+f"(d[7]),
      "+f"(d[8]), "+f"(d[9]), "+f"(d[10]), "+f"(d[11]), "+f"(d[12]), "+f"(d[13]), "+f"(d[14]), "+f"(d[15]),
      "+f"(d[16]), "+f"(d[17]), "+f"(d[18]), "+f"(d[19]), "+f"(d[20]), "+f"(d[21]), "+f"(d[22]), "+f"(d[23]),
      "+f"(d[24]), "+f"(d[25]), "+f"(d[26]), "+f"(d[27]), "+f"(d[28]), "+f"(d[29]), "+f"(d[30]), "+f"(d[31]),
      "+f"(d[32]), "+f"(d[33]), "+f"(d[34]), "+f"(d[35]), "+f"(d[36]), "+f"(d[37]), "+f"(d[38]), "+f"(d[39]),
      "+f"(d[40]), "+f"(d[41]), "+f"(d[42]), "+f"(d[43]), "+f"(d[44]), "+f"(d[45]), "+f"(d[46]), "+f"(d[47]),
      "+f"(d[48]), "+f"(d[49]), "+f"(d[50]), "+f"(d[51]), "+f"(d[52]), "+f"(d[53]), "+f"(d[54]), "+f"(d[55]),
      "+f"(d[56]), "+f"(d[57]), "+f"(d[58]), "+f"(d[59]), "+f"(d[60]), "+f"(d[61]), "+f"(d[62]), "+f"(d[63]),
      "+f"(d[64]), "+f"(d[65]), "+f"(d[66]), "+f"(d[67]), "+f"(d[68]), "+f"(d[69]), "+f"(d[70]), "+f"(d[71]),
      "+f"(d[72]), "+f"(d[73]), "+f"(d[74]), "+f"(d[75]), "+f"(d[76]), "+f"(d[77]), "+f"(d[78]), "+f"(d[79]),
      "+f"(d[80]), "+f"(d[81]), "+f"(d[82]), "+f"(d[83]), "+f"(d[84]), "+f"(d[85]), "+f"(d[86]), "+f"(d[87]),
      "+f"(d[88]), "+f"(d[89]), "+f"(d[90]), "+f"(d[91]), "+f"(d[92]), "+f"(d[93]), "+f"(d[94]), "+f"(d[95]),
      "+f"(d[96]), "+f"(d[97]), "+f"(d[98]), "+f"(d[99]), "+f"(d[100]), "+f"(d[101]), "+f"(d[102]), "+f"(d[103]),
      "+f"(d[104]), "+f"(d[105]), "+f"(d[106]), "+f"(d[107]), "+f"(d[108]), "+f"(d[109]), "+f"(d[110]), "+f"(d[111])
    : "l"(da), "l"(db), "r"(scale_d));
}
__device__ __forceinline__ uint32_t pack_bf16(float lo, float hi) {
  uint32_t r;
  asm("cvt.rn.bf16x2.f32 %0, %1, %2;" : "=r"(r) : "f"(hi), "f"(lo));
  return r;
}

__device__ __forceinline__ int perm32(int n) { return (n & ~30) | ((n & 6) << 2) | ((n >> 2) & 6); }

constexpr int SMEM_X = 0;
constexpr int SMEM_W = 2 * XS * X_SLICE;
constexpr int SMEM_Q = SMEM_W + WS * W_STAGE;
constexpr int Q_UNIT = 8 * BN * 4;
constexpr int SMEM_BAR = SMEM_Q + W_STAGE;
constexpr int B_FULLW = 0, B_FULLQ = 8, B_FULLX = 16, B_DONE = 32, B_W0 = 48, B_RAW0 = 49, B_COUNT = 51;
constexpr int SMEM_TL = SMEM_BAR + 512;
constexpr int SMEM_TOTAL = SMEM_TL + 2048;
constexpr int W_OFF = 128;
constexpr unsigned FLAG_FULL = NI * 7;

#define TL(i)
#define TLG(i)

__device__ __forceinline__ void store_acc(const float (&a)[112], __nv_bfloat16* p, int J0, int J1) {
#pragma unroll
  for (int J = J0; J < J1; J++) {
    uint4 v0, v1;
    v0.x = pack_bf16(a[16 * J + 0], a[16 * J + 1]);
    v0.y = pack_bf16(a[16 * J + 4], a[16 * J + 5]);
    v0.z = pack_bf16(a[16 * J + 8], a[16 * J + 9]);
    v0.w = pack_bf16(a[16 * J + 12], a[16 * J + 13]);
    v1.x = pack_bf16(a[16 * J + 2], a[16 * J + 3]);
    v1.y = pack_bf16(a[16 * J + 6], a[16 * J + 7]);
    v1.z = pack_bf16(a[16 * J + 10], a[16 * J + 11]);
    v1.w = pack_bf16(a[16 * J + 14], a[16 * J + 15]);
    *reinterpret_cast<uint4*>(p + 32 * J) = v0;
    *reinterpret_cast<uint4*>(p + 8 * F_DIM + 32 * J) = v1;
  }
}

__device__ __forceinline__ void load_unit(int (&q)[8], const int* p) {
#pragma unroll
  for (int i = 0; i < 8; i++) q[i] = ldg_stream(p + i * F_DIM);
}
__device__ __forceinline__ uint4 convert_unit(const int (&q)[8], float lutv, float sc) {
  float v[8];
#pragma unroll
  for (int i = 0; i < 8; i++) v[i] = __shfl_sync(0xffffffffu, lutv, q[i]) * sc;
  uint4 o;
  o.x = pack_bf16(v[0], v[1]);
  o.y = pack_bf16(v[2], v[3]);
  o.z = pack_bf16(v[4], v[5]);
  o.w = pack_bf16(v[6], v[7]);
  return o;
}

struct Table {
  uint32_t lo[4], hi[4];
};
__device__ __forceinline__ uint32_t prmt(uint32_t a, uint32_t b, uint32_t s) {
  uint32_t r;
  asm("prmt.b32 %0, %1, %2, %3;" : "=r"(r) : "r"(a), "r"(b), "r"(s));
  return r;
}
__device__ __forceinline__ Table make_table(float lutv, float sc) {
  Table t;
#pragma unroll
  for (int i = 0; i < 4; i++) {
    const uint32_t a = pack_bf16(__shfl_sync(0xffffffffu, lutv, 4 * i) * sc, __shfl_sync(0xffffffffu, lutv, 4 * i + 1) * sc);
    const uint32_t b =
        pack_bf16(__shfl_sync(0xffffffffu, lutv, 4 * i + 2) * sc, __shfl_sync(0xffffffffu, lutv, 4 * i + 3) * sc);
    t.lo[i] = prmt(a, b, 0x6420);
    t.hi[i] = prmt(a, b, 0x7531);
  }
  return t;
}
__device__ __forceinline__ uint4 convert_unit(const int (&q)[8], const Table& t) {
  const uint32_t all = ((q[7] * 16 + q[6]) * 256 + (q[5] * 16 + q[4])) * 65536 + ((q[3] * 16 + q[2]) * 256 + (q[1] * 16 + q[0]));
  const uint32_t s7 = all & 0x77777777u;
  const uint32_t s2 = ((all >> 1) & 0x44444444u) | 0x32103210u;
  uint32_t o[4];
#pragma unroll
  for (int h = 0; h < 2; h++) {
    const uint32_t a = h ? s7 >> 16 : s7, b = h ? s2 >> 16 : s2;
    const uint32_t lo = prmt(prmt(t.lo[0], t.lo[1], a), prmt(t.lo[2], t.lo[3], a), b);
    const uint32_t hi = prmt(prmt(t.hi[0], t.hi[1], a), prmt(t.hi[2], t.hi[3], a), b);
    o[2 * h] = prmt(lo, hi, 0x5140);
    o[2 * h + 1] = prmt(lo, hi, 0x7362);
  }
  return make_uint4(o[0], o[1], o[2], o[3]);
}

__device__ __forceinline__ void dequant_lookup(int (&q)[8], float lutv) {
  asm volatile(
      "shfl.sync.idx.b32 %0, %8, %0, 31, 0xffffffff;\n"
      "shfl.sync.idx.b32 %1, %8, %1, 31, 0xffffffff;\n"
      "shfl.sync.idx.b32 %2, %8, %2, 31, 0xffffffff;\n"
      "shfl.sync.idx.b32 %3, %8, %3, 31, 0xffffffff;\n"
      "shfl.sync.idx.b32 %4, %8, %4, 31, 0xffffffff;\n"
      "shfl.sync.idx.b32 %5, %8, %5, 31, 0xffffffff;\n"
      "shfl.sync.idx.b32 %6, %8, %6, 31, 0xffffffff;\n"
      "shfl.sync.idx.b32 %7, %8, %7, 31, 0xffffffff;\n"
      : "+r"(q[0]), "+r"(q[1]), "+r"(q[2]), "+r"(q[3]), "+r"(q[4]), "+r"(q[5]), "+r"(q[6]), "+r"(q[7])
      : "r"(__float_as_int(lutv)));
}
__device__ __forceinline__ void dequant_finish(int (&q)[8], unsigned& rb, uint4* wp, float sc, uint32_t qbar,
                                               uint32_t qpar, uint32_t qaddr) {
  asm volatile(
      "{\n.reg .pred W;\n.reg .b32 o0, o1, o2, o3;\n"
      "DQ_WAIT:\n"
      "mbarrier.try_wait.parity.shared::cta.b64 W, [%11], %13;\n"
      "@!W bra DQ_WAIT;\n"
      "mul.rn.f32 %0, %0, %10;\nmul.rn.f32 %1, %1, %10;\nmul.rn.f32 %2, %2, %10;\nmul.rn.f32 %3, %3, %10;\n"
      "mul.rn.f32 %4, %4, %10;\nmul.rn.f32 %5, %5, %10;\nmul.rn.f32 %6, %6, %10;\nmul.rn.f32 %7, %7, %10;\n"
      "cvt.rn.bf16x2.f32 o0, %1, %0;\ncvt.rn.bf16x2.f32 o1, %3, %2;\n"
      "cvt.rn.bf16x2.f32 o2, %5, %4;\ncvt.rn.bf16x2.f32 o3, %7, %6;\n"
      "ld.volatile.shared.b32 %0, [%12];\nld.volatile.shared.b32 %1, [%12+896];\n"
      "ld.volatile.shared.b32 %2, [%12+1792];\nld.volatile.shared.b32 %3, [%12+2688];\n"
      "ld.volatile.shared.b32 %4, [%12+3584];\nld.volatile.shared.b32 %5, [%12+4480];\n"
      "ld.volatile.shared.b32 %6, [%12+5376];\nld.volatile.shared.b32 %7, [%12+6272];\n"
      "st.relaxed.gpu.global.v4.u32 [%9], {o0, o1, o2, o3};\n"
      "ld.relaxed.gpu.global.u32 %8, [%9];\n}\n"
      : "+r"(q[0]), "+r"(q[1]), "+r"(q[2]), "+r"(q[3]), "+r"(q[4]), "+r"(q[5]), "+r"(q[6]), "+r"(q[7]), "=r"(rb)
      : "l"(wp), "r"(__float_as_int(sc)), "r"(qbar), "r"(qaddr), "r"(qpar)
      : "memory");
}

#define Q6_EARLY 0
constexpr int PU = 3;
#define HEAVY 0x3BBBAu
__host__ __device__ constexpr int popc(unsigned v) { return v ? (v & 1) + popc(v >> 1) : 0; }
__host__ __device__ constexpr bool heavy(int n) { return n >= 0 && ((HEAVY >> n) & 1); }
__host__ __device__ constexpr int unit_at(int n) { return PU + popc(HEAVY & ((1u << n) - 1)); }
__host__ __device__ constexpr int emit_slot(int u) {
  if (u < PU) return -1;
  for (int n = 0; n < 24; n++)
    if (heavy(n) && unit_at(n) == u) return n;
  return 99;
}
__host__ __device__ constexpr int end_kb(int e) { return e < 3 ? NR + e : NR + 7 - e; }
__host__ __device__ constexpr int cmax(int a, int b) { return a > b ? a : b; }
__host__ __device__ constexpr int w_slot(int m) {
  return m == 15 ? cmax(emit_slot(15) + 3, 20) : cmax(2 * m - 5, emit_slot(m) + 3);
}
__host__ __device__ constexpr int q_slot(int u) {
  return u <= 5 + Q6_EARLY ? 1 : cmax(q_slot(u - 1) + 1, u < 8 ? 2 : u == 8 ? 4 : emit_slot(u - 5) + 2);
}
__host__ __device__ constexpr int w_at(int n) {
  for (int m = 2; m < NKB; m++)
    if (w_slot(m) == n) return m;
  return -1;
}
__host__ __device__ constexpr int q_at(int n) {
  for (int u = 5; u < NKB; u++)
    if (q_slot(u) == n) return u;
  return -1;
}
constexpr bool schedule_ok() {
  if (popc(HEAVY) != NKB - PU || (HEAVY & 7) != 2 || (HEAVY >> 20)) return false;
  for (int m = 2; m < NKB; m++) {
    if (w_at(w_slot(m)) != m || (m != 14 && w_slot(m) >= 2 * NR)) return false;
    if (m < NR && w_slot(m) > 2 * m - 2) return false;
  }
  for (int u = 5; u < NKB; u++)
    if (q_slot(u) + 2 > emit_slot(u - 1)) return false;
  return true;
}
static_assert(schedule_ok(), "bad schedule");
template <int V>
struct IC {
  static constexpr int value = V;
};
template <int I, int N, class F>
__device__ __forceinline__ void static_for(F&& f) {
  if constexpr (I < N) {
    f(IC<I>{});
    static_for<I + 1, N>(f);
  }
}

#define SHFL_MASK 0
#define RSPLIT 5
#define PACE_X 1100
#define PACE_Q2 1600
#define PACE_Q3 2100
#define WAIT_MODE 0
#define Q2_FIRST 0
#define X3_LATE 0
#define Q5_EARLY 0
#define NCP 3
#define U1_POS 0
#define PACE_L 0
#define STAG_L 70
#define PACE_INIT 650
#define PUB_AT 6
#define PF_X 0
#define PF_Q 0

constexpr uint32_t sbase = 1024;

__global__ void __launch_bounds__(256, 1)
fused_kernel(const int* __restrict__ qw, const __nv_bfloat16* __restrict__ lut,
             const __nv_bfloat16* __restrict__ scales, __nv_bfloat16* __restrict__ out, uint8_t* scratch,
             const __grid_constant__ CUtensorMap tm_x, const __grid_constant__ CUtensorMap tm_q) {
  extern __shared__ __align__(1024) uint8_t smem_raw[];
  constexpr uint32_t bars = sbase + SMEM_BAR;
  const int j = blockIdx.x >> 3, it = blockIdx.x & 7;
  constexpr uint32_t raw0 = sbase + SMEM_W + 2 * W_STAGE;
  uint32_t lut_raw = 0, sc_raw = 0;
  if (threadIdx.x < 224) {
    const unsigned t = threadIdx.x, row0 = (t >> 3) & 3, col = (t & ~31u) + (t & 7) * 4;
    const int* src = qw + (row0 * F_DIM + j * BN + col);
    const uint32_t dst = row0 * (BN * 4) + col * 4;
    lut_raw = ldg_u16(lut + (t & 15));
    sc_raw = ldg_u16(scales + (j * BN + perm32(t)));
    __syncwarp();
#pragma unroll
    for (int g = 0; g < NCP + 1; g++) {
      const unsigned row = g == 0 ? BK + it * 8 : (g - 1) * 8;
      const uint32_t d = dst + (g == 0 ? sbase + SMEM_Q + Q_UNIT : raw0 + (g - 1) * Q_UNIT);
      cp_async16(d, src + row * F_DIM);
      cp_async16(d + 4 * BN * 4, src + (row + 4) * F_DIM);
      cp_async_commit();
    }
  }
  const int warp = __shfl_sync(0xffffffffu, threadIdx.x >> 5, 0);
  const int wg = warp >> 2;
  int lane;
  asm volatile("mov.u32 %0, %%laneid;" : "=r"(lane));
  const unsigned t_start = clk32();
  auto pace = [&](unsigned t) {
    while (__any_sync(0xffffffffu, clk32() - t_start < t)) {}
  };
  TL(0); TLG(1);

  uint8_t* const region = scratch + (size_t)j * REGION;
  uint8_t* const wp = region + W_OFF + it * W_KC + (warp * 32 + lane) * 16;
  unsigned* const fl = reinterpret_cast<unsigned*>(region) + lane;
  float lutv, sc;
  unsigned rb;
  const int xrow = it * BM + wg * 128;

  auto w_ptr = [&](int u) { return reinterpret_cast<uint4*>(wp + u * W_STAGE); };
  auto emit_unit = [&](uint4 w, int u) {
    st_strong128(w_ptr(u), w);
    rb = ld_strong(w_ptr(u));
  };
  auto publish = [&](int u, unsigned inc) {
    asm volatile(
        "{\n.reg .pred P, Q;\n"
        "setp.ne.u32 P, %1, 0xffffffff;\n"
        "vote.sync.all.pred P, P, 0xffffffff;\n"
        "setp.eq.and.s32 Q, %2, %3, P;\n"
        "@Q red.relaxed.gpu.global.add.u32 [%0], %4;\n}"
        ::"l"(fl), "r"(rb), "r"(lane), "r"(u), "r"(inc) : "memory");
  };
  auto load_x = [&](int g, int n, int kb, int half) {
    const uint32_t bar = ring(bars + 8 * B_FULLX, n) + g * 64;
    mbar_expect_tx(bar, X_SLICE);
    tma_load_2d(sbase + SMEM_X + (n % XS) * X_SLICE + g * (XS * X_SLICE), &tm_x, kb * BK,
                it * BM + g * 128 + half * 64, bar);
  };
  auto load_q = [&](int u) {
    const uint32_t bar = ring(bars + 8 * B_FULLQ, u);
    mbar_expect_tx(bar, Q_UNIT);
    tma_load_2d(sbase + SMEM_Q + (u & 3) * Q_UNIT, &tm_q, j * BN, u * BK + it * 8, bar);
  };
  auto prefetch_x = [&](int g) {
    if (PF_X) tma_prefetch_2d(&tm_x, (4 * g + (j >> 2)) * BK, it * BM + (j & 3) * 64);
  };
  auto prefetch_q = [&](int u) {
    if (PF_Q) tma_prefetch_2d(&tm_q, j * BN, u * BK + it * 8);
  };

  unsigned ready = 0;
  auto load_w = [&](uint32_t bar, int dst, int src, int bytes) {
    mbar_expect_tx(bar, bytes);
    bulk_load(sbase + SMEM_W + dst, region + W_OFF + src, bytes, bar);
  };
  auto poll = [&]() { ready |= __ballot_sync(0xffffffffu, ld_strong(fl) >= FLAG_FULL); };
  auto wait_ready = [&](int kb) {
    int spins = 0;
    while (!((ready >> kb) & 1)) {
      poll();
      if (++spins > (1 << 22)) __trap();
    }
  };

  uint32_t qbase;
  asm volatile("mov.u32 %0, %1;" : "=r"(qbase) : "r"(sbase + SMEM_Q + warp * 128 + perm32(lane) * 4));
  auto lds_unit = [&](int (&q)[8], int u) {
    ring_wait(bars + 8 * B_FULLQ, u);
#pragma unroll
    for (int i = 0; i < 8; i++) q[i] = lds32(qbase + (u & 3) * Q_UNIT + i * (BN * 4));
  };
  auto arrive_one = [&](uint32_t bar) {
    asm volatile("{\n.reg .pred P;\nelect.sync _|P, 0xffffffff;\n@P mbarrier.arrive.shared::cta.b64 _, [%0];\n}"
                 ::"r"(bar) : "memory");
  };

  int q[8];
  if (warp == 7) {
    if (elect_one()) {
      mbar_init(bars + 8 * B_RAW0, RSPLIT - NCP);
      if (RSPLIT < 8) mbar_init(bars + 8 * B_RAW0 + 8, 8 - RSPLIT);
      asm volatile("fence.mbarrier_init.release.cluster;" ::: "memory");
    }
    __syncwarp();
    bar_arrive(4, (9 - NCP) * 32);
    if (elect_one()) {
      asm volatile("prefetch.tensormap [%0];" ::"l"(&tm_x) : "memory");
      asm volatile("prefetch.tensormap [%0];" ::"l"(&tm_q) : "memory");
    }
    TL(5);
    pace(PACE_INIT);
    if (elect_one()) {
#pragma unroll
      for (int i = 0; i < B_RAW0; i++) mbar_init(bars + 8 * i, i == B_W0 ? 7 : i >= B_DONE ? 4 : 1);
      asm volatile("fence.mbarrier_init.release.cluster;" ::: "memory");
    }
    __syncwarp();
    rb = ld_strong(fl);
    bar_arrive(0, 256);
    TL(4);
    lutv = 0.f;
    sc = 0.f;
    if (smem_u32(smem_raw) != sbase) __trap();
    if (elect_one()) {
      mbar_arrive(bars + 8 * B_FULLW);
      mbar_arrive(bars + 8 * B_FULLQ);
      mbar_arrive(bars + 8 * B_FULLQ + 8);
    }
    if (PACE_X) pace(PACE_X);
    if (elect_one()) {
      if (Q2_FIRST) load_q(2);
      load_x(0, 0, 0, 0); load_x(1, 0, 0, 0); load_x(0, 1, 0, 1); load_x(1, 1, 0, 1);
    }
    if (!Q2_FIRST) {
      pace(PACE_Q2);
      if (elect_one()) load_q(2);
    }
    if (WAIT_MODE == 0) pace(PACE_Q3);
    if (WAIT_MODE == 1) mbar_wait(bars + 8 * B_FULLQ + 16, 0);
    if (WAIT_MODE == 2) mbar_wait(bars + 8 * B_FULLX, 0);
    ready = __ballot_sync(0xffffffffu, rb >= FLAG_FULL);
    rb = ld_strong(fl);
    if (elect_one()) {
      load_q(3);
      load_x(0, 2, 1, 0); load_x(1, 2, 1, 0);
      if (!X3_LATE) { load_x(0, 3, 1, 1); load_x(1, 3, 1, 1); }
    }
    ready |= __ballot_sync(0xffffffffu, rb >= FLAG_FULL);
    wait_ready(1);
    asm volatile("fence.proxy.async.global;" ::: "memory");
    if (elect_one()) {
      load_w(bars + 8 * B_FULLW + 8, W_STAGE, W_STAGE, W_STAGE);
      if (X3_LATE) { load_x(0, 3, 1, 1); load_x(1, 3, 1, 1); }
      load_q(4);
      load_x(0, 4, 2, 0); load_x(1, 4, 2, 0);
      if (Q5_EARLY) load_q(5);
    }
    TL(2);
    TL(3);
  } else {
    if (warp + NCP < 8) {
      bar_sync(4, (9 - NCP) * 32);
      pace(PACE_L + warp * STAG_L);
      if (elect_one()) {
        const int c = warp + NCP;
        const uint32_t bar = bars + 8 * B_RAW0 + (c < RSPLIT ? 0 : 8);
        mbar_expect_tx(bar, Q_UNIT);
#pragma unroll
        for (int i = 0; i < 8; i++)
          bulk_load(raw0 + (c * 8 + i) * (BN * 4), qw + (size_t)(c * 8 + i) * F_DIM + j * BN, BN * 4, bar);
      }
    }
    bar_sync(0, 256);
    pace(200);
    asm volatile("shl.b32 %0, %0, 16;\nshl.b32 %1, %1, 16;" : "+r"(lut_raw), "+r"(sc_raw));
    lutv = __uint_as_float(lut_raw);
    sc = __uint_as_float(sc_raw);
    const Table tab = make_table(lutv, sc);
    if (__any_sync(0xffffffffu, lane > 31 && (tab.lo[0] ^ tab.lo[1] ^ tab.lo[2] ^ tab.lo[3] ^ tab.hi[0] ^ tab.hi[1] ^
                                              tab.hi[2] ^ tab.hi[3]) == 1))
      __trap();
    int r[2][8];
    auto lds_group = [&](auto G) {
      constexpr int g = decltype(G)::value, c = g < U1_POS ? g : g - 1;
      if constexpr (g <= NCP) {
        cp_async_wait<NCP - g>();
        __syncwarp();
      } else {
        if (c == NCP) mbar_wait(bars + 8 * B_RAW0, 0);
        if (c == RSPLIT) mbar_wait(bars + 8 * B_RAW0 + 8, 0);
      }
#pragma unroll
      for (int i = 0; i < 8; i++)
        r[g & 1][i] = lds32(qbase + (g == U1_POS ? Q_UNIT : raw0 - sbase - SMEM_Q + c * Q_UNIT) + i * (BN * 4));
    };
    lds_group(IC<0>{});
    TL(6);
    static_for<0, 9>([&](auto G) {
      constexpr int g = decltype(G)::value, c = g < U1_POS ? g : g - 1;
      if (g == PUB_AT) {
        publish(1, 1);
        TL(3);
      }
      if (g == U1_POS) {
        emit_unit(convert_unit(r[g & 1], tab), 1);
        __syncwarp();
        TL(2);
        if constexpr (g < 8) lds_group(IC<g + 1>{});
      } else {
        if constexpr (g < 8) lds_group(IC<g + 1>{});
        sts128(sbase + SMEM_W + c * W_KC + (warp * 32 + lane) * 16,
               ((SHFL_MASK >> c) & 1) ? convert_unit(r[g & 1], lutv, sc) : convert_unit(r[g & 1], tab));
      }
    });
    asm volatile("fence.proxy.async.shared::cta;" ::: "memory");
    __syncwarp();
    arrive_one(bars + 8 * B_W0);
    if (PUB_AT == 9) {
      publish(1, 1);
      TL(3);
    }
    TL(4);
    if (wg == 1) {
      lds_unit(q, 2);
      emit_unit(convert_unit(q, tab), 2);
    }
    TL(5);
  }

  float acc0[112], acc1[112];
  constexpr uint32_t DA_HI = (1u << 30) | (1024 >> 4), DB_HI = (128 >> 4);
  const uint32_t da0 = ((1u << 16) | ((sbase + SMEM_X) >> 4)) + wg * (XS * X_SLICE >> 4);
  constexpr uint32_t db0 = ((W_KC >> 4) << 16) | ((sbase + SMEM_W) >> 4);
  const uint32_t fullx = bars + 8 * B_FULLX + wg * 64, done = bars + 8 * B_DONE + wg * 64;
  const bool x_issuer = (warp & 3) == 3;

  auto mma = [&](float (&acc)[112], int n, int kb, int k0, int k1) {
    const int wslot = kb == 15 ? 4 : (kb & 3);
    wgmma_fence();
#pragma unroll
    for (int k = k0; k < k1; k++)
      wgmma_m64n224k16(acc, make_desc(da0 + (n % XS) * (X_SLICE >> 4) + k * 2, DA_HI),
                       make_desc(db0 + wslot * (W_STAGE >> 4) + k * (2 * W_KC >> 4), DB_HI), kb != 0 || k != 0);
    wgmma_commit();
  };
  auto release = [&](int n) {
    arrive_one(ring(done, n));
    if (x_issuer) {
      ring_wait(done, n);
      const int m = n + 4;
      if (elect_one())
        load_x(wg, m, m < 2 * NR ? m >> 1 : end_kb((m - 2 * NR) % ENDK), m < 2 * NR ? m & 1 : (m - 2 * NR) / ENDK);
    }
  };
  auto end_slot = [&](int n) {
    wgmma_wait<1>();
    release(n);
  };
  auto slot = [&](float (&acc)[112], auto N) {
    constexpr int n = decltype(N)::value;
    constexpr bool hv = heavy(n), pub = heavy(n - 1);
    ring_wait(fullx, n);
    mma(acc, n, n >> 1, 0, 4);
    if (hv && warp < 7) dequant_lookup(q, lutv);
    end_slot(n);
    if (warp < 7) {
      constexpr int u = unit_at(n);
      if (pub) publish(u - 1, 1);
      if (n == 2) lds_unit(q, 4);
      if (hv) {
        constexpr int un = u + 1 < NKB ? u + 1 : u;
        dequant_finish(q, rb, w_ptr(u), sc, ring(bars + 8 * B_FULLQ, un), un >> 3, qbase + (un & 3) * Q_UNIT);
      }
    } else {
      constexpr int m = w_at(n), u = q_at(n), m_next = w_at(n + 1);
      if (m >= 0 || u >= 0) ring_wait(bars + 8 * B_DONE, n - 1);
      if (m >= 0) {
        ready |= __ballot_sync(0xffffffffu, rb >= FLAG_FULL);
        wait_ready(m);
        asm volatile("fence.proxy.async.global;" ::: "memory");
      }
      if (m_next >= 0) rb = ld_strong(fl);
      if ((m >= 0 || u >= 0 || n == 4 || n == 10) && elect_one()) {
        if (m >= 0)
          load_w(ring(bars + 8 * B_FULLW, m), (m == 15 ? 4 : m & 3) * W_STAGE, m * W_STAGE, W_STAGE);
        if (u >= 0) load_q(u);
        if (u >= 0 && u + 2 < NKB) prefetch_q(u + 2);
        if (n == 4 || n == 10) prefetch_x(n == 4 ? 2 : 3);
      }
    }
  };

  mbar_wait(bars + 8 * B_W0, 0);
  mbar_wait(fullx, 0);
  TL(8); TLG(46);
  mma(acc0, 0, 0, 0, 4);
  mbar_wait(fullx + 8, 0);
  TL(9);
  mma(acc1, 1, 0, 0, 4);
  if (wg == 0) lds_unit(q, 2);
  arrive_one(done);
  if (warp < 7) {
    if (wg == 0) {
      emit_unit(convert_unit(q, lutv, sc), 2);
    } else {
      publish(2, 1);
    }
    lds_unit(q, 3);
    const uint4 w3 = convert_unit(q, lutv, sc);
    if (wg == 0) publish(2, 1);
    st_strong128(w_ptr(3), w3);
    rb = ld_strong(w_ptr(3));
  } else if (warp == 7) {
    if (!Q5_EARLY && elect_one()) load_q(5);
    if (Q6_EARLY) {
      mbar_wait(bars + 8 * B_DONE, 0);
      mbar_wait(done, 0);
      if (elect_one()) load_q(6);
    }
  }
  end_slot(1);
  if (warp == 7) rb = ld_strong(fl);

  static_for<1, NR>([&](auto R) {
    constexpr int r = decltype(R)::value;
    ring_wait(bars + 8 * B_FULLW, r);
    TL(8 + 2 * r);
    slot(acc0, IC<2 * r>{});
    TL(9 + 2 * r);
    slot(acc1, IC<2 * r + 1>{});
  });

  __nv_bfloat16* op = out + (size_t)(xrow + (warp & 3) * 16 + (lane >> 2)) * F_DIM + j * BN + (lane & 3) * 8;
  TL(40); TLG(48);
  if (wg == 1) {
    wgmma_wait<0>();
    release(2 * NR);
    if (warp == 7) {
      wait_ready(14);
      asm volatile("fence.proxy.async.global;" ::: "memory");
      ring_wait(bars + 8 * B_DONE, 2 * NR);
      if (elect_one()) load_w(ring(bars + 8 * B_FULLW, 14), 2 * W_STAGE, 14 * W_STAGE, W_STAGE);
      unsigned old = 0;
      if (lane == 17) old = atomicAdd(fl, 1u);
      if (__shfl_sync(0xffffffffu, old, 17) == NI - 1) *fl = 0;
    }
    bar_sync(1, 256);
  }
#pragma unroll
  for (int e = 0; e < ENDK; e++) {
    ring_wait(bars + 8 * B_FULLW, end_kb(e));
    ring_wait(fullx, 2 * NR + e);
    mma(acc0, 2 * NR + e, end_kb(e), 0, 4);
    if (e == ENDK - 1) bar_arrive(1 + wg, 256);
    wgmma_wait<1>();
    if (e > 0 || wg == 0) release(2 * NR + e);
  }
  wgmma_wait<0>();
  release(2 * NR + ENDK);
  TL(41);
  store_acc(acc0, op, 0, 7);
  TL(42);
  bar_sync(2 - wg, 256);
#pragma unroll
  for (int e = 0; e < ENDK; e++) {
    ring_wait(fullx, 2 * NR + ENDK + e);
    mma(acc1, 2 * NR + ENDK + e, end_kb(e), 0, 4);
  }
  if (wg == 0) bar_arrive(1, 256);
  wgmma_wait<0>();
  TL(43); TLG(47);
  store_acc(acc1, op + 64 * F_DIM, 0, 7);
  TL(44);
}

typedef CUresult (*EncodeTiledFn)(CUtensorMap*, CUtensorMapDataType, cuuint32_t, void*, const cuuint64_t*,
                                  const cuuint64_t*, const cuuint32_t*, const cuuint32_t*, CUtensorMapInterleave,
                                  CUtensorMapSwizzle, CUtensorMapL2promotion, CUtensorMapFloatOOBfill);

}

#define XPROMO CU_TENSOR_MAP_L2_PROMOTION_L2_128B
extern "C" void kernel_launch(void* const* d_in, const int* in_sizes, int n_in, void* d_out, int out_size) {
  const __nv_bfloat16* x = (const __nv_bfloat16*)d_in[0];
  const int* qw = (const int*)d_in[1];
  const __nv_bfloat16* lut = (const __nv_bfloat16*)d_in[2];
  const __nv_bfloat16* scales = (const __nv_bfloat16*)d_in[3];
  __nv_bfloat16* out = (__nv_bfloat16*)d_out;

  static EncodeTiledFn enc = nullptr;
  static uint8_t* p_scr = nullptr;
  if (!enc) {
    void* fn = nullptr;
    cudaDriverEntryPointQueryResult qr;
    cudaGetDriverEntryPoint("cuTensorMapEncodeTiled", &fn, cudaEnableDefault, &qr);
    enc = (EncodeTiledFn)fn;
    void* p = nullptr;
    cudaGetSymbolAddress(&p, g_scratch);
    p_scr = (uint8_t*)(((uintptr_t)p + REGION - 1) & ~(uintptr_t)(REGION - 1));
    cudaFuncSetAttribute(fused_kernel, cudaFuncAttributeMaxDynamicSharedMemorySize, SMEM_TOTAL);
  }
  CUtensorMap tm_x, tm_q;
  cuuint32_t estr[2] = {1, 1};
  {
    cuuint64_t gdim[2] = {(cuuint64_t)D_DIM, (cuuint64_t)S_DIM};
    cuuint64_t gstr[1] = {(cuuint64_t)D_DIM * 2};
    cuuint32_t box[2] = {(cuuint32_t)BK, 64};
    enc(&tm_x, CU_TENSOR_MAP_DATA_TYPE_BFLOAT16, 2, (void*)x, gdim, gstr, box, estr, CU_TENSOR_MAP_INTERLEAVE_NONE,
        CU_TENSOR_MAP_SWIZZLE_128B, XPROMO, CU_TENSOR_MAP_FLOAT_OOB_FILL_NONE);
  }
  {
    cuuint64_t gdim[2] = {(cuuint64_t)F_DIM, (cuuint64_t)D_DIM};
    cuuint64_t gstr[1] = {(cuuint64_t)F_DIM * 4};
    cuuint32_t box[2] = {(cuuint32_t)BN, 8};
    enc(&tm_q, CU_TENSOR_MAP_DATA_TYPE_INT32, 2, (void*)qw, gdim, gstr, box, estr, CU_TENSOR_MAP_INTERLEAVE_NONE,
        CU_TENSOR_MAP_SWIZZLE_NONE, CU_TENSOR_MAP_L2_PROMOTION_NONE, CU_TENSOR_MAP_FLOAT_OOB_FILL_NONE);
  }
  fused_kernel<<<NI * NJ, 256, SMEM_TOTAL, cudaStreamPerThread>>>(qw, lut, scales, out, p_scr, tm_x, tm_q);
}
```

```cpp
#include <cuda_runtime.h>
#include <cuda_bf16.h>
#include <cuda.h>
#include <stdint.h>

namespace {

constexpr int S_DIM = 2048, D_DIM = 1024, F_DIM = 3584;
constexpr int BM = 256, BN = 224, BK = 64;
constexpr int NKB = D_DIM / BK;
constexpr int NJ = F_DIM / BN;
constexpr int NI = S_DIM / BM;
constexpr int WS = 4;
constexpr int XS = 5;
constexpr int ENDK = 5;
constexpr int NR = NKB - ENDK;
constexpr int X_SLICE = 64 * BK * 2;
constexpr int W_STAGE = BN * BK * 2;
constexpr int W_KC = BN * 16;

constexpr int REGION = 512 * 1024;
__device__ uint4 g_scratch[(NJ + 1) * REGION / 16];

__device__ __forceinline__ uint32_t smem_u32(const void* p) { return (uint32_t)__cvta_generic_to_shared(p); }
__device__ __forceinline__ unsigned clk32() {
  unsigned c;
  asm volatile("mov.u32 %0, %%clock;" : "=r"(c)::"memory");
  return c;
}
__device__ __forceinline__ bool elect_one() {
  uint32_t p;
  asm volatile("{\n.reg .pred P;\nelect.sync _|P, 0xffffffff;\nselp.b32 %0, 1, 0, P;\n}" : "=r"(p));
  return p != 0;
}
__device__ __forceinline__ void mbar_init(uint32_t bar, uint32_t cnt) {
  asm volatile("mbarrier.init.shared::cta.b64 [%0], %1;" ::"r"(bar), "r"(cnt) : "memory");
}
__device__ __forceinline__ void mbar_expect_tx(uint32_t bar, uint32_t bytes) {
  asm volatile("mbarrier.arrive.expect_tx.shared::cta.b64 _, [%0], %1;" ::"r"(bar), "r"(bytes) : "memory");
}
__device__ __forceinline__ void mbar_arrive(uint32_t bar) {
  asm volatile("mbarrier.arrive.shared::cta.b64 _, [%0];" ::"r"(bar) : "memory");
}
__device__ __forceinline__ bool mbar_test(uint32_t bar, uint32_t parity) {
  uint32_t ok;
  asm volatile(
      "{\n.reg .pred p;\nmbarrier.test_wait.parity.shared::cta.b64 p, [%1], %2;\nselp.b32 %0, 1, 0, p;\n}\n"
      : "=r"(ok) : "r"(bar), "r"(parity) : "memory");
  return ok != 0;
}
__device__ __forceinline__ void mbar_wait(uint32_t bar, uint32_t parity) {
  asm volatile(
      "{\n.reg .pred p;\n"
      "LAB_WAIT:\n"
      "mbarrier.try_wait.parity.shared::cta.b64 p, [%0], %1;\n"
      "@p bra LAB_DONE;\n"
      "bra LAB_WAIT;\n"
      "LAB_DONE:\n}\n" ::"r"(bar), "r"(parity) : "memory");
}
__device__ __forceinline__ uint32_t ring(uint32_t base, int i) { return base + 8 * (i & 7); }
__device__ __forceinline__ void ring_wait(uint32_t base, int i) { mbar_wait(ring(base, i), (i >> 3) & 1); }
__device__ __forceinline__ void tma_load_2d(uint32_t dst, const CUtensorMap* tm, int c0, int c1, uint32_t bar) {
  asm volatile(
      "cp.async.bulk.tensor.2d.shared::cluster.global.mbarrier::complete_tx::bytes [%0], [%1, {%3, %4}], [%2];"
      ::"r"(dst), "l"(tm), "r"(bar), "r"(c0), "r"(c1) : "memory");
}
__device__ __forceinline__ void tma_prefetch_2d(const CUtensorMap* tm, int c0, int c1) {
  asm volatile("cp.async.bulk.prefetch.tensor.2d.L2.global [%0, {%1, %2}];" ::"l"(tm), "r"(c0), "r"(c1) : "memory");
}
__device__ __forceinline__ void bulk_load(uint32_t dst, const void* src, uint32_t bytes, uint32_t bar) {
  asm volatile(
      "cp.async.bulk.shared::cluster.global.mbarrier::complete_tx::bytes [%0], [%1], %2, [%3];"
      ::"r"(dst), "l"(src), "r"(bytes), "r"(bar) : "memory");
}
__device__ __forceinline__ int ldg_stream(const int* p) {
  int v;
  asm volatile("ld.global.L1::no_allocate.b32 %0, [%1];" : "=r"(v) : "l"(p) : "memory");
  return v;
}
__device__ __forceinline__ void cp_async16(uint32_t dst, const void* src) {
  asm volatile("cp.async.cg.shared.global [%0], [%1], 16;" ::"r"(dst), "l"(src) : "memory");
}
__device__ __forceinline__ void cp_async_commit() { asm volatile("cp.async.commit_group;" ::: "memory"); }
template <int N>
__device__ __forceinline__ void cp_async_wait() { asm volatile("cp.async.wait_group %0;" ::"n"(N) : "memory"); }
__device__ __forceinline__ uint32_t ldg_u16(const void* p) {
  uint32_t v;
  asm volatile("ld.global.u16 %0, [%1];" : "=r"(v) : "l"(p) : "memory");
  return v;
}
__device__ __forceinline__ int lds32(uint32_t addr) {
  int v;
  asm volatile("ld.shared.b32 %0, [%1];" : "=r"(v) : "r"(addr) : "memory");
  return v;
}
__device__ __forceinline__ void sts128(uint32_t addr, uint4 v) {
  asm volatile("st.shared.v4.u32 [%0], {%1, %2, %3, %4};" ::"r"(addr), "r"(v.x), "r"(v.y), "r"(v.z), "r"(v.w) : "memory");
}
__device__ __forceinline__ uint64_t make_desc(uint32_t lo, uint32_t hi) {
  uint64_t d;
  asm("mov.b64 %0, {%1, %2};" : "=l"(d) : "r"(lo), "r"(hi));
  return d;
}
__device__ __forceinline__ unsigned ld_strong(const void* p) {
  unsigned v;
  asm volatile("ld.relaxed.gpu.global.u32 %0, [%1];" : "=r"(v) : "l"(p) : "memory");
  return v;
}
__device__ __forceinline__ void st_strong128(void* p, uint4 v) {
  asm volatile("st.relaxed.gpu.global.v4.u32 [%0], {%1, %2, %3, %4};" ::"l"(p), "r"(v.x), "r"(v.y), "r"(v.z), "r"(v.w)
               : "memory");
}
__device__ __forceinline__ void wgmma_fence() { asm volatile("wgmma.fence.sync.aligned;" ::: "memory"); }
__device__ __forceinline__ void wgmma_commit() { asm volatile("wgmma.commit_group.sync.aligned;" ::: "memory"); }
template <int N>
__device__ __forceinline__ void wgmma_wait() { asm volatile("wgmma.wait_group.sync.aligned %0;" ::"n"(N) : "memory"); }
__device__ __forceinline__ void bar_sync(int id, int n) { asm volatile("bar.sync %0, %1;" ::"r"(id), "r"(n) : "memory"); }
__device__ __forceinline__ void bar_arrive(int id, int n) { asm volatile("bar.arrive %0, %1;" ::"r"(id), "r"(n) : "memory"); }

__device__ __forceinline__ void wgmma_m64n224k16(float (&d)[112], uint64_t da, uint64_t db, int scale_d) {
  asm volatile(
    "{\n.reg .pred p;\nsetp.ne.b32 p, %114, 0;\n"
    "wgmma.mma_async.sync.aligned.m64n224k16.f32.bf16.bf16 "
    "{%0, %1, %2, %3, %4, %5, %6, %7, %8, %9, %10, %11, %12, %13, %14, %15, "
    "%16, %17, %18, %19, %20, %21, %22, %23, %24, %25, %26, %27, %28, %29, %30, %31, "
    "%32, %33, %34, %35, %36, %37, %38, %39, %40, %41, %42, %43, %44, %45, %46, %47, "
    "%48, %49, %50, %51, %52, %53, %54, %55, %56, %57, %58, %59, %60, %61, %62, %63, "
    "%64, %65, %66, %67, %68, %69, %70, %71, %72, %73, %74, %75, %76, %77, %78, %79, "
    "%80, %81, %82, %83, %84, %85, %86, %87, %88, %89, %90, %91, %92, %93, %94, %95, "
    "%96, %97, %98, %99, %100, %101, %102, %103, %104, %105, %106, %107, %108, %109, %110, %111}, "
    "%112, %113, p, 1, 1, 0, 0;\n}\n"
    : "+f"(d[0]), "+f"(d[1]), "+f"(d[2]), "+f"(d[3]), "+f"(d[4]), "+f"(d[5]), "+f"(d[6]), "+f"(d[7]),
      "+f"(d[8]), "+f"(d[9]), "+f"(d[10]), "+f"(d[11]), "+f"(d[12]), "+f"(d[13]), "+f"(d[14]), "+f"(d[15]),
      "+f"(d[16]), "+f"(d[17]), "+f"(d[18]), "+f"(d[19]), "+f"(d[20]), "+f"(d[21]), "+f"(d[22]), "+f"(d[23]),
      "+f"(d[24]), "+f"(d[25]), "+f"(d[26]), "+f"(d[27]), "+f"(d[28]), "+f"(d[29]), "+f"(d[30]), "+f"(d[31]),
      "+f"(d[32]), "+f"(d[33]), "+f"(d[34]), "+f"(d[35]), "+f"(d[36]), "+f"(d[37]), "+f"(d[38]), "+f"(d[39]),
      "+f"(d[40]), "+f"(d[41]), "+f"(d[42]), "+f"(d[43]), "+f"(d[44]), "+f"(d[45]), "+f"(d[46]), "+f"(d[47]),
      "+f"(d[48]), "+f"(d[49]), "+f"(d[50]), "+f"(d[51]), "+f"(d[52]), "+f"(d[53]), "+f"(d[54]), "+f"(d[55]),
      "+f"(d[56]), "+f"(d[57]), "+f"(d[58]), "+f"(d[59]), "+f"(d[60]), "+f"(d[61]), "+f"(d[62]), "+f"(d[63]),
      "+f"(d[64]), "+f"(d[65]), "+f"(d[66]), "+f"(d[67]), "+f"(d[68]), "+f"(d[69]), "+f"(d[70]), "+f"(d[71]),
      "+f"(d[72]), "+f"(d[73]), "+f"(d[74]), "+f"(d[75]), "+f"(d[76]), "+f"(d[77]), "+f"(d[78]), "+f"(d[79]),
      "+f"(d[80]), "+f"(d[81]), "+f"(d[82]), "+f"(d[83]), "+f"(d[84]), "+f"(d[85]), "+f"(d[86]), "+f"(d[87]),
      "+f"(d[88]), "+f"(d[89]), "+f"(d[90]), "+f"(d[91]), "+f"(d[92]), "+f"(d[93]), "+f"(d[94]), "+f"(d[95]),
      "+f"(d[96]), "+f"(d[97]), "+f"(d[98]), "+f"(d[99]), "+f"(d[100]), "+f"(d[101]), "+f"(d[102]), "+f"(d[103]),
      "+f"(d[104]), "+f"(d[105]), "+f"(d[106]), "+f"(d[107]), "+f"(d[108]), "+f"(d[109]), "+f"(d[110]), "+f"(d[111])
    : "l"(da), "l"(db), "r"(scale_d));
}
template <int O>
__device__ __forceinline__ void wgmma_rs_m64n96k16(float (&d)[112], const uint32_t (&a)[4], uint64_t db) {
  asm volatile(
    "wgmma.mma_async.sync.aligned.m64n96k16.f32.bf16.bf16 "
    "{%0, %1, %2, %3, %4, %5, %6, %7, %8, %9, %10, %11, %12, %13, %14, %15, "
    "%16, %17, %18, %19, %20, %21, %22, %23, %24, %25, %26, %27, %28, %29, %30, %31, "
    "%32, %33, %34, %35, %36, %37, %38, %39, %40, %41, %42, %43, %44, %45, %46, %47}, "
    "{%48, %49, %50, %51}, %52, 1, 1, 1, 0;\n"
    : "+f"(d[O + 0]), "+f"(d[O + 1]), "+f"(d[O + 2]), "+f"(d[O + 3]),
      "+f"(d[O + 4]), "+f"(d[O + 5]), "+f"(d[O + 6]), "+f"(d[O + 7]),
      "+f"(d[O + 8]), "+f"(d[O + 9]), "+f"(d[O + 10]), "+f"(d[O + 11]),
      "+f"(d[O + 12]), "+f"(d[O + 13]), "+f"(d[O + 14]), "+f"(d[O + 15]),
      "+f"(d[O + 16]), "+f"(d[O + 17]), "+f"(d[O + 18]), "+f"(d[O + 19]),
      "+f"(d[O + 20]), "+f"(d[O + 21]), "+f"(d[O + 22]), "+f"(d[O + 23]),
      "+f"(d[O + 24]), "+f"(d[O + 25]), "+f"(d[O + 26]), "+f"(d[O + 27]),
      "+f"(d[O + 28]), "+f"(d[O + 29]), "+f"(d[O + 30]), "+f"(d[O + 31]),
      "+f"(d[O + 32]), "+f"(d[O + 33]), "+f"(d[O + 34]), "+f"(d[O + 35]),
      "+f"(d[O + 36]), "+f"(d[O + 37]), "+f"(d[O + 38]), "+f"(d[O + 39]),
      "+f"(d[O + 40]), "+f"(d[O + 41]), "+f"(d[O + 42]), "+f"(d[O + 43]),
      "+f"(d[O + 44]), "+f"(d[O + 45]), "+f"(d[O + 46]), "+f"(d[O + 47])
    : "r"(a[0]), "r"(a[1]), "r"(a[2]), "r"(a[3]), "l"(db));
}
template <int O>
__device__ __forceinline__ void wgmma_rs_m64n64k16(float (&d)[112], const uint32_t (&a)[4], uint64_t db) {
  asm volatile(
    "wgmma.mma_async.sync.aligned.m64n64k16.f32.bf16.bf16 "
    "{%0, %1, %2, %3, %4, %5, %6, %7, %8, %9, %10, %11, %12, %13, %14, %15, "
    "%16, %17, %18, %19, %20, %21, %22, %23, %24, %25, %26, %27, %28, %29, %30, %31}, "
    "{%32, %33, %34, %35}, %36, 1, 1, 1, 0;\n"
    : "+f"(d[O + 0]), "+f"(d[O + 1]), "+f"(d[O + 2]), "+f"(d[O + 3]),
      "+f"(d[O + 4]), "+f"(d[O + 5]), "+f"(d[O + 6]), "+f"(d[O + 7]),
      "+f"(d[O + 8]), "+f"(d[O + 9]), "+f"(d[O + 10]), "+f"(d[O + 11]),
      "+f"(d[O + 12]), "+f"(d[O + 13]), "+f"(d[O + 14]), "+f"(d[O + 15]),
      "+f"(d[O + 16]), "+f"(d[O + 17]), "+f"(d[O + 18]), "+f"(d[O + 19]),
      "+f"(d[O + 20]), "+f"(d[O + 21]), "+f"(d[O + 22]), "+f"(d[O + 23]),
      "+f"(d[O + 24]), "+f"(d[O + 25]), "+f"(d[O + 26]), "+f"(d[O + 27]),
      "+f"(d[O + 28]), "+f"(d[O + 29]), "+f"(d[O + 30]), "+f"(d[O + 31])
    : "r"(a[0]), "r"(a[1]), "r"(a[2]), "r"(a[3]), "l"(db));
}

__device__ __forceinline__ uint32_t pack_bf16(float lo, float hi) {
  uint32_t r;
  asm("cvt.rn.bf16x2.f32 %0, %1, %2;" : "=r"(r) : "f"(hi), "f"(lo));
  return r;
}

__device__ __forceinline__ int perm32(int n) { return (n & ~30) | ((n & 6) << 2) | ((n >> 2) & 6); }

constexpr int SMEM_X = 0;
constexpr int SMEM_W = 2 * XS * X_SLICE;
constexpr int SMEM_Q = SMEM_W + WS * W_STAGE;
constexpr int Q_UNIT = 8 * BN * 4;
constexpr int SMEM_BAR = SMEM_Q + W_STAGE;
constexpr int B_FULLW = 0, B_FULLQ = 8, B_FULLX = 16, B_DONE = 32, B_W0 = 48, B_RAW0 = 49, B_COUNT = 51;
constexpr int SMEM_TL = SMEM_BAR + 512;
constexpr int SMEM_TOTAL = SMEM_TL + 2048;
constexpr int W_OFF = 128;
constexpr unsigned FLAG_FULL = NI * 7;

#define TL(i)
#define TLG(i)

__device__ __forceinline__ void store_acc(const float (&a)[112], __nv_bfloat16* p, int J0, int J1) {
#pragma unroll
  for (int J = J0; J < J1; J++) {
    uint4 v0, v1;
    v0.x = pack_bf16(a[16 * J + 0], a[16 * J + 1]);
    v0.y = pack_bf16(a[16 * J + 4], a[16 * J + 5]);
    v0.z = pack_bf16(a[16 * J + 8], a[16 * J + 9]);
    v0.w = pack_bf16(a[16 * J + 12], a[16 * J + 13]);
    v1.x = pack_bf16(a[16 * J + 2], a[16 * J + 3]);
    v1.y = pack_bf16(a[16 * J + 6], a[16 * J + 7]);
    v1.z = pack_bf16(a[16 * J + 10], a[16 * J + 11]);
    v1.w = pack_bf16(a[16 * J + 14], a[16 * J + 15]);
    *reinterpret_cast<uint4*>(p + 32 * J) = v0;
    *reinterpret_cast<uint4*>(p + 8 * F_DIM + 32 * J) = v1;
  }
}

__device__ __forceinline__ void load_unit(int (&q)[8], const int* p) {
#pragma unroll
  for (int i = 0; i < 8; i++) q[i] = ldg_stream(p + i * F_DIM);
}
__device__ __forceinline__ uint4 convert_unit(const int (&q)[8], float lutv, float sc) {
  float v[8];
#pragma unroll
  for (int i = 0; i < 8; i++) v[i] = __shfl_sync(0xffffffffu, lutv, q[i]) * sc;
  uint4 o;
  o.x = pack_bf16(v[0], v[1]);
  o.y = pack_bf16(v[2], v[3]);
  o.z = pack_bf16(v[4], v[5]);
  o.w = pack_bf16(v[6], v[7]);
  return o;
}

struct Table {
  uint32_t lo[4], hi[4];
};
__device__ __forceinline__ uint32_t prmt(uint32_t a, uint32_t b, uint32_t s) {
  uint32_t r;
  asm("prmt.b32 %0, %1, %2, %3;" : "=r"(r) : "r"(a), "r"(b), "r"(s));
  return r;
}
__device__ __forceinline__ Table make_table(float lutv, float sc) {
  Table t;
#pragma unroll
  for (int i = 0; i < 4; i++) {
    const uint32_t a = pack_bf16(__shfl_sync(0xffffffffu, lutv, 4 * i) * sc, __shfl_sync(0xffffffffu, lutv, 4 * i + 1) * sc);
    const uint32_t b =
        pack_bf16(__shfl_sync(0xffffffffu, lutv, 4 * i + 2) * sc, __shfl_sync(0xffffffffu, lutv, 4 * i + 3) * sc);
    t.lo[i] = prmt(a, b, 0x6420);
    t.hi[i] = prmt(a, b, 0x7531);
  }
  return t;
}
__device__ __forceinline__ uint4 convert_unit(const int (&q)[8], const Table& t) {
  const uint32_t all = ((q[7] * 16 + q[6]) * 256 + (q[5] * 16 + q[4])) * 65536 + ((q[3] * 16 + q[2]) * 256 + (q[1] * 16 + q[0]));
  const uint32_t s7 = all & 0x77777777u;
  const uint32_t s2 = ((all >> 1) & 0x44444444u) | 0x32103210u;
  uint32_t o[4];
#pragma unroll
  for (int h = 0; h < 2; h++) {
    const uint32_t a = h ? s7 >> 16 : s7, b = h ? s2 >> 16 : s2;
    const uint32_t lo = prmt(prmt(t.lo[0], t.lo[1], a), prmt(t.lo[2], t.lo[3], a), b);
    const uint32_t hi = prmt(prmt(t.hi[0], t.hi[1], a), prmt(t.hi[2], t.hi[3], a), b);
    o[2 * h] = prmt(lo, hi, 0x5140);
    o[2 * h + 1] = prmt(lo, hi, 0x7362);
  }
  return make_uint4(o[0], o[1], o[2], o[3]);
}

__device__ __forceinline__ void dequant_lookup(int (&q)[8], float lutv) {
  asm volatile(
      "shfl.sync.idx.b32 %0, %8, %0, 31, 0xffffffff;\n"
      "shfl.sync.idx.b32 %1, %8, %1, 31, 0xffffffff;\n"
      "shfl.sync.idx.b32 %2, %8, %2, 31, 0xffffffff;\n"
      "shfl.sync.idx.b32 %3, %8, %3, 31, 0xffffffff;\n"
      "shfl.sync.idx.b32 %4, %8, %4, 31, 0xffffffff;\n"
      "shfl.sync.idx.b32 %5, %8, %5, 31, 0xffffffff;\n"
      "shfl.sync.idx.b32 %6, %8, %6, 31, 0xffffffff;\n"
      "shfl.sync.idx.b32 %7, %8, %7, 31, 0xffffffff;\n"
      : "+r"(q[0]), "+r"(q[1]), "+r"(q[2]), "+r"(q[3]), "+r"(q[4]), "+r"(q[5]), "+r"(q[6]), "+r"(q[7])
      : "r"(__float_as_int(lutv)));
}
__device__ __forceinline__ void dequant_finish(int (&q)[8], unsigned& rb, uint4* wp, float sc, uint32_t qbar,
                                               uint32_t qpar, uint32_t qaddr) {
  asm volatile(
      "{\n.reg .pred W;\n.reg .b32 o0, o1, o2, o3;\n"
      "DQ_WAIT:\n"
      "mbarrier.try_wait.parity.shared::cta.b64 W, [%11], %13;\n"
      "@!W bra DQ_WAIT;\n"
      "mul.rn.f32 %0, %0, %10;\nmul.rn.f32 %1, %1, %10;\nmul.rn.f32 %2, %2, %10;\nmul.rn.f32 %3, %3, %10;\n"
      "mul.rn.f32 %4, %4, %10;\nmul.rn.f32 %5, %5, %10;\nmul.rn.f32 %6, %6, %10;\nmul.rn.f32 %7, %7, %10;\n"
      "cvt.rn.bf16x2.f32 o0, %1, %0;\ncvt.rn.bf16x2.f32 o1, %3, %2;\n"
      "cvt.rn.bf16x2.f32 o2, %5, %4;\ncvt.rn.bf16x2.f32 o3, %7, %6;\n"
      "ld.volatile.shared.b32 %0, [%12];\nld.volatile.shared.b32 %1, [%12+896];\n"
      "ld.volatile.shared.b32 %2, [%12+1792];\nld.volatile.shared.b32 %3, [%12+2688];\n"
      "ld.volatile.shared.b32 %4, [%12+3584];\nld.volatile.shared.b32 %5, [%12+4480];\n"
      "ld.volatile.shared.b32 %6, [%12+5376];\nld.volatile.shared.b32 %7, [%12+6272];\n"
      "st.relaxed.gpu.global.v4.u32 [%9], {o0, o1, o2, o3};\n"
      "ld.relaxed.gpu.global.u32 %8, [%9];\n}\n"
      : "+r"(q[0]), "+r"(q[1]), "+r"(q[2]), "+r"(q[3]), "+r"(q[4]), "+r"(q[5]), "+r"(q[6]), "+r"(q[7]), "=r"(rb)
      : "l"(wp), "r"(__float_as_int(sc)), "r"(qbar), "r"(qaddr), "r"(qpar)
      : "memory");
}

#define Q6_EARLY 0
constexpr int PU = 3;
#define HEAVY 0x3BBBAu
__host__ __device__ constexpr int popc(unsigned v) { return v ? (v & 1) + popc(v >> 1) : 0; }
__host__ __device__ constexpr bool heavy(int n) { return n >= 0 && ((HEAVY >> n) & 1); }
__host__ __device__ constexpr int unit_at(int n) { return PU + popc(HEAVY & ((1u << n) - 1)); }
__host__ __device__ constexpr int emit_slot(int u) {
  if (u < PU) return -1;
  for (int n = 0; n < 24; n++)
    if (heavy(n) && unit_at(n) == u) return n;
  return 99;
}
__host__ __device__ constexpr int end_kb(int e) { return e < 3 ? NR + e : NR + 7 - e; }
__host__ __device__ constexpr int cmax(int a, int b) { return a > b ? a : b; }
__host__ __device__ constexpr int w_slot(int m) {
  return m == 15 ? cmax(emit_slot(15) + 3, 20) : cmax(2 * m - 5, emit_slot(m) + 3);
}
__host__ __device__ constexpr int q_slot(int u) {
  return u <= 5 + Q6_EARLY ? 1 : cmax(q_slot(u - 1) + 1, u < 8 ? 2 : u == 8 ? 4 : emit_slot(u - 5) + 2);
}
__host__ __device__ constexpr int w_at(int n) {
  for (int m = 2; m < NKB; m++)
    if (w_slot(m) == n) return m;
  return -1;
}
__host__ __device__ constexpr int q_at(int n) {
  for (int u = 5; u < NKB; u++)
    if (q_slot(u) == n) return u;
  return -1;
}
constexpr bool schedule_ok() {
  if (popc(HEAVY) != NKB - PU || (HEAVY & 7) != 2 || (HEAVY >> 20)) return false;
  for (int m = 2; m < NKB; m++) {
    if (w_at(w_slot(m)) != m || (m != 14 && w_slot(m) >= 2 * NR)) return false;
    if (m < NR && w_slot(m) > 2 * m - 2) return false;
  }
  for (int u = 5; u < NKB; u++)
    if (q_slot(u) + 2 > emit_slot(u - 1)) return false;
  return true;
}
static_assert(schedule_ok(), "bad schedule");
template <int V>
struct IC {
  static constexpr int value = V;
};
template <int I, int N, class F>
__device__ __forceinline__ void static_for(F&& f) {
  if constexpr (I < N) {
    f(IC<I>{});
    static_for<I + 1, N>(f);
  }
}

#define SHFL_MASK 0
#define RSPLIT 5
#define PACE_X 1100
#define PACE_Q2 1600
#define PACE_Q3 2100
#define WAIT_MODE 0
#define Q2_FIRST 0
#define X3_LATE 0
#define Q5_EARLY 0
#define SPLIT_END 1
#define ST_GAP 200
#define LD_SHIFT 0
#define LEAD 8
#define W0_N 5
#define W0_GAP 1
#define W0_LATE 2100
#define NCP 3
#define U1_POS 0
#define PACE_L 0
#define STAG_L 70
#define PACE_INIT 650
#define PUB_AT 6
#define PF_X 0
#define PF_Q 0

constexpr uint32_t sbase = 1024;

__global__ void __launch_bounds__(256, 1)
fused_kernel(const int* __restrict__ qw, const __nv_bfloat16* __restrict__ lut,
             const __nv_bfloat16* __restrict__ scales, __nv_bfloat16* __restrict__ out, uint8_t* scratch,
             const __grid_constant__ CUtensorMap tm_x, const __grid_constant__ CUtensorMap tm_q) {
  extern __shared__ __align__(1024) uint8_t smem_raw[];
  constexpr uint32_t bars = sbase + SMEM_BAR;
  const int j = blockIdx.x >> 3, it = blockIdx.x & 7;
  constexpr uint32_t raw0 = sbase + SMEM_W + 2 * W_STAGE;
  uint32_t lut_raw = 0, sc_raw = 0;
  if (threadIdx.x < 224) {
    const unsigned t = threadIdx.x, row0 = (t >> 3) & 3, col = (t & ~31u) + (t & 7) * 4;
    const int* src = qw + (row0 * F_DIM + j * BN + col);
    const uint32_t dst = row0 * (BN * 4) + col * 4;
    lut_raw = ldg_u16(lut + (t & 15));
    sc_raw = ldg_u16(scales + (j * BN + perm32(t)));
    __syncwarp();
#pragma unroll
    for (int g = 0; g < NCP + 1; g++) {
      const unsigned row = g == 0 ? BK + it * 8 : (g - 1) * 8;
      const uint32_t d = dst + (g == 0 ? sbase + SMEM_Q + Q_UNIT : raw0 + (g - 1) * Q_UNIT);
      cp_async16(d, src + row * F_DIM);
      cp_async16(d + 4 * BN * 4, src + (row + 4) * F_DIM);
      cp_async_commit();
    }
  }
  const int warp = __shfl_sync(0xffffffffu, threadIdx.x >> 5, 0);
  const int wg = warp >> 2;
  int lane;
  asm volatile("mov.u32 %0, %%laneid;" : "=r"(lane));
  const unsigned t_start = clk32();
  auto pace = [&](unsigned t) {
    while (__any_sync(0xffffffffu, clk32() - t_start < t)) {}
  };
  TL(0); TLG(1);

  uint8_t* const region = scratch + (size_t)j * REGION;
  uint8_t* const wp = region + W_OFF + it * W_KC + (warp * 32 + lane) * 16;
  unsigned* const fl = reinterpret_cast<unsigned*>(region) + lane;
  float lutv, sc;
  unsigned rb;
  const int xrow = it * BM + wg * 128;

  auto w_ptr = [&](int u) { return reinterpret_cast<uint4*>(wp + u * W_STAGE); };
  auto emit_unit = [&](uint4 w, int u) {
    st_strong128(w_ptr(u), w);
    rb = ld_strong(w_ptr(u));
  };
  auto publish = [&](int u, unsigned inc) {
    asm volatile(
        "{\n.reg .pred P, Q;\n"
        "setp.ne.u32 P, %1, 0xffffffff;\n"
        "vote.sync.all.pred P, P, 0xffffffff;\n"
        "setp.eq.and.s32 Q, %2, %3, P;\n"
        "@Q red.relaxed.gpu.global.add.u32 [%0], %4;\n}"
        ::"l"(fl), "r"(rb), "r"(lane), "r"(u), "r"(inc) : "memory");
  };
  auto load_x = [&](int g, int n, int kb, int half) {
    const uint32_t bar = ring(bars + 8 * B_FULLX, n) + g * 64;
    mbar_expect_tx(bar, X_SLICE);
    tma_load_2d(sbase + SMEM_X + (n % XS) * X_SLICE + g * (XS * X_SLICE), &tm_x, kb * BK,
                it * BM + g * 128 + half * 64, bar);
  };
  auto load_q = [&](int u) {
    const uint32_t bar = ring(bars + 8 * B_FULLQ, u);
    mbar_expect_tx(bar, Q_UNIT);
    tma_load_2d(sbase + SMEM_Q + (u & 3) * Q_UNIT, &tm_q, j * BN, u * BK + it * 8, bar);
  };
  auto prefetch_x = [&](int g) {
    if (PF_X) tma_prefetch_2d(&tm_x, (4 * g + (j >> 2)) * BK, it * BM + (j & 3) * 64);
  };
  auto prefetch_q = [&](int u) {
    if (PF_Q) tma_prefetch_2d(&tm_q, j * BN, u * BK + it * 8);
  };

  unsigned ready = 0;
  auto load_w = [&](uint32_t bar, int dst, int src, int bytes) {
    mbar_expect_tx(bar, bytes);
    bulk_load(sbase + SMEM_W + dst, region + W_OFF + src, bytes, bar);
  };
  auto poll = [&]() { ready |= __ballot_sync(0xffffffffu, ld_strong(fl) >= FLAG_FULL); };
  auto wait_ready = [&](int kb) {
    int spins = 0;
    while (!((ready >> kb) & 1)) {
      poll();
      if (++spins > (1 << 22)) __trap();
    }
  };

  uint32_t qbase;
  asm volatile("mov.u32 %0, %1;" : "=r"(qbase) : "r"(sbase + SMEM_Q + warp * 128 + perm32(lane) * 4));
  auto lds_unit = [&](int (&q)[8], int u) {
    ring_wait(bars + 8 * B_FULLQ, u);
#pragma unroll
    for (int i = 0; i < 8; i++) q[i] = lds32(qbase + (u & 3) * Q_UNIT + i * (BN * 4));
  };
  auto arrive_one = [&](uint32_t bar) {
    asm volatile("{\n.reg .pred P;\nelect.sync _|P, 0xffffffff;\n@P mbarrier.arrive.shared::cta.b64 _, [%0];\n}"
                 ::"r"(bar) : "memory");
  };

  int q[8];
  if (warp == 7) {
    if (elect_one()) {
      mbar_init(bars + 8 * B_RAW0, RSPLIT - NCP);
      if (RSPLIT < 8) mbar_init(bars + 8 * B_RAW0 + 8, 8 - RSPLIT);
      asm volatile("fence.mbarrier_init.release.cluster;" ::: "memory");
    }
    __syncwarp();
    bar_arrive(4, (9 - NCP) * 32);
    if (elect_one()) {
      asm volatile("prefetch.tensormap [%0];" ::"l"(&tm_x) : "memory");
      asm volatile("prefetch.tensormap [%0];" ::"l"(&tm_q) : "memory");
    }
    TL(5);
    pace(PACE_INIT);
    if (elect_one()) {
#pragma unroll
      for (int i = 0; i < B_RAW0; i++) mbar_init(bars + 8 * i, i == B_W0 ? 7 : i >= B_DONE ? 4 : 1);
      asm volatile("fence.mbarrier_init.release.cluster;" ::: "memory");
    }
    __syncwarp();
    rb = ld_strong(fl);
    bar_arrive(0, 256);
    TL(4);
    lutv = 0.f;
    sc = 0.f;
    if (smem_u32(smem_raw) != sbase) __trap();
    if (elect_one()) {
      mbar_arrive(bars + 8 * B_FULLW);
      mbar_arrive(bars + 8 * B_FULLQ);
      mbar_arrive(bars + 8 * B_FULLQ + 8);
    }
    if (PACE_X) pace(PACE_X);
    if (elect_one()) {
      if (Q2_FIRST) load_q(2);
      load_x(0, 0, 0, 0); load_x(1, 0, 0, 0); load_x(0, 1, 0, 1); load_x(1, 1, 0, 1);
    }
    if (!Q2_FIRST) {
      pace(PACE_Q2);
      if (elect_one()) load_q(2);
    }
    if (WAIT_MODE == 0) pace(PACE_Q3);
    if (WAIT_MODE == 1) mbar_wait(bars + 8 * B_FULLQ + 16, 0);
    if (WAIT_MODE == 2) mbar_wait(bars + 8 * B_FULLX, 0);
    ready = __ballot_sync(0xffffffffu, rb >= FLAG_FULL);
    rb = ld_strong(fl);
    if (elect_one()) {
      load_q(3);
      load_x(0, 2, 1, 0); load_x(1, 2, 1, 0);
      if (!X3_LATE) { load_x(0, 3, 1, 1); load_x(1, 3, 1, 1); }
    }
    ready |= __ballot_sync(0xffffffffu, rb >= FLAG_FULL);
    wait_ready(1);
    asm volatile("fence.proxy.async.global;" ::: "memory");
    if (elect_one()) {
      load_w(bars + 8 * B_FULLW + 8, W_STAGE, W_STAGE, W_STAGE);
      if (X3_LATE) { load_x(0, 3, 1, 1); load_x(1, 3, 1, 1); }
      load_q(4);
      load_x(0, 4, 2, 0); load_x(1, 4, 2, 0);
      if (Q5_EARLY) load_q(5);
    }
    TL(2);
    TL(3);
  } else {
    if (warp + NCP < 8) {
      bar_sync(4, (9 - NCP) * 32);
      pace(PACE_L + warp * STAG_L);
      if (elect_one()) {
        const int c = warp + NCP;
        const uint32_t bar = bars + 8 * B_RAW0 + (c < RSPLIT ? 0 : 8);
        mbar_expect_tx(bar, Q_UNIT);
#pragma unroll
        for (int i = 0; i < 8; i++)
          bulk_load(raw0 + (c * 8 + i) * (BN * 4), qw + (size_t)(c * 8 + i) * F_DIM + j * BN, BN * 4, bar);
      }
    }
    bar_sync(0, 256);
    pace(200);
    asm volatile("shl.b32 %0, %0, 16;\nshl.b32 %1, %1, 16;" : "+r"(lut_raw), "+r"(sc_raw));
    lutv = __uint_as_float(lut_raw);
    sc = __uint_as_float(sc_raw);
    const Table tab = make_table(lutv, sc);
    if (__any_sync(0xffffffffu, lane > 31 && (tab.lo[0] ^ tab.lo[1] ^ tab.lo[2] ^ tab.lo[3] ^ tab.hi[0] ^ tab.hi[1] ^
                                              tab.hi[2] ^ tab.hi[3]) == 1))
      __trap();
    int r[2][8];
    auto lds_group = [&](auto G) {
      constexpr int g = decltype(G)::value, c = g < U1_POS ? g : g - 1;
      if constexpr (g <= NCP) {
        cp_async_wait<NCP - g>();
        __syncwarp();
      } else {
        if (c == NCP) mbar_wait(bars + 8 * B_RAW0, 0);
        if (c == RSPLIT) mbar_wait(bars + 8 * B_RAW0 + 8, 0);
      }
#pragma unroll
      for (int i = 0; i < 8; i++)
        r[g & 1][i] = lds32(qbase + (g == U1_POS ? Q_UNIT : raw0 - sbase - SMEM_Q + c * Q_UNIT) + i * (BN * 4));
    };
    lds_group(IC<0>{});
    TL(6);
    static_for<0, 9>([&](auto G) {
      constexpr int g = decltype(G)::value, c = g < U1_POS ? g : g - 1;
      if (g == PUB_AT) {
        publish(1, 1);
        TL(3);
      }
      if (g == U1_POS) {
        emit_unit(convert_unit(r[g & 1], tab), 1);
        __syncwarp();
        TL(2);
        if constexpr (g < 8) lds_group(IC<g + 1>{});
      } else {
        if constexpr (g < 8) lds_group(IC<g + 1>{});
        sts128(sbase + SMEM_W + c * W_KC + (warp * 32 + lane) * 16,
               ((SHFL_MASK >> c) & 1) ? convert_unit(r[g & 1], lutv, sc) : convert_unit(r[g & 1], tab));
      }
    });
    asm volatile("fence.proxy.async.shared::cta;" ::: "memory");
    __syncwarp();
    arrive_one(bars + 8 * B_W0);
    if (PUB_AT == 9) {
      publish(1, 1);
      TL(3);
    }
    TL(4);
    if (wg == 1) {
      lds_unit(q, 2);
      emit_unit(convert_unit(q, tab), 2);
    }
    TL(5);
  }

  float acc0[112], acc1[112];
  constexpr uint32_t DA_HI = (1u << 30) | (1024 >> 4), DB_HI = (128 >> 4);
  const uint32_t da0 = ((1u << 16) | ((sbase + SMEM_X) >> 4)) + wg * (XS * X_SLICE >> 4);
  constexpr uint32_t db0 = ((W_KC >> 4) << 16) | ((sbase + SMEM_W) >> 4);
  const uint32_t fullx = bars + 8 * B_FULLX + wg * 64, done = bars + 8 * B_DONE + wg * 64;
  const bool x_issuer = (warp & 3) == 3;

  auto mma = [&](float (&acc)[112], int n, int kb, int k0, int k1) {
    const int wslot = kb == 15 ? 4 : (kb & 3);
    wgmma_fence();
#pragma unroll
    for (int k = k0; k < k1; k++)
      wgmma_m64n224k16(acc, make_desc(da0 + (n % XS) * (X_SLICE >> 4) + k * 2, DA_HI),
                       make_desc(db0 + wslot * (W_STAGE >> 4) + k * (2 * W_KC >> 4), DB_HI), kb != 0 || k != 0);
    wgmma_commit();
  };
  auto release = [&](int n) {
    arrive_one(ring(done, n));
    if (x_issuer) {
      ring_wait(done, n);
      const int m = n + 4;
      if (elect_one())
        load_x(wg, m, m < 2 * NR ? m >> 1 : end_kb((m - 2 * NR) % ENDK), m < 2 * NR ? m & 1 : (m - 2 * NR) / ENDK);
    }
  };
  auto end_slot = [&](int n) {
    wgmma_wait<1>();
    release(n);
  };
  auto slot = [&](float (&acc)[112], auto N) {
    constexpr int n = decltype(N)::value;
    constexpr bool hv = heavy(n), pub = heavy(n - 1);
    ring_wait(fullx, n);
    mma(acc, n, n >> 1, 0, 4);
    if (hv && warp < 7) dequant_lookup(q, lutv);
    end_slot(n);
    if (warp < 7) {
      constexpr int u = unit_at(n);
      if (pub) publish(u - 1, 1);
      if (n == 2) lds_unit(q, 4);
      if (hv) {
        constexpr int un = u + 1 < NKB ? u + 1 : u;
        dequant_finish(q, rb, w_ptr(u), sc, ring(bars + 8 * B_FULLQ, un), un >> 3, qbase + (un & 3) * Q_UNIT);
      }
    } else {
      constexpr int m = w_at(n), u = q_at(n), m_next = w_at(n + 1);
      if (m >= 0 || u >= 0) ring_wait(bars + 8 * B_DONE, n - 1);
      if (m >= 0) {
        ready |= __ballot_sync(0xffffffffu, rb >= FLAG_FULL);
        wait_ready(m);
        asm volatile("fence.proxy.async.global;" ::: "memory");
      }
      if (m_next >= 0) rb = ld_strong(fl);
      if ((m >= 0 || u >= 0 || n == 4 || n == 10) && elect_one()) {
        if (m >= 0)
          load_w(ring(bars + 8 * B_FULLW, m), (m == 15 ? 4 : m & 3) * W_STAGE, m * W_STAGE, W_STAGE);
        if (u >= 0) load_q(u);
        if (u >= 0 && u + 2 < NKB) prefetch_q(u + 2);
        if (n == 4 || n == 10) prefetch_x(n == 4 ? 2 : 3);
      }
    }
  };

  mbar_wait(bars + 8 * B_W0, 0);
  mbar_wait(fullx, 0);
  TL(8); TLG(46);
  mma(acc0, 0, 0, 0, 4);
  mbar_wait(fullx + 8, 0);
  TL(9);
  mma(acc1, 1, 0, 0, 4);
  if (wg == 0) lds_unit(q, 2);
  arrive_one(done);
  if (warp < 7) {
    if (wg == 0) {
      emit_unit(convert_unit(q, lutv, sc), 2);
    } else {
      publish(2, 1);
    }
    lds_unit(q, 3);
    const uint4 w3 = convert_unit(q, lutv, sc);
    if (wg == 0) publish(2, 1);
    st_strong128(w_ptr(3), w3);
    rb = ld_strong(w_ptr(3));
  } else if (warp == 7) {
    if (!Q5_EARLY && elect_one()) load_q(5);
    if (Q6_EARLY) {
      mbar_wait(bars + 8 * B_DONE, 0);
      mbar_wait(done, 0);
      if (elect_one()) load_q(6);
    }
  }
  end_slot(1);
  if (warp == 7) rb = ld_strong(fl);

  static_for<1, NR>([&](auto R) {
    constexpr int r = decltype(R)::value;
    ring_wait(bars + 8 * B_FULLW, r);
    TL(8 + 2 * r);
    slot(acc0, IC<2 * r>{});
    TL(9 + 2 * r);
    slot(acc1, IC<2 * r + 1>{});
  });

  __nv_bfloat16* op = out + (size_t)(xrow + (warp & 3) * 16 + (lane >> 2)) * F_DIM + j * BN + (lane & 3) * 8;
  TL(40); TLG(48);
  if (wg == 1) {
    wgmma_wait<0>();
    release(2 * NR);
    if (warp == 7) {
      wait_ready(14);
      asm volatile("fence.proxy.async.global;" ::: "memory");
      ring_wait(bars + 8 * B_DONE, 2 * NR);
      if (elect_one()) load_w(ring(bars + 8 * B_FULLW, 14), 2 * W_STAGE, 14 * W_STAGE, W_STAGE);
      unsigned old = 0;
      if (lane == 17) old = atomicAdd(fl, 1u);
      if (__shfl_sync(0xffffffffu, old, 17) == NI - 1) *fl = 0;
    }
    bar_sync(1, 256);
  }
#pragma unroll
  for (int e = 0; e < ENDK; e++) {
    ring_wait(bars + 8 * B_FULLW, end_kb(e));
    ring_wait(fullx, 2 * NR + e);
    mma(acc0, 2 * NR + e, end_kb(e), 0, 4);
    if (e == ENDK - 1) bar_arrive(1 + wg, 256);
    wgmma_wait<1>();
    if (e > 0 || wg == 0) release(2 * NR + e);
  }
  wgmma_wait<0>();
  release(2 * NR + ENDK);
  TL(41);
  auto delay_to = [&](unsigned t0, unsigned t) {
    while (__any_sync(0xffffffffu, clk32() - t0 < t)) {}
  };
  if (!SPLIT_END || wg == 0) {
    store_acc(acc0, op, 0, 7);
    TL(42);
    bar_sync(2 - wg, 256);
#pragma unroll
    for (int e = 0; e < ENDK; e++) {
      ring_wait(fullx, 2 * NR + ENDK + e);
      mma(acc1, 2 * NR + ENDK + e, end_kb(e), 0, 4);
    }
    if (wg == 0) bar_arrive(1, 256);
    wgmma_wait<0>();
    TL(43); TLG(47);
    if (SPLIT_END) {
      const unsigned t0 = clk32();
#pragma unroll
      for (int J = 0; J < 7; J++) {
        if (J > 0) delay_to(t0, J < W0_N ? J * W0_GAP : W0_LATE);
        store_acc(acc1, op + 64 * F_DIM, J, J + 1);
      }
    } else {
      store_acc(acc1, op + 64 * F_DIM, 0, 7);
    }
  } else {
    uint32_t af[4 * ENDK][4];
    const uint32_t abase = sbase + SMEM_X + XS * X_SLICE + ((warp & 3) * 16 + (lane & 15)) * 128;
    float accp[112];
    const unsigned t0 = clk32();
#pragma unroll
    for (int J = 0; J < 7; J++) {
      if (J > 0) delay_to(t0, J * ST_GAP);
      store_acc(acc0, op, J, J + 1);
      if (J == 0) {
#pragma unroll
        for (int i = 0; i < 112; i++) asm volatile("add.rn.f32 %0, %1, 0f00000000;" : "=f"(accp[i]) : "f"(acc1[i]));
      }
      if (J >= 7 - ENDK - LD_SHIFT && J < 7 - LD_SHIFT) {
        const int e = J - (7 - ENDK - LD_SHIFT), n = 2 * NR + ENDK + e;
        ring_wait(fullx, n);
#pragma unroll
        for (int k = 0; k < 4; k++)
          asm volatile("ldmatrix.sync.aligned.m8n8.x4.shared.b16 {%0, %1, %2, %3}, [%4];"
                       : "=r"(af[4 * e + k][0]), "=r"(af[4 * e + k][1]), "=r"(af[4 * e + k][2]), "=r"(af[4 * e + k][3])
                       : "r"(abase + (n % XS) * X_SLICE + (((2 * k + (lane >> 4)) ^ (lane & 7)) << 4))
                       : "memory");
      }
    }
    TL(42);
    auto part = [&](auto P, int s0, int s1) {
      constexpr int p = decltype(P)::value;
      wgmma_fence();
#pragma unroll
      for (int st = s0; st < s1; st++) {
        const int kb = end_kb(st >> 2);
        const uint64_t db = make_desc(db0 + (kb == 15 ? 4 : kb & 3) * (W_STAGE >> 4) + (st & 3) * (2 * W_KC >> 4) +
                                          (p == 0 ? 0 : 32 + 64 * p), DB_HI);
        if constexpr (p == 0) wgmma_rs_m64n96k16<0>(accp, af[st], db);
        else wgmma_rs_m64n64k16<16 + 32 * p>(accp, af[st], db);
      }
      wgmma_commit();
    };
    bar_sync(1, 256);
    TL(51);
    part(IC<0>{}, 0, 4 * ENDK);
    part(IC<1>{}, 0, LEAD);
    wgmma_wait<1>();
    store_acc(accp, op + 64 * F_DIM, 0, 3);
    part(IC<1>{}, LEAD, 4 * ENDK);
    part(IC<2>{}, 0, LEAD);
    wgmma_wait<1>();
    store_acc(accp, op + 64 * F_DIM, 3, 5);
    part(IC<2>{}, LEAD, 4 * ENDK);
    wgmma_wait<0>();
    TL(43); TLG(47);
    store_acc(accp, op + 64 * F_DIM, 5, 7);
  }
  TL(44);
}

typedef CUresult (*EncodeTiledFn)(CUtensorMap*, CUtensorMapDataType, cuuint32_t, void*, const cuuint64_t*,
                                  const cuuint64_t*, const cuuint32_t*, const cuuint32_t*, CUtensorMapInterleave,
                                  CUtensorMapSwizzle, CUtensorMapL2promotion, CUtensorMapFloatOOBfill);

}

#define XPROMO CU_TENSOR_MAP_L2_PROMOTION_L2_128B
extern "C" void kernel_launch(void* const* d_in, const int* in_sizes, int n_in, void* d_out, int out_size) {
  const __nv_bfloat16* x = (const __nv_bfloat16*)d_in[0];
  const int* qw = (const int*)d_in[1];
  const __nv_bfloat16* lut = (const __nv_bfloat16*)d_in[2];
  const __nv_bfloat16* scales = (const __nv_bfloat16*)d_in[3];
  __nv_bfloat16* out = (__nv_bfloat16*)d_out;

  static EncodeTiledFn enc = nullptr;
  static uint8_t* p_scr = nullptr;
  if (!enc) {
    void* fn = nullptr;
    cudaDriverEntryPointQueryResult qr;
    cudaGetDriverEntryPoint("cuTensorMapEncodeTiled", &fn, cudaEnableDefault, &qr);
    enc = (EncodeTiledFn)fn;
    void* p = nullptr;
    cudaGetSymbolAddress(&p, g_scratch);
    p_scr = (uint8_t*)(((uintptr_t)p + REGION - 1) & ~(uintptr_t)(REGION - 1));
    cudaFuncSetAttribute(fused_kernel, cudaFuncAttributeMaxDynamicSharedMemorySize, SMEM_TOTAL);
  }
  CUtensorMap tm_x, tm_q;
  cuuint32_t estr[2] = {1, 1};
  {
    cuuint64_t gdim[2] = {(cuuint64_t)D_DIM, (cuuint64_t)S_DIM};
    cuuint64_t gstr[1] = {(cuuint64_t)D_DIM * 2};
    cuuint32_t box[2] = {(cuuint32_t)BK, 64};
    enc(&tm_x, CU_TENSOR_MAP_DATA_TYPE_BFLOAT16, 2, (void*)x, gdim, gstr, box, estr, CU_TENSOR_MAP_INTERLEAVE_NONE,
        CU_TENSOR_MAP_SWIZZLE_128B, XPROMO, CU_TENSOR_MAP_FLOAT_OOB_FILL_NONE);
  }
  {
    cuuint64_t gdim[2] = {(cuuint64_t)F_DIM, (cuuint64_t)D_DIM};
    cuuint64_t gstr[1] = {(cuuint64_t)F_DIM * 4};
    cuuint32_t box[2] = {(cuuint32_t)BN, 8};
    enc(&tm_q, CU_TENSOR_MAP_DATA_TYPE_INT32, 2, (void*)qw, gdim, gstr, box, estr, CU_TENSOR_MAP_INTERLEAVE_NONE,
        CU_TENSOR_MAP_SWIZZLE_NONE, CU_TENSOR_MAP_L2_PROMOTION_NONE, CU_TENSOR_MAP_FLOAT_OOB_FILL_NONE);
  }
  fused_kernel<<<NI * NJ, 256, SMEM_TOTAL, cudaStreamPerThread>>>(qw, lut, scales, out, p_scr, tm_x, tm_q);
}
```

```cpp
#include <cuda_runtime.h>
#include <cuda_bf16.h>
#include <cuda.h>
#include <stdint.h>

namespace {

constexpr int S_DIM = 2048, D_DIM = 1024, F_DIM = 3584;
constexpr int BM = 256, BN = 224, BK = 64;
constexpr int NKB = D_DIM / BK;
constexpr int NJ = F_DIM / BN;
constexpr int NI = S_DIM / BM;
constexpr int WS = 4;
constexpr int XS = 5;
constexpr int ENDK = 5;
constexpr int NR = NKB - ENDK;
constexpr int X_SLICE = 64 * BK * 2;
constexpr int W_STAGE = BN * BK * 2;
constexpr int W_KC = BN * 16;

constexpr int REGION = 512 * 1024;
__device__ uint4 g_scratch[(NJ + 1) * REGION / 16];

__device__ __forceinline__ uint32_t smem_u32(const void* p) { return (uint32_t)__cvta_generic_to_shared(p); }
__device__ __forceinline__ unsigned clk32() {
  unsigned c;
  asm volatile("mov.u32 %0, %%clock;" : "=r"(c)::"memory");
  return c;
}
__device__ __forceinline__ bool elect_one() {
  uint32_t p;
  asm volatile("{\n.reg .pred P;\nelect.sync _|P, 0xffffffff;\nselp.b32 %0, 1, 0, P;\n}" : "=r"(p));
  return p != 0;
}
__device__ __forceinline__ void mbar_init(uint32_t bar, uint32_t cnt) {
  asm volatile("mbarrier.init.shared::cta.b64 [%0], %1;" ::"r"(bar), "r"(cnt) : "memory");
}
__device__ __forceinline__ void mbar_expect_tx(uint32_t bar, uint32_t bytes) {
  asm volatile("mbarrier.arrive.expect_tx.shared::cta.b64 _, [%0], %1;" ::"r"(bar), "r"(bytes) : "memory");
}
__device__ __forceinline__ void mbar_arrive(uint32_t bar) {
  asm volatile("mbarrier.arrive.shared::cta.b64 _, [%0];" ::"r"(bar) : "memory");
}
__device__ __forceinline__ bool mbar_test(uint32_t bar, uint32_t parity) {
  uint32_t ok;
  asm volatile(
      "{\n.reg .pred p;\nmbarrier.test_wait.parity.shared::cta.b64 p, [%1], %2;\nselp.b32 %0, 1, 0, p;\n}\n"
      : "=r"(ok) : "r"(bar), "r"(parity) : "memory");
  return ok != 0;
}
__device__ __forceinline__ void mbar_wait(uint32_t bar, uint32_t parity) {
  asm volatile(
      "{\n.reg .pred p;\n"
      "LAB_WAIT:\n"
      "mbarrier.try_wait.parity.shared::cta.b64 p, [%0], %1;\n"
      "@p bra LAB_DONE;\n"
      "bra LAB_WAIT;\n"
      "LAB_DONE:\n}\n" ::"r"(bar), "r"(parity) : "memory");
}
__device__ __forceinline__ uint32_t ring(uint32_t base, int i) { return base + 8 * (i & 7); }
__device__ __forceinline__ void ring_wait(uint32_t base, int i) { mbar_wait(ring(base, i), (i >> 3) & 1); }
__device__ __forceinline__ void tma_load_2d(uint32_t dst, const CUtensorMap* tm, int c0, int c1, uint32_t bar) {
  asm volatile(
      "cp.async.bulk.tensor.2d.shared::cluster.global.mbarrier::complete_tx::bytes [%0], [%1, {%3, %4}], [%2];"
      ::"r"(dst), "l"(tm), "r"(bar), "r"(c0), "r"(c1) : "memory");
}
__device__ __forceinline__ void tma_prefetch_2d(const CUtensorMap* tm, int c0, int c1) {
  asm volatile("cp.async.bulk.prefetch.tensor.2d.L2.global [%0, {%1, %2}];" ::"l"(tm), "r"(c0), "r"(c1) : "memory");
}
__device__ __forceinline__ void bulk_load(uint32_t dst, const void* src, uint32_t bytes, uint32_t bar) {
  asm volatile(
      "cp.async.bulk.shared::cluster.global.mbarrier::complete_tx::bytes [%0], [%1], %2, [%3];"
      ::"r"(dst), "l"(src), "r"(bytes), "r"(bar) : "memory");
}
__device__ __forceinline__ int ldg_stream(const int* p) {
  int v;
  asm volatile("ld.global.L1::no_allocate.b32 %0, [%1];" : "=r"(v) : "l"(p) : "memory");
  return v;
}
__device__ __forceinline__ void cp_async16(uint32_t dst, const void* src) {
  asm volatile("cp.async.cg.shared.global [%0], [%1], 16;" ::"r"(dst), "l"(src) : "memory");
}
__device__ __forceinline__ void cp_async_commit() { asm volatile("cp.async.commit_group;" ::: "memory"); }
template <int N>
__device__ __forceinline__ void cp_async_wait() { asm volatile("cp.async.wait_group %0;" ::"n"(N) : "memory"); }
__device__ __forceinline__ uint32_t ldg_u16(const void* p) {
  uint32_t v;
  asm volatile("ld.global.u16 %0, [%1];" : "=r"(v) : "l"(p) : "memory");
  return v;
}
__device__ __forceinline__ int lds32(uint32_t addr) {
  int v;
  asm volatile("ld.shared.b32 %0, [%1];" : "=r"(v) : "r"(addr) : "memory");
  return v;
}
__device__ __forceinline__ void sts128(uint32_t addr, uint4 v) {
  asm volatile("st.shared.v4.u32 [%0], {%1, %2, %3, %4};" ::"r"(addr), "r"(v.x), "r"(v.y), "r"(v.z), "r"(v.w) : "memory");
}
__device__ __forceinline__ uint64_t make_desc(uint32_t lo, uint32_t hi) {
  uint64_t d;
  asm("mov.b64 %0, {%1, %2};" : "=l"(d) : "r"(lo), "r"(hi));
  return d;
}
__device__ __forceinline__ unsigned ld_strong(const void* p) {
  unsigned v;
  asm volatile("ld.relaxed.gpu.global.u32 %0, [%1];" : "=r"(v) : "l"(p) : "memory");
  return v;
}
__device__ __forceinline__ void st_strong128(void* p, uint4 v) {
  asm volatile("st.relaxed.gpu.global.v4.u32 [%0], {%1, %2, %3, %4};" ::"l"(p), "r"(v.x), "r"(v.y), "r"(v.z), "r"(v.w)
               : "memory");
}
__device__ __forceinline__ void wgmma_fence() { asm volatile("wgmma.fence.sync.aligned;" ::: "memory"); }
__device__ __forceinline__ void wgmma_commit() { asm volatile("wgmma.commit_group.sync.aligned;" ::: "memory"); }
template <int N>
__device__ __forceinline__ void wgmma_wait() { asm volatile("wgmma.wait_group.sync.aligned %0;" ::"n"(N) : "memory"); }
__device__ __forceinline__ void bar_sync(int id, int n) { asm volatile("bar.sync %0, %1;" ::"r"(id), "r"(n) : "memory"); }
__device__ __forceinline__ void bar_arrive(int id, int n) { asm volatile("bar.arrive %0, %1;" ::"r"(id), "r"(n) : "memory"); }

__device__ __forceinline__ void wgmma_m64n224k16(float (&d)[112], uint64_t da, uint64_t db, int scale_d) {
  asm volatile(
    "{\n.reg .pred p;\nsetp.ne.b32 p, %114, 0;\n"
    "wgmma.mma_async.sync.aligned.m64n224k16.f32.bf16.bf16 "
    "{%0, %1, %2, %3, %4, %5, %6, %7, %8, %9, %10, %11, %12, %13, %14, %15, "
    "%16, %17, %18, %19, %20, %21, %22, %23, %24, %25, %26, %27, %28, %29, %30, %31, "
    "%32, %33, %34, %35, %36, %37, %38, %39, %40, %41, %42, %43, %44, %45, %46, %47, "
    "%48, %49, %50, %51, %52, %53, %54, %55, %56, %57, %58, %59, %60, %61, %62, %63, "
    "%64, %65, %66, %67, %68, %69, %70, %71, %72, %73, %74, %75, %76, %77, %78, %79, "
    "%80, %81, %82, %83, %84, %85, %86, %87, %88, %89, %90, %91, %92, %93, %94, %95, "
    "%96, %97, %98, %99, %100, %101, %102, %103, %104, %105, %106, %107, %108, %109, %110, %111}, "
    "%112, %113, p, 1, 1, 0, 0;\n}\n"
    : "+f"(d[0]), "+f"(d[1]), "+f"(d[2]), "+f"(d[3]), "+f"(d[4]), "+f"(d[5]), "+f"(d[6]), "+f"(d[7]),
      "+f"(d[8]), "+f"(d[9]), "+f"(d[10]), "+f"(d[11]), "+f"(d[12]), "+f"(d[13]), "+f"(d[14]), "+f"(d[15]),
      "+f"(d[16]), "+f"(d[17]), "+f"(d[18]), "+f"(d[19]), "+f"(d[20]), "+f"(d[21]), "+f"(d[22]), "+f"(d[23]),
      "+f"(d[24]), "+f"(d[25]), "+f"(d[26]), "+f"(d[27]), "+f"(d[28]), "+f"(d[29]), "+f"(d[30]), "+f"(d[31]),
      "+f"(d[32]), "+f"(d[33]), "+f"(d[34]), "+f"(d[35]), "+f"(d[36]), "+f"(d[37]), "+f"(d[38]), "+f"(d[39]),
      "+f"(d[40]), "+f"(d[41]), "+f"(d[42]), "+f"(d[43]), "+f"(d[44]), "+f"(d[45]), "+f"(d[46]), "+f"(d[47]),
      "+f"(d[48]), "+f"(d[49]), "+f"(d[50]), "+f"(d[51]), "+f"(d[52]), "+f"(d[53]), "+f"(d[54]), "+f"(d[55]),
      "+f"(d[56]), "+f"(d[57]), "+f"(d[58]), "+f"(d[59]), "+f"(d[60]), "+f"(d[61]), "+f"(d[62]), "+f"(d[63]),
      "+f"(d[64]), "+f"(d[65]), "+f"(d[66]), "+f"(d[67]), "+f"(d[68]), "+f"(d[69]), "+f"(d[70]), "+f"(d[71]),
      "+f"(d[72]), "+f"(d[73]), "+f"(d[74]), "+f"(d[75]), "+f"(d[76]), "+f"(d[77]), "+f"(d[78]), "+f"(d[79]),
      "+f"(d[80]), "+f"(d[81]), "+f"(d[82]), "+f"(d[83]), "+f"(d[84]), "+f"(d[85]), "+f"(d[86]), "+f"(d[87]),
      "+f"(d[88]), "+f"(d[89]), "+f"(d[90]), "+f"(d[91]), "+f"(d[92]), "+f"(d[93]), "+f"(d[94]), "+f"(d[95]),
      "+f"(d[96]), "+f"(d[97]), "+f"(d[98]), "+f"(d[99]), "+f"(d[100]), "+f"(d[101]), "+f"(d[102]), "+f"(d[103]),
      "+f"(d[104]), "+f"(d[105]), "+f"(d[106]), "+f"(d[107]), "+f"(d[108]), "+f"(d[109]), "+f"(d[110]), "+f"(d[111])
    : "l"(da), "l"(db), "r"(scale_d));
}
template <int O>
__device__ __forceinline__ void wgmma_rs_m64n96k16(float (&d)[112], const uint32_t (&a)[4], uint64_t db) {
  asm volatile(
    "wgmma.mma_async.sync.aligned.m64n96k16.f32.bf16.bf16 "
    "{%0, %1, %2, %3, %4, %5, %6, %7, %8, %9, %10, %11, %12, %13, %14, %15, "
    "%16, %17, %18, %19, %20, %21, %22, %23, %24, %25, %26, %27, %28, %29, %30, %31, "
    "%32, %33, %34, %35, %36, %37, %38, %39, %40, %41, %42, %43, %44, %45, %46, %47}, "
    "{%48, %49, %50, %51}, %52, 1, 1, 1, 0;\n"
    : "+f"(d[O + 0]), "+f"(d[O + 1]), "+f"(d[O + 2]), "+f"(d[O + 3]),
      "+f"(d[O + 4]), "+f"(d[O + 5]), "+f"(d[O + 6]), "+f"(d[O + 7]),
      "+f"(d[O + 8]), "+f"(d[O + 9]), "+f"(d[O + 10]), "+f"(d[O + 11]),
      "+f"(d[O + 12]), "+f"(d[O + 13]), "+f"(d[O + 14]), "+f"(d[O + 15]),
      "+f"(d[O + 16]), "+f"(d[O + 17]), "+f"(d[O + 18]), "+f"(d[O + 19]),
      "+f"(d[O + 20]), "+f"(d[O + 21]), "+f"(d[O + 22]), "+f"(d[O + 23]),
      "+f"(d[O + 24]), "+f"(d[O + 25]), "+f"(d[O + 26]), "+f"(d[O + 27]),
      "+f"(d[O + 28]), "+f"(d[O + 29]), "+f"(d[O + 30]), "+f"(d[O + 31]),
      "+f"(d[O + 32]), "+f"(d[O + 33]), "+f"(d[O + 34]), "+f"(d[O + 35]),
      "+f"(d[O + 36]), "+f"(d[O + 37]), "+f"(d[O + 38]), "+f"(d[O + 39]),
      "+f"(d[O + 40]), "+f"(d[O + 41]), "+f"(d[O + 42]), "+f"(d[O + 43]),
      "+f"(d[O + 44]), "+f"(d[O + 45]), "+f"(d[O + 46]), "+f"(d[O + 47])
    : "r"(a[0]), "r"(a[1]), "r"(a[2]), "r"(a[3]), "l"(db));
}
template <int O>
__device__ __forceinline__ void wgmma_rs_m64n64k16(float (&d)[112], const uint32_t (&a)[4], uint64_t db) {
  asm volatile(
    "wgmma.mma_async.sync.aligned.m64n64k16.f32.bf16.bf16 "
    "{%0, %1, %2, %3, %4, %5, %6, %7, %8, %9, %10, %11, %12, %13, %14, %15, "
    "%16, %17, %18, %19, %20, %21, %22, %23, %24, %25, %26, %27, %28, %29, %30, %31}, "
    "{%32, %33, %34, %35}, %36, 1, 1, 1, 0;\n"
    : "+f"(d[O + 0]), "+f"(d[O + 1]), "+f"(d[O + 2]), "+f"(d[O + 3]),
      "+f"(d[O + 4]), "+f"(d[O + 5]), "+f"(d[O + 6]), "+f"(d[O + 7]),
      "+f"(d[O + 8]), "+f"(d[O + 9]), "+f"(d[O + 10]), "+f"(d[O + 11]),
      "+f"(d[O + 12]), "+f"(d[O + 13]), "+f"(d[O + 14]), "+f"(d[O + 15]),
      "+f"(d[O + 16]), "+f"(d[O + 17]), "+f"(d[O + 18]), "+f"(d[O + 19]),
      "+f"(d[O + 20]), "+f"(d[O + 21]), "+f"(d[O + 22]), "+f"(d[O + 23]),
      "+f"(d[O + 24]), "+f"(d[O + 25]), "+f"(d[O + 26]), "+f"(d[O + 27]),
      "+f"(d[O + 28]), "+f"(d[O + 29]), "+f"(d[O + 30]), "+f"(d[O + 31])
    : "r"(a[0]), "r"(a[1]), "r"(a[2]), "r"(a[3]), "l"(db));
}

__device__ __forceinline__ uint32_t pack_bf16(float lo, float hi) {
  uint32_t r;
  asm("cvt.rn.bf16x2.f32 %0, %1, %2;" : "=r"(r) : "f"(hi), "f"(lo));
  return r;
}

__device__ __forceinline__ int perm32(int n) { return (n & ~30) | ((n & 6) << 2) | ((n >> 2) & 6); }

constexpr int SMEM_X = 0;
constexpr int SMEM_W = 2 * XS * X_SLICE;
constexpr int SMEM_Q = SMEM_W + WS * W_STAGE;
constexpr int Q_UNIT = 8 * BN * 4;
constexpr int SMEM_BAR = SMEM_Q + W_STAGE;
constexpr int B_FULLW = 0, B_FULLQ = 8, B_FULLX = 16, B_DONE = 32, B_W0 = 48, B_RAW0 = 49, B_COUNT = 51;
constexpr int SMEM_TL = SMEM_BAR + 512;
constexpr int SMEM_TOTAL = SMEM_TL + 2048;
constexpr int W_OFF = 128;
constexpr unsigned FLAG_FULL = NI * 7;

#define TL(i)
#define TLG(i)

__device__ __forceinline__ void store_acc(const float (&a)[112], __nv_bfloat16* p, int J0, int J1) {
#pragma unroll
  for (int J = J0; J < J1; J++) {
    uint4 v0, v1;
    v0.x = pack_bf16(a[16 * J + 0], a[16 * J + 1]);
    v0.y = pack_bf16(a[16 * J + 4], a[16 * J + 5]);
    v0.z = pack_bf16(a[16 * J + 8], a[16 * J + 9]);
    v0.w = pack_bf16(a[16 * J + 12], a[16 * J + 13]);
    v1.x = pack_bf16(a[16 * J + 2], a[16 * J + 3]);
    v1.y = pack_bf16(a[16 * J + 6], a[16 * J + 7]);
    v1.z = pack_bf16(a[16 * J + 10], a[16 * J + 11]);
    v1.w = pack_bf16(a[16 * J + 14], a[16 * J + 15]);
    *reinterpret_cast<uint4*>(p + 32 * J) = v0;
    *reinterpret_cast<uint4*>(p + 8 * F_DIM + 32 * J) = v1;
  }
}

__device__ __forceinline__ void load_unit(int (&q)[8], const int* p) {
#pragma unroll
  for (int i = 0; i < 8; i++) q[i] = ldg_stream(p + i * F_DIM);
}
__device__ __forceinline__ uint4 convert_unit(const int (&q)[8], float lutv, float sc) {
  float v[8];
#pragma unroll
  for (int i = 0; i < 8; i++) v[i] = __shfl_sync(0xffffffffu, lutv, q[i]) * sc;
  uint4 o;
  o.x = pack_bf16(v[0], v[1]);
  o.y = pack_bf16(v[2], v[3]);
  o.z = pack_bf16(v[4], v[5]);
  o.w = pack_bf16(v[6], v[7]);
  return o;
}

struct Table {
  uint32_t lo[4], hi[4];
};
__device__ __forceinline__ uint32_t prmt(uint32_t a, uint32_t b, uint32_t s) {
  uint32_t r;
  asm("prmt.b32 %0, %1, %2, %3;" : "=r"(r) : "r"(a), "r"(b), "r"(s));
  return r;
}
__device__ __forceinline__ Table make_table(float lutv, float sc) {
  Table t;
#pragma unroll
  for (int i = 0; i < 4; i++) {
    const uint32_t a = pack_bf16(__shfl_sync(0xffffffffu, lutv, 4 * i) * sc, __shfl_sync(0xffffffffu, lutv, 4 * i + 1) * sc);
    const uint32_t b =
        pack_bf16(__shfl_sync(0xffffffffu, lutv, 4 * i + 2) * sc, __shfl_sync(0xffffffffu, lutv, 4 * i + 3) * sc);
    t.lo[i] = prmt(a, b, 0x6420);
    t.hi[i] = prmt(a, b, 0x7531);
  }
  return t;
}
__device__ __forceinline__ uint4 convert_unit(const int (&q)[8], const Table& t) {
  const uint32_t all = ((q[7] * 16 + q[6]) * 256 + (q[5] * 16 + q[4])) * 65536 + ((q[3] * 16 + q[2]) * 256 + (q[1] * 16 + q[0]));
  const uint32_t s7 = all & 0x77777777u;
  const uint32_t s2 = ((all >> 1) & 0x44444444u) | 0x32103210u;
  uint32_t o[4];
#pragma unroll
  for (int h = 0; h < 2; h++) {
    const uint32_t a = h ? s7 >> 16 : s7, b = h ? s2 >> 16 : s2;
    const uint32_t lo = prmt(prmt(t.lo[0], t.lo[1], a), prmt(t.lo[2], t.lo[3], a), b);
    const uint32_t hi = prmt(prmt(t.hi[0], t.hi[1], a), prmt(t.hi[2], t.hi[3], a), b);
    o[2 * h] = prmt(lo, hi, 0x5140);
    o[2 * h + 1] = prmt(lo, hi, 0x7362);
  }
  return make_uint4(o[0], o[1], o[2], o[3]);
}

__device__ __forceinline__ void dequant_lookup(int (&q)[8], float lutv) {
  asm volatile(
      "shfl.sync.idx.b32 %0, %8, %0, 31, 0xffffffff;\n"
      "shfl.sync.idx.b32 %1, %8, %1, 31, 0xffffffff;\n"
      "shfl.sync.idx.b32 %2, %8, %2, 31, 0xffffffff;\n"
      "shfl.sync.idx.b32 %3, %8, %3, 31, 0xffffffff;\n"
      "shfl.sync.idx.b32 %4, %8, %4, 31, 0xffffffff;\n"
      "shfl.sync.idx.b32 %5, %8, %5, 31, 0xffffffff;\n"
      "shfl.sync.idx.b32 %6, %8, %6, 31, 0xffffffff;\n"
      "shfl.sync.idx.b32 %7, %8, %7, 31, 0xffffffff;\n"
      : "+r"(q[0]), "+r"(q[1]), "+r"(q[2]), "+r"(q[3]), "+r"(q[4]), "+r"(q[5]), "+r"(q[6]), "+r"(q[7])
      : "r"(__float_as_int(lutv)));
}
__device__ __forceinline__ void dequant_finish(int (&q)[8], unsigned& rb, uint4* wp, float sc, uint32_t qbar,
                                               uint32_t qpar, uint32_t qaddr) {
  asm volatile(
      "{\n.reg .pred W;\n.reg .b32 o0, o1, o2, o3;\n"
      "DQ_WAIT:\n"
      "mbarrier.try_wait.parity.shared::cta.b64 W, [%11], %13;\n"
      "@!W bra DQ_WAIT;\n"
      "mul.rn.f32 %0, %0, %10;\nmul.rn.f32 %1, %1, %10;\nmul.rn.f32 %2, %2, %10;\nmul.rn.f32 %3, %3, %10;\n"
      "mul.rn.f32 %4, %4, %10;\nmul.rn.f32 %5, %5, %10;\nmul.rn.f32 %6, %6, %10;\nmul.rn.f32 %7, %7, %10;\n"
      "cvt.rn.bf16x2.f32 o0, %1, %0;\ncvt.rn.bf16x2.f32 o1, %3, %2;\n"
      "cvt.rn.bf16x2.f32 o2, %5, %4;\ncvt.rn.bf16x2.f32 o3, %7, %6;\n"
      "ld.volatile.shared.b32 %0, [%12];\nld.volatile.shared.b32 %1, [%12+896];\n"
      "ld.volatile.shared.b32 %2, [%12+1792];\nld.volatile.shared.b32 %3, [%12+2688];\n"
      "ld.volatile.shared.b32 %4, [%12+3584];\nld.volatile.shared.b32 %5, [%12+4480];\n"
      "ld.volatile.shared.b32 %6, [%12+5376];\nld.volatile.shared.b32 %7, [%12+6272];\n"
      "st.relaxed.gpu.global.v4.u32 [%9], {o0, o1, o2, o3};\n"
      "ld.relaxed.gpu.global.u32 %8, [%9];\n}\n"
      : "+r"(q[0]), "+r"(q[1]), "+r"(q[2]), "+r"(q[3]), "+r"(q[4]), "+r"(q[5]), "+r"(q[6]), "+r"(q[7]), "=r"(rb)
      : "l"(wp), "r"(__float_as_int(sc)), "r"(qbar), "r"(qaddr), "r"(qpar)
      : "memory");
}

#define Q6_EARLY 0
constexpr int PU = 3;
#define HEAVY 0x3BBBAu
__host__ __device__ constexpr int popc(unsigned v) { return v ? (v & 1) + popc(v >> 1) : 0; }
__host__ __device__ constexpr bool heavy(int n) { return n >= 0 && ((HEAVY >> n) & 1); }
__host__ __device__ constexpr int unit_at(int n) { return PU + popc(HEAVY & ((1u << n) - 1)); }
__host__ __device__ constexpr int emit_slot(int u) {
  if (u < PU) return -1;
  for (int n = 0; n < 24; n++)
    if (heavy(n) && unit_at(n) == u) return n;
  return 99;
}
__host__ __device__ constexpr int end_kb(int e) { return e < 3 ? NR + e : NR + 7 - e; }
__host__ __device__ constexpr int cmax(int a, int b) { return a > b ? a : b; }
__host__ __device__ constexpr int w_slot(int m) {
  return m == 15 ? cmax(emit_slot(15) + 3, 20) : cmax(2 * m - 5, emit_slot(m) + 3);
}
__host__ __device__ constexpr int q_slot(int u) {
  return u <= 5 + Q6_EARLY ? 1 : cmax(q_slot(u - 1) + 1, u < 8 ? 2 : u == 8 ? 4 : emit_slot(u - 5) + 2);
}
__host__ __device__ constexpr int w_at(int n) {
  for (int m = 2; m < NKB; m++)
    if (w_slot(m) == n) return m;
  return -1;
}
__host__ __device__ constexpr int q_at(int n) {
  for (int u = 5; u < NKB; u++)
    if (q_slot(u) == n) return u;
  return -1;
}
constexpr bool schedule_ok() {
  if (popc(HEAVY) != NKB - PU || (HEAVY & 7) != 2 || (HEAVY >> 20)) return false;
  for (int m = 2; m < NKB; m++) {
    if (w_at(w_slot(m)) != m || (m != 14 && w_slot(m) >= 2 * NR)) return false;
    if (m < NR && w_slot(m) > 2 * m - 2) return false;
  }
  for (int u = 5; u < NKB; u++)
    if (q_slot(u) + 2 > emit_slot(u - 1)) return false;
  return true;
}
static_assert(schedule_ok(), "bad schedule");
template <int V>
struct IC {
  static constexpr int value = V;
};
template <int I, int N, class F>
__device__ __forceinline__ void static_for(F&& f) {
  if constexpr (I < N) {
    f(IC<I>{});
    static_for<I + 1, N>(f);
  }
}

#define SHFL_MASK 0
#define RSPLIT 5
#define PACE_X 1100
#define PACE_Q2 1600
#define PACE_Q3 2100
#define WAIT_MODE 0
#define Q2_FIRST 0
#define X3_LATE 0
#define Q5_EARLY 0
#define SPLIT_END 1
#define ST_GAP 170
#define LD_SHIFT 1
#define LEAD 8
#define NCP 3
#define U1_POS 0
#define PACE_L 0
#define STAG_L 70
#define PACE_INIT 650
#define PUB_AT 6
#define PF_X 0
#define PF_Q 0

constexpr uint32_t sbase = 1024;

__global__ void __launch_bounds__(256, 1)
fused_kernel(const int* __restrict__ qw, const __nv_bfloat16* __restrict__ lut,
             const __nv_bfloat16* __restrict__ scales, __nv_bfloat16* __restrict__ out, uint8_t* scratch,
             const __grid_constant__ CUtensorMap tm_x, const __grid_constant__ CUtensorMap tm_q) {
  extern __shared__ __align__(1024) uint8_t smem_raw[];
  constexpr uint32_t bars = sbase + SMEM_BAR;
  const int j = blockIdx.x >> 3, it = blockIdx.x & 7;
  constexpr uint32_t raw0 = sbase + SMEM_W + 2 * W_STAGE;
  uint32_t lut_raw = 0, sc_raw = 0;
  if (threadIdx.x < 224) {
    const unsigned t = threadIdx.x, row0 = (t >> 3) & 3, col = (t & ~31u) + (t & 7) * 4;
    const int* src = qw + (row0 * F_DIM + j * BN + col);
    const uint32_t dst = row0 * (BN * 4) + col * 4;
    lut_raw = ldg_u16(lut + (t & 15));
    sc_raw = ldg_u16(scales + (j * BN + perm32(t)));
    __syncwarp();
#pragma unroll
    for (int g = 0; g < NCP + 1; g++) {
      const unsigned row = g == 0 ? BK + it * 8 : (g - 1) * 8;
      const uint32_t d = dst + (g == 0 ? sbase + SMEM_Q + Q_UNIT : raw0 + (g - 1) * Q_UNIT);
      cp_async16(d, src + row * F_DIM);
      cp_async16(d + 4 * BN * 4, src + (row + 4) * F_DIM);
      cp_async_commit();
    }
  }
  const int warp = __shfl_sync(0xffffffffu, threadIdx.x >> 5, 0);
  const int wg = warp >> 2;
  int lane;
  asm volatile("mov.u32 %0, %%laneid;" : "=r"(lane));
  const unsigned t_start = clk32();
  auto pace = [&](unsigned t) {
    while (__any_sync(0xffffffffu, clk32() - t_start < t)) {}
  };

  uint8_t* const region = scratch + (size_t)j * REGION;
  uint8_t* const wp = region + W_OFF + it * W_KC + (warp * 32 + lane) * 16;
  unsigned* const fl = reinterpret_cast<unsigned*>(region) + lane;
  float lutv, sc;
  unsigned rb;
  const int xrow = it * BM + wg * 128;

  auto w_ptr = [&](int u) { return reinterpret_cast<uint4*>(wp + u * W_STAGE); };
  auto emit_unit = [&](uint4 w, int u) {
    st_strong128(w_ptr(u), w);
    rb = ld_strong(w_ptr(u));
  };
  auto publish = [&](int u, unsigned inc) {
    asm volatile(
        "{\n.reg .pred P, Q;\n"
        "setp.ne.u32 P, %1, 0xffffffff;\n"
        "vote.sync.all.pred P, P, 0xffffffff;\n"
        "setp.eq.and.s32 Q, %2, %3, P;\n"
        "@Q red.relaxed.gpu.global.add.u32 [%0], %4;\n}"
        ::"l"(fl), "r"(rb), "r"(lane), "r"(u), "r"(inc) : "memory");
  };
  auto load_x = [&](int g, int n, int kb, int half) {
    const uint32_t bar = ring(bars + 8 * B_FULLX, n) + g * 64;
    mbar_expect_tx(bar, X_SLICE);
    tma_load_2d(sbase + SMEM_X + (n % XS) * X_SLICE + g * (XS * X_SLICE), &tm_x, kb * BK,
                it * BM + g * 128 + half * 64, bar);
  };
  auto load_q = [&](int u) {
    const uint32_t bar = ring(bars + 8 * B_FULLQ, u);
    mbar_expect_tx(bar, Q_UNIT);
    tma_load_2d(sbase + SMEM_Q + (u & 3) * Q_UNIT, &tm_q, j * BN, u * BK + it * 8, bar);
  };
  auto prefetch_x = [&](int g) {
    if (PF_X) tma_prefetch_2d(&tm_x, (4 * g + (j >> 2)) * BK, it * BM + (j & 3) * 64);
  };
  auto prefetch_q = [&](int u) {
    if (PF_Q) tma_prefetch_2d(&tm_q, j * BN, u * BK + it * 8);
  };

  unsigned ready = 0;
  auto load_w = [&](uint32_t bar, int dst, int src, int bytes) {
    mbar_expect_tx(bar, bytes);
    bulk_load(sbase + SMEM_W + dst, region + W_OFF + src, bytes, bar);
  };
  auto poll = [&]() { ready |= __ballot_sync(0xffffffffu, ld_strong(fl) >= FLAG_FULL); };
  auto wait_ready = [&](int kb) {
    int spins = 0;
    while (!((ready >> kb) & 1)) {
      poll();
      if (++spins > (1 << 22)) __trap();
    }
  };

  uint32_t qbase;
  asm volatile("mov.u32 %0, %1;" : "=r"(qbase) : "r"(sbase + SMEM_Q + warp * 128 + perm32(lane) * 4));
  auto lds_unit = [&](int (&q)[8], int u) {
    ring_wait(bars + 8 * B_FULLQ, u);
#pragma unroll
    for (int i = 0; i < 8; i++) q[i] = lds32(qbase + (u & 3) * Q_UNIT + i * (BN * 4));
  };
  auto arrive_one = [&](uint32_t bar) {
    asm volatile("{\n.reg .pred P;\nelect.sync _|P, 0xffffffff;\n@P mbarrier.arrive.shared::cta.b64 _, [%0];\n}"
                 ::"r"(bar) : "memory");
  };

  int q[8];
  if (warp == 7) {
    if (elect_one()) {
      mbar_init(bars + 8 * B_RAW0, RSPLIT - NCP);
      if (RSPLIT < 8) mbar_init(bars + 8 * B_RAW0 + 8, 8 - RSPLIT);
      asm volatile("fence.mbarrier_init.release.cluster;" ::: "memory");
    }
    __syncwarp();
    bar_arrive(4, (9 - NCP) * 32);
    if (elect_one()) {
      asm volatile("prefetch.tensormap [%0];" ::"l"(&tm_x) : "memory");
      asm volatile("prefetch.tensormap [%0];" ::"l"(&tm_q) : "memory");
    }
    TL(5);
    pace(PACE_INIT);
    if (elect_one()) {
#pragma unroll
      for (int i = 0; i < B_RAW0; i++) mbar_init(bars + 8 * i, i == B_W0 ? 7 : i >= B_DONE ? 4 : 1);
      asm volatile("fence.mbarrier_init.release.cluster;" ::: "memory");
    }
    __syncwarp();
    rb = ld_strong(fl);
    bar_arrive(0, 256);
    TL(4);
    lutv = 0.f;
    sc = 0.f;
    if (smem_u32(smem_raw) != sbase) __trap();
    if (elect_one()) {
      mbar_arrive(bars + 8 * B_FULLW);
      mbar_arrive(bars + 8 * B_FULLQ);
      mbar_arrive(bars + 8 * B_FULLQ + 8);
    }
    if (PACE_X) pace(PACE_X);
    if (elect_one()) {
      if (Q2_FIRST) load_q(2);
      load_x(0, 0, 0, 0); load_x(1, 0, 0, 0); load_x(0, 1, 0, 1); load_x(1, 1, 0, 1);
    }
    if (!Q2_FIRST) {
      pace(PACE_Q2);
      if (elect_one()) load_q(2);
    }
    if (WAIT_MODE == 0) pace(PACE_Q3);
    if (WAIT_MODE == 1) mbar_wait(bars + 8 * B_FULLQ + 16, 0);
    if (WAIT_MODE == 2) mbar_wait(bars + 8 * B_FULLX, 0);
    ready = __ballot_sync(0xffffffffu, rb >= FLAG_FULL);
    rb = ld_strong(fl);
    if (elect_one()) {
      load_q(3);
      load_x(0, 2, 1, 0); load_x(1, 2, 1, 0);
      if (!X3_LATE) { load_x(0, 3, 1, 1); load_x(1, 3, 1, 1); }
    }
    ready |= __ballot_sync(0xffffffffu, rb >= FLAG_FULL);
    wait_ready(1);
    asm volatile("fence.proxy.async.global;" ::: "memory");
    if (elect_one()) {
      load_w(bars + 8 * B_FULLW + 8, W_STAGE, W_STAGE, W_STAGE);
      if (X3_LATE) { load_x(0, 3, 1, 1); load_x(1, 3, 1, 1); }
      load_q(4);
      load_x(0, 4, 2, 0); load_x(1, 4, 2, 0);
      if (Q5_EARLY) load_q(5);
    }
    TL(2);
    TL(3);
  } else {
    if (warp + NCP < 8) {
      bar_sync(4, (9 - NCP) * 32);
      pace(PACE_L + warp * STAG_L);
      if (elect_one()) {
        const int c = warp + NCP;
        const uint32_t bar = bars + 8 * B_RAW0 + (c < RSPLIT ? 0 : 8);
        mbar_expect_tx(bar, Q_UNIT);
#pragma unroll
        for (int i = 0; i < 8; i++)
          bulk_load(raw0 + (c * 8 + i) * (BN * 4), qw + (size_t)(c * 8 + i) * F_DIM + j * BN, BN * 4, bar);
      }
    }
    bar_sync(0, 256);
    pace(200);
    asm volatile("shl.b32 %0, %0, 16;\nshl.b32 %1, %1, 16;" : "+r"(lut_raw), "+r"(sc_raw));
    lutv = __uint_as_float(lut_raw);
    sc = __uint_as_float(sc_raw);
    const Table tab = make_table(lutv, sc);
    if (__any_sync(0xffffffffu, lane > 31 && (tab.lo[0] ^ tab.lo[1] ^ tab.lo[2] ^ tab.lo[3] ^ tab.hi[0] ^ tab.hi[1] ^
                                              tab.hi[2] ^ tab.hi[3]) == 1))
      __trap();
    int r[2][8];
    auto lds_group = [&](auto G) {
      constexpr int g = decltype(G)::value, c = g < U1_POS ? g : g - 1;
      if constexpr (g <= NCP) {
        cp_async_wait<NCP - g>();
        __syncwarp();
      } else {
        if (c == NCP) mbar_wait(bars + 8 * B_RAW0, 0);
        if (c == RSPLIT) mbar_wait(bars + 8 * B_RAW0 + 8, 0);
      }
#pragma unroll
      for (int i = 0; i < 8; i++)
        r[g & 1][i] = lds32(qbase + (g == U1_POS ? Q_UNIT : raw0 - sbase - SMEM_Q + c * Q_UNIT) + i * (BN * 4));
    };
    lds_group(IC<0>{});
    TL(6);
    static_for<0, 9>([&](auto G) {
      constexpr int g = decltype(G)::value, c = g < U1_POS ? g : g - 1;
      if (g == PUB_AT) {
        publish(1, 1);
        TL(3);
      }
      if (g == U1_POS) {
        emit_unit(convert_unit(r[g & 1], tab), 1);
        __syncwarp();
        TL(2);
        if constexpr (g < 8) lds_group(IC<g + 1>{});
      } else {
        if constexpr (g < 8) lds_group(IC<g + 1>{});
        sts128(sbase + SMEM_W + c * W_KC + (warp * 32 + lane) * 16,
               ((SHFL_MASK >> c) & 1) ? convert_unit(r[g & 1], lutv, sc) : convert_unit(r[g & 1], tab));
      }
    });
    asm volatile("fence.proxy.async.shared::cta;" ::: "memory");
    __syncwarp();
    arrive_one(bars + 8 * B_W0);
    if (PUB_AT == 9) {
      publish(1, 1);
      TL(3);
    }
    TL(4);
    if (wg == 1) {
      lds_unit(q, 2);
      emit_unit(convert_unit(q, tab), 2);
    }
    TL(5);
  }

  float acc0[112], acc1[112];
  constexpr uint32_t DA_HI = (1u << 30) | (1024 >> 4), DB_HI = (128 >> 4);
  const uint32_t da0 = ((1u << 16) | ((sbase + SMEM_X) >> 4)) + wg * (XS * X_SLICE >> 4);
  constexpr uint32_t db0 = ((W_KC >> 4) << 16) | ((sbase + SMEM_W) >> 4);
  const uint32_t fullx = bars + 8 * B_FULLX + wg * 64, done = bars + 8 * B_DONE + wg * 64;
  const bool x_issuer = (warp & 3) == 3;

  auto mma = [&](float (&acc)[112], int n, int kb, int k0, int k1) {
    const int wslot = kb == 15 ? 4 : (kb & 3);
    wgmma_fence();
#pragma unroll
    for (int k = k0; k < k1; k++)
      wgmma_m64n224k16(acc, make_desc(da0 + (n % XS) * (X_SLICE >> 4) + k * 2, DA_HI),
                       make_desc(db0 + wslot * (W_STAGE >> 4) + k * (2 * W_KC >> 4), DB_HI), kb != 0 || k != 0);
    wgmma_commit();
  };
  auto release = [&](int n) {
    arrive_one(ring(done, n));
    if (x_issuer) {
      ring_wait(done, n);
      const int m = n + 4;
      if (elect_one())
        load_x(wg, m, m < 2 * NR ? m >> 1 : end_kb((m - 2 * NR) % ENDK), m < 2 * NR ? m & 1 : (m - 2 * NR) / ENDK);
    }
  };
  auto end_slot = [&](int n) {
    wgmma_wait<1>();
    release(n);
  };
  auto slot = [&](float (&acc)[112], auto N) {
    constexpr int n = decltype(N)::value;
    constexpr bool hv = heavy(n), pub = heavy(n - 1);
    ring_wait(fullx, n);
    mma(acc, n, n >> 1, 0, 4);
    if (hv && warp < 7) dequant_lookup(q, lutv);
    end_slot(n);
    if (warp < 7) {
      constexpr int u = unit_at(n);
      if (pub) publish(u - 1, 1);
      if (n == 2) lds_unit(q, 4);
      if (hv) {
        constexpr int un = u + 1 < NKB ? u + 1 : u;
        dequant_finish(q, rb, w_ptr(u), sc, ring(bars + 8 * B_FULLQ, un), un >> 3, qbase + (un & 3) * Q_UNIT);
      }
    } else {
      constexpr int m = w_at(n), u = q_at(n), m_next = w_at(n + 1);
      if (m >= 0 || u >= 0) ring_wait(bars + 8 * B_DONE, n - 1);
      if (m >= 0) {
        ready |= __ballot_sync(0xffffffffu, rb >= FLAG_FULL);
        wait_ready(m);
        asm volatile("fence.proxy.async.global;" ::: "memory");
      }
      if (m_next >= 0) rb = ld_strong(fl);
      if ((m >= 0 || u >= 0 || n == 4 || n == 10) && elect_one()) {
        if (m >= 0)
          load_w(ring(bars + 8 * B_FULLW, m), (m == 15 ? 4 : m & 3) * W_STAGE, m * W_STAGE, W_STAGE);
        if (u >= 0) load_q(u);
        if (u >= 0 && u + 2 < NKB) prefetch_q(u + 2);
        if (n == 4 || n == 10) prefetch_x(n == 4 ? 2 : 3);
      }
    }
  };

  mbar_wait(bars + 8 * B_W0, 0);
  mbar_wait(fullx, 0);
  TL(8); TLG(46);
  mma(acc0, 0, 0, 0, 4);
  mbar_wait(fullx + 8, 0);
  TL(9);
  mma(acc1, 1, 0, 0, 4);
  if (wg == 0) lds_unit(q, 2);
  arrive_one(done);
  if (warp < 7) {
    if (wg == 0) {
      emit_unit(convert_unit(q, lutv, sc), 2);
    } else {
      publish(2, 1);
    }
    lds_unit(q, 3);
    const uint4 w3 = convert_unit(q, lutv, sc);
    if (wg == 0) publish(2, 1);
    st_strong128(w_ptr(3), w3);
    rb = ld_strong(w_ptr(3));
  } else if (warp == 7) {
    if (!Q5_EARLY && elect_one()) load_q(5);
    if (Q6_EARLY) {
      mbar_wait(bars + 8 * B_DONE, 0);
      mbar_wait(done, 0);
      if (elect_one()) load_q(6);
    }
  }
  end_slot(1);
  if (warp == 7) rb = ld_strong(fl);

  static_for<1, NR>([&](auto R) {
    constexpr int r = decltype(R)::value;
    ring_wait(bars + 8 * B_FULLW, r);
    TL(8 + 2 * r);
    slot(acc0, IC<2 * r>{});
    TL(9 + 2 * r);
    slot(acc1, IC<2 * r + 1>{});
  });

  __nv_bfloat16* op = out + (size_t)(xrow + (warp & 3) * 16 + (lane >> 2)) * F_DIM + j * BN + (lane & 3) * 8;
  TL(40); TLG(48);
  if (wg == 1) {
    wgmma_wait<0>();
    release(2 * NR);
    if (warp == 7) {
      wait_ready(14);
      asm volatile("fence.proxy.async.global;" ::: "memory");
      ring_wait(bars + 8 * B_DONE, 2 * NR);
      if (elect_one()) load_w(ring(bars + 8 * B_FULLW, 14), 2 * W_STAGE, 14 * W_STAGE, W_STAGE);
      unsigned old = 0;
      if (lane == 17) old = atomicAdd(fl, 1u);
      if (__shfl_sync(0xffffffffu, old, 17) == NI - 1) *fl = 0;
    }
    bar_sync(1, 256);
  }
#pragma unroll
  for (int e = 0; e < ENDK; e++) {
    ring_wait(bars + 8 * B_FULLW, end_kb(e));
    ring_wait(fullx, 2 * NR + e);
    mma(acc0, 2 * NR + e, end_kb(e), 0, 4);
    if (e == ENDK - 1) bar_arrive(1 + wg, 256);
    wgmma_wait<1>();
    if (e > 0 || wg == 0) release(2 * NR + e);
  }
  wgmma_wait<0>();
  release(2 * NR + ENDK);
  TL(41);
  auto delay_to = [&](unsigned t0, unsigned t) {
    while (__any_sync(0xffffffffu, clk32() - t0 < t)) {}
  };
  if (!SPLIT_END || wg == 0) {
    store_acc(acc0, op, 0, 7);
    TL(42);
    bar_sync(2 - wg, 256);
#pragma unroll
    for (int e = 0; e < ENDK; e++) {
      ring_wait(fullx, 2 * NR + ENDK + e);
      mma(acc1, 2 * NR + ENDK + e, end_kb(e), 0, 4);
    }
    if (wg == 0) bar_arrive(1, 256);
    wgmma_wait<0>();
    TL(43); TLG(47);
    store_acc(acc1, op + 64 * F_DIM, 0, 7);
  } else {
    uint32_t af[4 * ENDK][4];
    const uint32_t abase = sbase + SMEM_X + XS * X_SLICE + ((warp & 3) * 16 + (lane & 15)) * 128;
    float accp[112];
    const unsigned t0 = clk32();
#pragma unroll
    for (int J = 0; J < 7; J++) {
      if (J > 0) delay_to(t0, J * ST_GAP);
      store_acc(acc0, op, J, J + 1);
      if (J == 0) {
#pragma unroll
        for (int i = 0; i < 112; i++) asm volatile("add.rn.f32 %0, %1, 0f00000000;" : "=f"(accp[i]) : "f"(acc1[i]));
      }
      if (J >= 7 - ENDK - LD_SHIFT && J < 7 - LD_SHIFT) {
        const int e = J - (7 - ENDK - LD_SHIFT), n = 2 * NR + ENDK + e;
        ring_wait(fullx, n);
#pragma unroll
        for (int k = 0; k < 4; k++)
          asm volatile("ldmatrix.sync.aligned.m8n8.x4.shared.b16 {%0, %1, %2, %3}, [%4];"
                       : "=r"(af[4 * e + k][0]), "=r"(af[4 * e + k][1]), "=r"(af[4 * e + k][2]), "=r"(af[4 * e + k][3])
                       : "r"(abase + (n % XS) * X_SLICE + (((2 * k + (lane >> 4)) ^ (lane & 7)) << 4))
                       : "memory");
      }
    }
    TL(42);
    auto part = [&](auto P, int s0, int s1) {
      constexpr int p = decltype(P)::value;
      wgmma_fence();
#pragma unroll
      for (int st = s0; st < s1; st++) {
        const int kb = end_kb(st >> 2);
        const uint64_t db = make_desc(db0 + (kb == 15 ? 4 : kb & 3) * (W_STAGE >> 4) + (st & 3) * (2 * W_KC >> 4) +
                                          (p == 0 ? 0 : 32 + 64 * p), DB_HI);
        if constexpr (p == 0) wgmma_rs_m64n96k16<0>(accp, af[st], db);
        else wgmma_rs_m64n64k16<16 + 32 * p>(accp, af[st], db);
      }
      wgmma_commit();
    };
    bar_sync(1, 256);
    TL(51);
    part(IC<0>{}, 0, 4 * ENDK);
    part(IC<1>{}, 0, LEAD);
    wgmma_wait<1>();
    store_acc(accp, op + 64 * F_DIM, 0, 3);
    part(IC<1>{}, LEAD, 4 * ENDK);
    part(IC<2>{}, 0, LEAD);
    wgmma_wait<1>();
    store_acc(accp, op + 64 * F_DIM, 3, 5);
    part(IC<2>{}, LEAD, 4 * ENDK);
    wgmma_wait<0>();
    TL(43); TLG(47);
    store_acc(accp, op + 64 * F_DIM, 5, 7);
  }
  TL(44);
}

typedef CUresult (*EncodeTiledFn)(CUtensorMap*, CUtensorMapDataType, cuuint32_t, void*, const cuuint64_t*,
                                  const cuuint64_t*, const cuuint32_t*, const cuuint32_t*, CUtensorMapInterleave,
                                  CUtensorMapSwizzle, CUtensorMapL2promotion, CUtensorMapFloatOOBfill);

}

#define XPROMO CU_TENSOR_MAP_L2_PROMOTION_L2_128B
extern "C" void kernel_launch(void* const* d_in, const int* in_sizes, int n_in, void* d_out, int out_size) {
  const __nv_bfloat16* x = (const __nv_bfloat16*)d_in[0];
  const int* qw = (const int*)d_in[1];
  const __nv_bfloat16* lut = (const __nv_bfloat16*)d_in[2];
  const __nv_bfloat16* scales = (const __nv_bfloat16*)d_in[3];
  __nv_bfloat16* out = (__nv_bfloat16*)d_out;

  static EncodeTiledFn enc = nullptr;
  static uint8_t* p_scr = nullptr;
  if (!enc) {
    void* fn = nullptr;
    cudaDriverEntryPointQueryResult qr;
    cudaGetDriverEntryPoint("cuTensorMapEncodeTiled", &fn, cudaEnableDefault, &qr);
    enc = (EncodeTiledFn)fn;
    void* p = nullptr;
    cudaGetSymbolAddress(&p, g_scratch);
    p_scr = (uint8_t*)(((uintptr_t)p + REGION - 1) & ~(uintptr_t)(REGION - 1));
    cudaFuncSetAttribute(fused_kernel, cudaFuncAttributeMaxDynamicSharedMemorySize, SMEM_TOTAL);
  }
  CUtensorMap tm_x, tm_q;
  cuuint32_t estr[2] = {1, 1};
  {
    cuuint64_t gdim[2] = {(cuuint64_t)D_DIM, (cuuint64_t)S_DIM};
    cuuint64_t gstr[1] = {(cuuint64_t)D_DIM * 2};
    cuuint32_t box[2] = {(cuuint32_t)BK, 64};
    enc(&tm_x, CU_TENSOR_MAP_DATA_TYPE_BFLOAT16, 2, (void*)x, gdim, gstr, box, estr, CU_TENSOR_MAP_INTERLEAVE_NONE,
        CU_TENSOR_MAP_SWIZZLE_128B, XPROMO, CU_TENSOR_MAP_FLOAT_OOB_FILL_NONE);
  }
  {
    cuuint64_t gdim[2] = {(cuuint64_t)F_DIM, (cuuint64_t)D_DIM};
    cuuint64_t gstr[1] = {(cuuint64_t)F_DIM * 4};
    cuuint32_t box[2] = {(cuuint32_t)BN, 8};
    enc(&tm_q, CU_TENSOR_MAP_DATA_TYPE_INT32, 2, (void*)qw, gdim, gstr, box, estr, CU_TENSOR_MAP_INTERLEAVE_NONE,
        CU_TENSOR_MAP_SWIZZLE_NONE, CU_TENSOR_MAP_L2_PROMOTION_NONE, CU_TENSOR_MAP_FLOAT_OOB_FILL_NONE);
  }
  fused_kernel<<<NI * NJ, 256, SMEM_TOTAL, cudaStreamPerThread>>>(qw, lut, scales, out, p_scr, tm_x, tm_q);
}
```

```cpp
#include <cuda_runtime.h>
#include <cuda_bf16.h>
#include <cuda.h>
#include <stdint.h>

namespace {

constexpr int S_DIM = 2048, D_DIM = 1024, F_DIM = 3584;
constexpr int BM = 256, BN = 224, BK = 64;
constexpr int NKB = D_DIM / BK;
constexpr int NJ = F_DIM / BN;
constexpr int NI = S_DIM / BM;
constexpr int WS = 4;
constexpr int XS = 5;
constexpr int ENDK = 5;
constexpr int NR = NKB - ENDK;
constexpr int X_SLICE = 64 * BK * 2;
constexpr int W_STAGE = BN * BK * 2;
constexpr int W_KC = BN * 16;

constexpr int REGION = 512 * 1024;
__device__ uint4 g_scratch[(NJ + 1) * REGION / 16];

__device__ __forceinline__ uint32_t smem_u32(const void* p) { return (uint32_t)__cvta_generic_to_shared(p); }
__device__ __forceinline__ unsigned clk32() {
  unsigned c;
  asm volatile("mov.u32 %0, %%clock;" : "=r"(c)::"memory");
  return c;
}
__device__ __forceinline__ bool elect_one() {
  uint32_t p;
  asm volatile("{\n.reg .pred P;\nelect.sync _|P, 0xffffffff;\nselp.b32 %0, 1, 0, P;\n}" : "=r"(p));
  return p != 0;
}
__device__ __forceinline__ void mbar_init(uint32_t bar, uint32_t cnt) {
  asm volatile("mbarrier.init.shared::cta.b64 [%0], %1;" ::"r"(bar), "r"(cnt) : "memory");
}
__device__ __forceinline__ void mbar_expect_tx(uint32_t bar, uint32_t bytes) {
  asm volatile("mbarrier.arrive.expect_tx.shared::cta.b64 _, [%0], %1;" ::"r"(bar), "r"(bytes) : "memory");
}
__device__ __forceinline__ void mbar_arrive(uint32_t bar) {
  asm volatile("mbarrier.arrive.shared::cta.b64 _, [%0];" ::"r"(bar) : "memory");
}
__device__ __forceinline__ void mbar_wait(uint32_t bar, uint32_t parity) {
  asm volatile(
      "{\n.reg .pred p;\n"
      "LAB_WAIT:\n"
      "mbarrier.try_wait.parity.shared::cta.b64 p, [%0], %1;\n"
      "@p bra LAB_DONE;\n"
      "bra LAB_WAIT;\n"
      "LAB_DONE:\n}\n" ::"r"(bar), "r"(parity) : "memory");
}
template <int N>
__device__ __forceinline__ uint32_t ring(uint32_t base, int i) { return base + 8 * (i % N); }
template <int N>
__device__ __forceinline__ void ring_wait(uint32_t base, int i) { mbar_wait(ring<N>(base, i), (i / N) & 1); }
__device__ __forceinline__ void tma_load_2d(uint32_t dst, const CUtensorMap* tm, int c0, int c1, uint32_t bar) {
  asm volatile(
      "cp.async.bulk.tensor.2d.shared::cluster.global.mbarrier::complete_tx::bytes [%0], [%1, {%3, %4}], [%2];"
      ::"r"(dst), "l"(tm), "r"(bar), "r"(c0), "r"(c1) : "memory");
}
__device__ __forceinline__ void bulk_load(uint32_t dst, const void* src, uint32_t bytes, uint32_t bar) {
  asm volatile(
      "cp.async.bulk.shared::cluster.global.mbarrier::complete_tx::bytes [%0], [%1], %2, [%3];"
      ::"r"(dst), "l"(src), "r"(bytes), "r"(bar) : "memory");
}
__device__ __forceinline__ void cp_async16(uint32_t dst, const void* src) {
  asm volatile("cp.async.cg.shared.global [%0], [%1], 16;" ::"r"(dst), "l"(src) : "memory");
}
__device__ __forceinline__ void cp_async_commit() { asm volatile("cp.async.commit_group;" ::: "memory"); }
template <int N>
__device__ __forceinline__ void cp_async_wait() { asm volatile("cp.async.wait_group %0;" ::"n"(N) : "memory"); }
__device__ __forceinline__ uint32_t ldg_u16(const void* p) {
  uint32_t v;
  asm volatile("ld.global.u16 %0, [%1];" : "=r"(v) : "l"(p) : "memory");
  return v;
}
__device__ __forceinline__ int lds32(uint32_t addr) {
  int v;
  asm volatile("ld.shared.b32 %0, [%1];" : "=r"(v) : "r"(addr) : "memory");
  return v;
}
__device__ __forceinline__ void sts128(uint32_t addr, uint4 v) {
  asm volatile("st.shared.v4.u32 [%0], {%1, %2, %3, %4};" ::"r"(addr), "r"(v.x), "r"(v.y), "r"(v.z), "r"(v.w) : "memory");
}
__device__ __forceinline__ uint64_t make_desc(uint32_t lo, uint32_t hi) {
  uint64_t d;
  asm("mov.b64 %0, {%1, %2};" : "=l"(d) : "r"(lo), "r"(hi));
  return d;
}
__device__ __forceinline__ unsigned ld_strong(const void* p) {
  unsigned v;
  asm volatile("ld.relaxed.gpu.global.u32 %0, [%1];" : "=r"(v) : "l"(p) : "memory");
  return v;
}
__device__ __forceinline__ void st_strong128(void* p, uint4 v) {
  asm volatile("st.relaxed.gpu.global.v4.u32 [%0], {%1, %2, %3, %4};" ::"l"(p), "r"(v.x), "r"(v.y), "r"(v.z), "r"(v.w)
               : "memory");
}
__device__ __forceinline__ void wgmma_fence() { asm volatile("wgmma.fence.sync.aligned;" ::: "memory"); }
__device__ __forceinline__ void wgmma_commit() { asm volatile("wgmma.commit_group.sync.aligned;" ::: "memory"); }
template <int N>
__device__ __forceinline__ void wgmma_wait() { asm volatile("wgmma.wait_group.sync.aligned %0;" ::"n"(N) : "memory"); }
__device__ __forceinline__ void bar_sync(int id, int n) { asm volatile("bar.sync %0, %1;" ::"r"(id), "r"(n) : "memory"); }
__device__ __forceinline__ void bar_arrive(int id, int n) { asm volatile("bar.arrive %0, %1;" ::"r"(id), "r"(n) : "memory"); }

__device__ __forceinline__ void wgmma_m64n224k16(float (&d)[112], uint64_t da, uint64_t db, int scale_d) {
  asm volatile(
    "{\n.reg .pred p;\nsetp.ne.b32 p, %114, 0;\n"
    "wgmma.mma_async.sync.aligned.m64n224k16.f32.bf16.bf16 "
    "{%0, %1, %2, %3, %4, %5, %6, %7, %8, %9, %10, %11, %12, %13, %14, %15, "
    "%16, %17, %18, %19, %20, %21, %22, %23, %24, %25, %26, %27, %28, %29, %30, %31, "
    "%32, %33, %34, %35, %36, %37, %38, %39, %40, %41, %42, %43, %44, %45, %46, %47, "
    "%48, %49, %50, %51, %52, %53, %54, %55, %56, %57, %58, %59, %60, %61, %62, %63, "
    "%64, %65, %66, %67, %68, %69, %70, %71, %72, %73, %74, %75, %76, %77, %78, %79, "
    "%80, %81, %82, %83, %84, %85, %86, %87, %88, %89, %90, %91, %92, %93, %94, %95, "
    "%96, %97, %98, %99, %100, %101, %102, %103, %104, %105, %106, %107, %108, %109, %110, %111}, "
    "%112, %113, p, 1, 1, 0, 0;\n}\n"
    : "+f"(d[0]), "+f"(d[1]), "+f"(d[2]), "+f"(d[3]), "+f"(d[4]), "+f"(d[5]), "+f"(d[6]), "+f"(d[7]),
      "+f"(d[8]), "+f"(d[9]), "+f"(d[10]), "+f"(d[11]), "+f"(d[12]), "+f"(d[13]), "+f"(d[14]), "+f"(d[15]),
      "+f"(d[16]), "+f"(d[17]), "+f"(d[18]), "+f"(d[19]), "+f"(d[20]), "+f"(d[21]), "+f"(d[22]), "+f"(d[23]),
      "+f"(d[24]), "+f"(d[25]), "+f"(d[26]), "+f"(d[27]), "+f"(d[28]), "+f"(d[29]), "+f"(d[30]), "+f"(d[31]),
      "+f"(d[32]), "+f"(d[33]), "+f"(d[34]), "+f"(d[35]), "+f"(d[36]), "+f"(d[37]), "+f"(d[38]), "+f"(d[39]),
      "+f"(d[40]), "+f"(d[41]), "+f"(d[42]), "+f"(d[43]), "+f"(d[44]), "+f"(d[45]), "+f"(d[46]), "+f"(d[47]),
      "+f"(d[48]), "+f"(d[49]), "+f"(d[50]), "+f"(d[51]), "+f"(d[52]), "+f"(d[53]), "+f"(d[54]), "+f"(d[55]),
      "+f"(d[56]), "+f"(d[57]), "+f"(d[58]), "+f"(d[59]), "+f"(d[60]), "+f"(d[61]), "+f"(d[62]), "+f"(d[63]),
      "+f"(d[64]), "+f"(d[65]), "+f"(d[66]), "+f"(d[67]), "+f"(d[68]), "+f"(d[69]), "+f"(d[70]), "+f"(d[71]),
      "+f"(d[72]), "+f"(d[73]), "+f"(d[74]), "+f"(d[75]), "+f"(d[76]), "+f"(d[77]), "+f"(d[78]), "+f"(d[79]),
      "+f"(d[80]), "+f"(d[81]), "+f"(d[82]), "+f"(d[83]), "+f"(d[84]), "+f"(d[85]), "+f"(d[86]), "+f"(d[87]),
      "+f"(d[88]), "+f"(d[89]), "+f"(d[90]), "+f"(d[91]), "+f"(d[92]), "+f"(d[93]), "+f"(d[94]), "+f"(d[95]),
      "+f"(d[96]), "+f"(d[97]), "+f"(d[98]), "+f"(d[99]), "+f"(d[100]), "+f"(d[101]), "+f"(d[102]), "+f"(d[103]),
      "+f"(d[104]), "+f"(d[105]), "+f"(d[106]), "+f"(d[107]), "+f"(d[108]), "+f"(d[109]), "+f"(d[110]), "+f"(d[111])
    : "l"(da), "l"(db), "r"(scale_d));
}
template <int O>
__device__ __forceinline__ void wgmma_rs_m64n96k16(float (&d)[112], const uint32_t (&a)[4], uint64_t db) {
  asm volatile(
    "wgmma.mma_async.sync.aligned.m64n96k16.f32.bf16.bf16 "
    "{%0, %1, %2, %3, %4, %5, %6, %7, %8, %9, %10, %11, %12, %13, %14, %15, "
    "%16, %17, %18, %19, %20, %21, %22, %23, %24, %25, %26, %27, %28, %29, %30, %31, "
    "%32, %33, %34, %35, %36, %37, %38, %39, %40, %41, %42, %43, %44, %45, %46, %47}, "
    "{%48, %49, %50, %51}, %52, 1, 1, 1, 0;\n"
    : "+f"(d[O + 0]), "+f"(d[O + 1]), "+f"(d[O + 2]), "+f"(d[O + 3]),
      "+f"(d[O + 4]), "+f"(d[O + 5]), "+f"(d[O + 6]), "+f"(d[O + 7]),
      "+f"(d[O + 8]), "+f"(d[O + 9]), "+f"(d[O + 10]), "+f"(d[O + 11]),
      "+f"(d[O + 12]), "+f"(d[O + 13]), "+f"(d[O + 14]), "+f"(d[O + 15]),
      "+f"(d[O + 16]), "+f"(d[O + 17]), "+f"(d[O + 18]), "+f"(d[O + 19]),
      "+f"(d[O + 20]), "+f"(d[O + 21]), "+f"(d[O + 22]), "+f"(d[O + 23]),
      "+f"(d[O + 24]), "+f"(d[O + 25]), "+f"(d[O + 26]), "+f"(d[O + 27]),
      "+f"(d[O + 28]), "+f"(d[O + 29]), "+f"(d[O + 30]), "+f"(d[O + 31]),
      "+f"(d[O + 32]), "+f"(d[O + 33]), "+f"(d[O + 34]), "+f"(d[O + 35]),
      "+f"(d[O + 36]), "+f"(d[O + 37]), "+f"(d[O + 38]), "+f"(d[O + 39]),
      "+f"(d[O + 40]), "+f"(d[O + 41]), "+f"(d[O + 42]), "+f"(d[O + 43]),
      "+f"(d[O + 44]), "+f"(d[O + 45]), "+f"(d[O + 46]), "+f"(d[O + 47])
    : "r"(a[0]), "r"(a[1]), "r"(a[2]), "r"(a[3]), "l"(db));
}
template <int O>
__device__ __forceinline__ void wgmma_rs_m64n64k16(float (&d)[112], const uint32_t (&a)[4], uint64_t db) {
  asm volatile(
    "wgmma.mma_async.sync.aligned.m64n64k16.f32.bf16.bf16 "
    "{%0, %1, %2, %3, %4, %5, %6, %7, %8, %9, %10, %11, %12, %13, %14, %15, "
    "%16, %17, %18, %19, %20, %21, %22, %23, %24, %25, %26, %27, %28, %29, %30, %31}, "
    "{%32, %33, %34, %35}, %36, 1, 1, 1, 0;\n"
    : "+f"(d[O + 0]), "+f"(d[O + 1]), "+f"(d[O + 2]), "+f"(d[O + 3]),
      "+f"(d[O + 4]), "+f"(d[O + 5]), "+f"(d[O + 6]), "+f"(d[O + 7]),
      "+f"(d[O + 8]), "+f"(d[O + 9]), "+f"(d[O + 10]), "+f"(d[O + 11]),
      "+f"(d[O + 12]), "+f"(d[O + 13]), "+f"(d[O + 14]), "+f"(d[O + 15]),
      "+f"(d[O + 16]), "+f"(d[O + 17]), "+f"(d[O + 18]), "+f"(d[O + 19]),
      "+f"(d[O + 20]), "+f"(d[O + 21]), "+f"(d[O + 22]), "+f"(d[O + 23]),
      "+f"(d[O + 24]), "+f"(d[O + 25]), "+f"(d[O + 26]), "+f"(d[O + 27]),
      "+f"(d[O + 28]), "+f"(d[O + 29]), "+f"(d[O + 30]), "+f"(d[O + 31])
    : "r"(a[0]), "r"(a[1]), "r"(a[2]), "r"(a[3]), "l"(db));
}

__device__ __forceinline__ uint32_t pack_bf16(float lo, float hi) {
  uint32_t r;
  asm("cvt.rn.bf16x2.f32 %0, %1, %2;" : "=r"(r) : "f"(hi), "f"(lo));
  return r;
}

__device__ __forceinline__ int perm32(int n) { return (n & ~30) | ((n & 6) << 2) | ((n >> 2) & 6); }

constexpr int SMEM_X = 0;
constexpr int SMEM_W = 2 * XS * X_SLICE;
constexpr int SMEM_Q = SMEM_W + WS * W_STAGE;
constexpr int Q_UNIT = 8 * BN * 4;
constexpr int SMEM_BAR = SMEM_Q + W_STAGE;
constexpr int B_FULLW = 0, B_FULLQ = 5, B_FULLX = 9, B_DONE = 19, B_W0 = 35, B_RAW0 = 36;
constexpr int SMEM_TL = SMEM_BAR + 512;
constexpr int SMEM_TOTAL = SMEM_TL;
constexpr int W_OFF = 128;
constexpr unsigned FLAG_FULL = NI * 7;

#define TL(i)
#define TLG(i)

__device__ __forceinline__ void store_acc(const float (&a)[112], __nv_bfloat16* p, int J0, int J1) {
#pragma unroll
  for (int J = J0; J < J1; J++) {
    uint4 v0, v1;
    v0.x = pack_bf16(a[16 * J + 0], a[16 * J + 1]);
    v0.y = pack_bf16(a[16 * J + 4], a[16 * J + 5]);
    v0.z = pack_bf16(a[16 * J + 8], a[16 * J + 9]);
    v0.w = pack_bf16(a[16 * J + 12], a[16 * J + 13]);
    v1.x = pack_bf16(a[16 * J + 2], a[16 * J + 3]);
    v1.y = pack_bf16(a[16 * J + 6], a[16 * J + 7]);
    v1.z = pack_bf16(a[16 * J + 10], a[16 * J + 11]);
    v1.w = pack_bf16(a[16 * J + 14], a[16 * J + 15]);
    *reinterpret_cast<uint4*>(p + 32 * J) = v0;
    *reinterpret_cast<uint4*>(p + 8 * F_DIM + 32 * J) = v1;
  }
}

__device__ __forceinline__ uint4 convert_unit(const int (&q)[8], float lutv, float sc) {
  float v[8];
#pragma unroll
  for (int i = 0; i < 8; i++) v[i] = __shfl_sync(0xffffffffu, lutv, q[i]) * sc;
  uint4 o;
  o.x = pack_bf16(v[0], v[1]);
  o.y = pack_bf16(v[2], v[3]);
  o.z = pack_bf16(v[4], v[5]);
  o.w = pack_bf16(v[6], v[7]);
  return o;
}

struct Table {
  uint32_t lo[4], hi[4];
};
__device__ __forceinline__ uint32_t prmt(uint32_t a, uint32_t b, uint32_t s) {
  uint32_t r;
  asm("prmt.b32 %0, %1, %2, %3;" : "=r"(r) : "r"(a), "r"(b), "r"(s));
  return r;
}
__device__ __forceinline__ Table make_table(float lutv, float sc) {
  Table t;
#pragma unroll
  for (int i = 0; i < 4; i++) {
    const uint32_t a = pack_bf16(__shfl_sync(0xffffffffu, lutv, 4 * i) * sc, __shfl_sync(0xffffffffu, lutv, 4 * i + 1) * sc);
    const uint32_t b =
        pack_bf16(__shfl_sync(0xffffffffu, lutv, 4 * i + 2) * sc, __shfl_sync(0xffffffffu, lutv, 4 * i + 3) * sc);
    t.lo[i] = prmt(a, b, 0x6420);
    t.hi[i] = prmt(a, b, 0x7531);
  }
  return t;
}
__device__ __forceinline__ uint4 convert_unit(const int (&q)[8], const Table& t) {
  const uint32_t all = ((q[7] * 16 + q[6]) * 256 + (q[5] * 16 + q[4])) * 65536 + ((q[3] * 16 + q[2]) * 256 + (q[1] * 16 + q[0]));
  const uint32_t s7 = all & 0x77777777u;
  const uint32_t s2 = ((all >> 1) & 0x44444444u) | 0x32103210u;
  uint32_t o[4];
#pragma unroll
  for (int h = 0; h < 2; h++) {
    const uint32_t a = h ? s7 >> 16 : s7, b = h ? s2 >> 16 : s2;
    const uint32_t lo = prmt(prmt(t.lo[0], t.lo[1], a), prmt(t.lo[2], t.lo[3], a), b);
    const uint32_t hi = prmt(prmt(t.hi[0], t.hi[1], a), prmt(t.hi[2], t.hi[3], a), b);
    o[2 * h] = prmt(lo, hi, 0x5140);
    o[2 * h + 1] = prmt(lo, hi, 0x7362);
  }
  return make_uint4(o[0], o[1], o[2], o[3]);
}

__device__ __forceinline__ void dequant_lookup(int (&q)[8], float lutv) {
  asm volatile(
      "shfl.sync.idx.b32 %0, %8, %0, 31, 0xffffffff;\n"
      "shfl.sync.idx.b32 %1, %8, %1, 31, 0xffffffff;\n"
      "shfl.sync.idx.b32 %2, %8, %2, 31, 0xffffffff;\n"
      "shfl.sync.idx.b32 %3, %8, %3, 31, 0xffffffff;\n"
      "shfl.sync.idx.b32 %4, %8, %4, 31, 0xffffffff;\n"
      "shfl.sync.idx.b32 %5, %8, %5, 31, 0xffffffff;\n"
      "shfl.sync.idx.b32 %6, %8, %6, 31, 0xffffffff;\n"
      "shfl.sync.idx.b32 %7, %8, %7, 31, 0xffffffff;\n"
      : "+r"(q[0]), "+r"(q[1]), "+r"(q[2]), "+r"(q[3]), "+r"(q[4]), "+r"(q[5]), "+r"(q[6]), "+r"(q[7])
      : "r"(__float_as_int(lutv)));
}
__device__ __forceinline__ void dequant_finish(int (&q)[8], unsigned& rb, uint4* wp, float sc, uint32_t qbar,
                                               uint32_t qpar, uint32_t qaddr) {
  asm volatile(
      "{\n.reg .pred W;\n.reg .b32 o0, o1, o2, o3;\n"
      "DQ_WAIT:\n"
      "mbarrier.try_wait.parity.shared::cta.b64 W, [%11], %13;\n"
      "@!W bra DQ_WAIT;\n"
      "mul.rn.f32 %0, %0, %10;\nmul.rn.f32 %1, %1, %10;\nmul.rn.f32 %2, %2, %10;\nmul.rn.f32 %3, %3, %10;\n"
      "mul.rn.f32 %4, %4, %10;\nmul.rn.f32 %5, %5, %10;\nmul.rn.f32 %6, %6, %10;\nmul.rn.f32 %7, %7, %10;\n"
      "cvt.rn.bf16x2.f32 o0, %1, %0;\ncvt.rn.bf16x2.f32 o1, %3, %2;\n"
      "cvt.rn.bf16x2.f32 o2, %5, %4;\ncvt.rn.bf16x2.f32 o3, %7, %6;\n"
      "ld.volatile.shared.b32 %0, [%12];\nld.volatile.shared.b32 %1, [%12+896];\n"
      "ld.volatile.shared.b32 %2, [%12+1792];\nld.volatile.shared.b32 %3, [%12+2688];\n"
      "ld.volatile.shared.b32 %4, [%12+3584];\nld.volatile.shared.b32 %5, [%12+4480];\n"
      "ld.volatile.shared.b32 %6, [%12+5376];\nld.volatile.shared.b32 %7, [%12+6272];\n"
      "st.relaxed.gpu.global.v4.u32 [%9], {o0, o1, o2, o3};\n"
      "ld.relaxed.gpu.global.u32 %8, [%9];\n}\n"
      : "+r"(q[0]), "+r"(q[1]), "+r"(q[2]), "+r"(q[3]), "+r"(q[4]), "+r"(q[5]), "+r"(q[6]), "+r"(q[7]), "=r"(rb)
      : "l"(wp), "r"(__float_as_int(sc)), "r"(qbar), "r"(qaddr), "r"(qpar)
      : "memory");
}

constexpr int PU = 3;
#define HEAVY 0x3BBBAu
__host__ __device__ constexpr int popc(unsigned v) { return v ? (v & 1) + popc(v >> 1) : 0; }
__host__ __device__ constexpr bool heavy(int n) { return n >= 0 && ((HEAVY >> n) & 1); }
__host__ __device__ constexpr int unit_at(int n) { return PU + popc(HEAVY & ((1u << n) - 1)); }
__host__ __device__ constexpr int emit_slot(int u) {
  if (u < PU) return -1;
  for (int n = 0; n < 24; n++)
    if (heavy(n) && unit_at(n) == u) return n;
  return 99;
}
__host__ __device__ constexpr int end_kb(int e) { return e < 3 ? NR + e : NR + 7 - e; }
__host__ __device__ constexpr int w_ring(int m) { return m == 15 ? 4 : m & 3; }
__host__ __device__ constexpr int cmax(int a, int b) { return a > b ? a : b; }
__host__ __device__ constexpr int w_slot(int m) {
  return m == 15 ? cmax(emit_slot(15) + 3, 20) : cmax(2 * m - 5, emit_slot(m) + 3);
}
__host__ __device__ constexpr int q_slot(int u) {
  return u == 5 ? 1 : cmax(q_slot(u - 1) + 1, u < 8 ? 2 : u == 8 ? 4 : emit_slot(u - 5) + 2);
}
__host__ __device__ constexpr int w_at(int n) {
  for (int m = 2; m < NKB; m++)
    if (w_slot(m) == n) return m;
  return -1;
}
__host__ __device__ constexpr int q_at(int n) {
  for (int u = 5; u < NKB; u++)
    if (q_slot(u) == n) return u;
  return -1;
}
constexpr bool schedule_ok() {
  if (popc(HEAVY) != NKB - PU || (HEAVY & 7) != 2 || (HEAVY >> 20)) return false;
  for (int m = 2; m < NKB; m++) {
    if (w_at(w_slot(m)) != m || (m != 14 && w_slot(m) >= 2 * NR)) return false;
    if (m < NR && w_slot(m) > 2 * m - 2) return false;
  }
  for (int u = 5; u < NKB; u++)
    if (q_slot(u) + 2 > emit_slot(u - 1)) return false;
  return true;
}
static_assert(schedule_ok(), "bad schedule");
template <int V>
struct IC {
  static constexpr int value = V;
};
template <int I, int N, class F>
__device__ __forceinline__ void static_for(F&& f) {
  if constexpr (I < N) {
    f(IC<I>{});
    static_for<I + 1, N>(f);
  }
}

#define NCP 3
#define RSPLIT 5
#define STAG_L 70
#define PACE_INIT 650
#define PACE_X 1100
#define PACE_Q2 1600
#define PACE_Q3 2100
#define PUB_AT 6
#define ST_GAP 170
#define LEAD 8

constexpr uint32_t sbase = 1024;

__global__ void __launch_bounds__(256, 1)
fused_kernel(const int* __restrict__ qw, const __nv_bfloat16* __restrict__ lut,
             const __nv_bfloat16* __restrict__ scales, __nv_bfloat16* __restrict__ out, uint8_t* scratch,
             unsigned flag_full,
             const __grid_constant__ CUtensorMap tm_x, const __grid_constant__ CUtensorMap tm_q) {
  extern __shared__ __align__(1024) uint8_t smem_raw[];
  constexpr uint32_t bars = sbase + SMEM_BAR;
  const int j = blockIdx.x >> 3, it = blockIdx.x & 7;
  constexpr uint32_t raw0 = sbase + SMEM_W + 2 * W_STAGE;
  uint32_t lut_raw = 0, sc_raw = 0;
  if (threadIdx.x < 224) {
    const unsigned t = threadIdx.x, row0 = (t >> 3) & 3, col = (t & ~31u) + (t & 7) * 4;
    const int* src = qw + (row0 * F_DIM + j * BN + col);
    const uint32_t dst = row0 * (BN * 4) + col * 4;
    lut_raw = ldg_u16(lut + (t & 15));
    sc_raw = ldg_u16(scales + (j * BN + perm32(t)));
    __syncwarp();
#pragma unroll
    for (int g = 0; g < NCP + 1; g++) {
      const unsigned row = g == 0 ? BK + it * 8 : (g - 1) * 8;
      const uint32_t d = dst + (g == 0 ? sbase + SMEM_Q + Q_UNIT : raw0 + (g - 1) * Q_UNIT);
      cp_async16(d, src + row * F_DIM);
      cp_async16(d + 4 * BN * 4, src + (row + 4) * F_DIM);
      cp_async_commit();
    }
  }
  const int warp = __shfl_sync(0xffffffffu, threadIdx.x >> 5, 0);
  const int wg = warp >> 2;
  int lane;
  asm volatile("mov.u32 %0, %%laneid;" : "=r"(lane));
  const unsigned t_start = clk32();
  auto pace = [&](unsigned t) {
    while (__any_sync(0xffffffffu, clk32() - t_start < t)) {}
  };

  uint8_t* const region = scratch + (size_t)j * REGION;
  uint8_t* const wp = region + W_OFF + it * W_KC + (warp * 32 + lane) * 16;
  unsigned* const fl = reinterpret_cast<unsigned*>(region) + lane;
  float lutv, sc;
  unsigned rb;
  const int xrow = it * BM + wg * 128;

  auto w_ptr = [&](int u) { return reinterpret_cast<uint4*>(wp + u * W_STAGE); };
  auto emit_unit = [&](uint4 w, int u) {
    st_strong128(w_ptr(u), w);
    rb = ld_strong(w_ptr(u));
  };
  auto publish = [&](int u) {
    asm volatile(
        "{\n.reg .pred P, Q;\n"
        "setp.ne.u32 P, %1, 0xffffffff;\n"
        "vote.sync.all.pred P, P, 0xffffffff;\n"
        "setp.eq.and.s32 Q, %2, %3, P;\n"
        "@Q red.relaxed.gpu.global.add.u32 [%0], 1;\n}"
        ::"l"(fl), "r"(rb), "r"(lane), "r"(u) : "memory");
  };
  auto load_x = [&](int g, int n, int kb, int half) {
    const uint32_t bar = ring<XS>(bars + 8 * B_FULLX, n) + g * (8 * XS);
    mbar_expect_tx(bar, X_SLICE);
    tma_load_2d(sbase + SMEM_X + (n % XS) * X_SLICE + g * (XS * X_SLICE), &tm_x, kb * BK,
                it * BM + g * 128 + half * 64, bar);
  };
  auto load_q = [&](int u) {
    const uint32_t bar = ring<4>(bars + 8 * B_FULLQ, u);
    mbar_expect_tx(bar, Q_UNIT);
    tma_load_2d(sbase + SMEM_Q + (u & 3) * Q_UNIT, &tm_q, j * BN, u * BK + it * 8, bar);
  };

  unsigned ready = 0;
  auto load_w = [&](int m) {
    const uint32_t bar = bars + 8 * (B_FULLW + w_ring(m));
    mbar_expect_tx(bar, W_STAGE);
    bulk_load(sbase + SMEM_W + w_ring(m) * W_STAGE, region + W_OFF + m * W_STAGE, W_STAGE, bar);
  };
  auto wait_w = [&](int m) { mbar_wait(bars + 8 * (B_FULLW + w_ring(m)), m == 15 ? 0 : (m >> 2) & 1); };
  auto poll = [&]() { ready |= __ballot_sync(0xffffffffu, ld_strong(fl) >= flag_full); };
  auto wait_ready = [&](int kb) {
    int spins = 0;
    while (!((ready >> kb) & 1)) {
      poll();
      if (++spins > (1 << 22)) __trap();
    }
  };

  uint32_t qbase;
  asm volatile("mov.u32 %0, %1;" : "=r"(qbase) : "r"(sbase + SMEM_Q + warp * 128 + perm32(lane) * 4));
  auto lds_unit = [&](int (&q)[8], int u) {
    ring_wait<4>(bars + 8 * B_FULLQ, u);
#pragma unroll
    for (int i = 0; i < 8; i++) q[i] = lds32(qbase + (u & 3) * Q_UNIT + i * (BN * 4));
  };
  auto arrive_one = [&](uint32_t bar) {
    asm volatile("{\n.reg .pred P;\nelect.sync _|P, 0xffffffff;\n@P mbarrier.arrive.shared::cta.b64 _, [%0];\n}"
                 ::"r"(bar) : "memory");
  };

  int q[8];
  if (warp == 7) {
    if (elect_one()) {
      mbar_init(bars + 8 * B_RAW0, RSPLIT - NCP);
      mbar_init(bars + 8 * B_RAW0 + 8, 8 - RSPLIT);
      asm volatile("fence.mbarrier_init.release.cluster;" ::: "memory");
    }
    __syncwarp();
    bar_arrive(4, (9 - NCP) * 32);
    if (elect_one()) {
      asm volatile("prefetch.tensormap [%0];" ::"l"(&tm_x) : "memory");
      asm volatile("prefetch.tensormap [%0];" ::"l"(&tm_q) : "memory");
    }
    TL(5);
    pace(PACE_INIT);
    if (elect_one()) {
#pragma unroll
      for (int i = 0; i < B_RAW0; i++) mbar_init(bars + 8 * i, i == B_W0 ? 7 : i >= B_DONE ? 4 : 1);
      asm volatile("fence.mbarrier_init.release.cluster;" ::: "memory");
    }
    __syncwarp();
    rb = ld_strong(fl);
    bar_arrive(0, 256);
    TL(4);
    lutv = 0.f;
    sc = 0.f;
    if (smem_u32(smem_raw) != sbase) __trap();
    if (elect_one()) {
      mbar_arrive(bars + 8 * B_FULLW);
      mbar_arrive(bars + 8 * B_FULLQ);
      mbar_arrive(bars + 8 * B_FULLQ + 8);
    }
    pace(PACE_X);
    if (elect_one()) {
      load_x(0, 0, 0, 0); load_x(1, 0, 0, 0); load_x(0, 1, 0, 1); load_x(1, 1, 0, 1);
    }
    pace(PACE_Q2);
    if (elect_one()) load_q(2);
    pace(PACE_Q3);
    ready = __ballot_sync(0xffffffffu, rb >= flag_full);
    rb = ld_strong(fl);
    if (elect_one()) {
      load_q(3);
      load_x(0, 2, 1, 0); load_x(1, 2, 1, 0); load_x(0, 3, 1, 1); load_x(1, 3, 1, 1);
    }
    ready |= __ballot_sync(0xffffffffu, rb >= flag_full);
    wait_ready(1);
    asm volatile("fence.proxy.async.global;" ::: "memory");
    if (elect_one()) {
      load_w(1);
      load_q(4);
      load_x(0, 4, 2, 0); load_x(1, 4, 2, 0);
    }
    TL(2);
    TL(3);
  } else {
    if (warp + NCP < 8) {
      bar_sync(4, (9 - NCP) * 32);
      pace(warp * STAG_L);
      if (elect_one()) {
        const int c = warp + NCP;
        const uint32_t bar = bars + 8 * B_RAW0 + (c < RSPLIT ? 0 : 8);
        mbar_expect_tx(bar, Q_UNIT);
#pragma unroll
        for (int i = 0; i < 8; i++)
          bulk_load(raw0 + (c * 8 + i) * (BN * 4), qw + (size_t)(c * 8 + i) * F_DIM + j * BN, BN * 4, bar);
      }
    }
    bar_sync(0, 256);
    pace(200);
    asm volatile("shl.b32 %0, %0, 16;\nshl.b32 %1, %1, 16;" : "+r"(lut_raw), "+r"(sc_raw));
    lutv = __uint_as_float(lut_raw);
    sc = __uint_as_float(sc_raw);
    const Table tab = make_table(lutv, sc);
    if (__any_sync(0xffffffffu, lane > 31 && (tab.lo[0] ^ tab.lo[1] ^ tab.lo[2] ^ tab.lo[3] ^ tab.hi[0] ^ tab.hi[1] ^
                                              tab.hi[2] ^ tab.hi[3]) == 1))
      __trap();
    int r[2][8];
    auto lds_group = [&](auto G) {
      constexpr int g = decltype(G)::value, c = g > 0 ? g - 1 : 0;
      if constexpr (g <= NCP) {
        cp_async_wait<NCP - g>();
        __syncwarp();
      } else {
        if (c == NCP) mbar_wait(bars + 8 * B_RAW0, 0);
        if (c == RSPLIT) mbar_wait(bars + 8 * B_RAW0 + 8, 0);
      }
#pragma unroll
      for (int i = 0; i < 8; i++)
        r[g & 1][i] = lds32(qbase + (g == 0 ? Q_UNIT : raw0 - sbase - SMEM_Q + c * Q_UNIT) + i * (BN * 4));
    };
    lds_group(IC<0>{});
    TL(6);
    static_for<0, 9>([&](auto G) {
      constexpr int g = decltype(G)::value, c = g > 0 ? g - 1 : 0;
      if (g == PUB_AT) {
        publish(1);
        TL(3);
      }
      if (g == 0) {
        emit_unit(convert_unit(r[g & 1], tab), 1);
        __syncwarp();
        TL(2);
        if constexpr (g < 8) lds_group(IC<g + 1>{});
      } else {
        if constexpr (g < 8) lds_group(IC<g + 1>{});
        sts128(sbase + SMEM_W + c * W_KC + (warp * 32 + lane) * 16, convert_unit(r[g & 1], tab));
      }
    });
    asm volatile("fence.proxy.async.shared::cta;" ::: "memory");
    __syncwarp();
    arrive_one(bars + 8 * B_W0);
    TL(4);
    if (wg == 1) {
      lds_unit(q, 2);
      emit_unit(convert_unit(q, tab), 2);
    }
    TL(5);
  }

  float acc0[112], acc1[112];
  constexpr uint32_t DA_HI = (1u << 30) | (1024 >> 4), DB_HI = (128 >> 4);
  const uint32_t da0 = ((1u << 16) | ((sbase + SMEM_X) >> 4)) + wg * (XS * X_SLICE >> 4);
  constexpr uint32_t db0 = ((W_KC >> 4) << 16) | ((sbase + SMEM_W) >> 4);
  const uint32_t fullx = bars + 8 * B_FULLX + wg * (8 * XS), done = bars + 8 * B_DONE + wg * 64;
  const bool x_issuer = (warp & 3) == 3;

  auto mma = [&](float (&acc)[112], int n, int kb, int k0, int k1) {
    wgmma_fence();
#pragma unroll
    for (int k = k0; k < k1; k++)
      wgmma_m64n224k16(acc, make_desc(da0 + (n % XS) * (X_SLICE >> 4) + k * 2, DA_HI),
                       make_desc(db0 + w_ring(kb) * (W_STAGE >> 4) + k * (2 * W_KC >> 4), DB_HI), kb != 0 || k != 0);
    wgmma_commit();
  };
  auto release = [&](int n) {
    arrive_one(ring<8>(done, n));
    if (x_issuer) {
      ring_wait<8>(done, n);
      const int m = n + 4;
      if (elect_one())
        load_x(wg, m, m < 2 * NR ? m >> 1 : end_kb((m - 2 * NR) % ENDK), m < 2 * NR ? m & 1 : (m - 2 * NR) / ENDK);
    }
  };
  auto end_slot = [&](int n) {
    wgmma_wait<1>();
    release(n);
  };
  auto slot = [&](float (&acc)[112], auto N) {
    constexpr int n = decltype(N)::value;
    constexpr bool hv = heavy(n), pub = heavy(n - 1);
    ring_wait<XS>(fullx, n);
    mma(acc, n, n >> 1, 0, 4);
    if (hv && warp < 7) dequant_lookup(q, lutv);
    end_slot(n);
    if (warp < 7) {
      constexpr int u = unit_at(n);
      if (pub) publish(u - 1);
      if (n == 2) lds_unit(q, 4);
      if (hv) {
        constexpr int un = u + 1 < NKB ? u + 1 : u;
        dequant_finish(q, rb, w_ptr(u), sc, ring<4>(bars + 8 * B_FULLQ, un), (un >> 2) & 1, qbase + (un & 3) * Q_UNIT);
      }
    } else {
      constexpr int m = w_at(n), u = q_at(n), m_next = w_at(n + 1);
      if (m >= 0 || u >= 0) ring_wait<8>(bars + 8 * B_DONE, n - 1);
      if (m >= 0) {
        ready |= __ballot_sync(0xffffffffu, rb >= flag_full);
        wait_ready(m);
        asm volatile("fence.proxy.async.global;" ::: "memory");
      }
      if (m_next >= 0) rb = ld_strong(fl);
      if ((m >= 0 || u >= 0) && elect_one()) {
        if (m >= 0) load_w(m);
        if (u >= 0) load_q(u);
      }
    }
  };

  mbar_wait(bars + 8 * B_W0, 0);
  mbar_wait(fullx, 0);
  TL(8); TLG(46);
  mma(acc0, 0, 0, 0, 4);
  mbar_wait(fullx + 8, 0);
  TL(9);
  mma(acc1, 1, 0, 0, 4);
  if (wg == 0) lds_unit(q, 2);
  arrive_one(done);
  if (warp < 7) {
    if (wg == 0) {
      emit_unit(convert_unit(q, lutv, sc), 2);
    } else {
      publish(2);
    }
    lds_unit(q, 3);
    const uint4 w3 = convert_unit(q, lutv, sc);
    if (wg == 0) publish(2);
    st_strong128(w_ptr(3), w3);
    rb = ld_strong(w_ptr(3));
  } else if (warp == 7) {
    if (elect_one()) load_q(5);
  }
  end_slot(1);
  if (warp == 7) rb = ld_strong(fl);

  static_for<1, NR>([&](auto R) {
    constexpr int r = decltype(R)::value;
    wait_w(r);
    TL(8 + 2 * r);
    slot(acc0, IC<2 * r>{});
    TL(9 + 2 * r);
    slot(acc1, IC<2 * r + 1>{});
  });

  __nv_bfloat16* op = out + (size_t)(xrow + (warp & 3) * 16 + (lane >> 2)) * F_DIM + j * BN + (lane & 3) * 8;
  TL(40); TLG(48);
  if (wg == 1) {
    wgmma_wait<0>();
    release(2 * NR);
    if (warp == 7) {
      wait_ready(14);
      asm volatile("fence.proxy.async.global;" ::: "memory");
      ring_wait<8>(bars + 8 * B_DONE, 2 * NR);
      if (elect_one()) load_w(14);
      unsigned old = 0;
      if (lane == 17) old = atomicAdd(fl, 1u);
      if (__shfl_sync(0xffffffffu, old, 17) == NI - 1) *fl = 0;
    }
    bar_sync(1, 256);
  }
#pragma unroll
  for (int e = 0; e < ENDK; e++) {
    wait_w(end_kb(e));
    ring_wait<XS>(fullx, 2 * NR + e);
    mma(acc0, 2 * NR + e, end_kb(e), 0, 4);
    if (e == ENDK - 1) bar_arrive(1 + wg, 256);
    wgmma_wait<1>();
    if (e > 0 || wg == 0) release(2 * NR + e);
  }
  wgmma_wait<0>();
  release(2 * NR + ENDK);
  TL(41);
  auto delay_to = [&](unsigned t0, unsigned t) {
    while (__any_sync(0xffffffffu, clk32() - t0 < t)) {}
  };
  if (wg == 0) {
    store_acc(acc0, op, 0, 7);
    TL(42);
    bar_sync(2, 256);
#pragma unroll
    for (int e = 0; e < ENDK; e++) {
      ring_wait<XS>(fullx, 2 * NR + ENDK + e);
      mma(acc1, 2 * NR + ENDK + e, end_kb(e), 0, 4);
    }
    bar_arrive(1, 256);
    wgmma_wait<0>();
    TL(43); TLG(47);
    store_acc(acc1, op + 64 * F_DIM, 0, 7);
  } else {
    uint32_t af[4 * ENDK][4];
    const uint32_t abase = sbase + SMEM_X + XS * X_SLICE + ((warp & 3) * 16 + (lane & 15)) * 128;
    float accp[112];
    const unsigned t0 = clk32();
#pragma unroll
    for (int J = 0; J < 7; J++) {
      if (J > 0) delay_to(t0, J * ST_GAP);
      store_acc(acc0, op, J, J + 1);
      if (J == 0) {
#pragma unroll
        for (int i = 0; i < 112; i++) asm volatile("add.rn.f32 %0, %1, 0f00000000;" : "=f"(accp[i]) : "f"(acc1[i]));
      }
      if (J >= 1 && J <= ENDK) {
        const int e = J - 1, n = 2 * NR + ENDK + e;
        ring_wait<XS>(fullx, n);
#pragma unroll
        for (int k = 0; k < 4; k++)
          asm volatile("ldmatrix.sync.aligned.m8n8.x4.shared.b16 {%0, %1, %2, %3}, [%4];"
                       : "=r"(af[4 * e + k][0]), "=r"(af[4 * e + k][1]), "=r"(af[4 * e + k][2]), "=r"(af[4 * e + k][3])
                       : "r"(abase + (n % XS) * X_SLICE + (((2 * k + (lane >> 4)) ^ (lane & 7)) << 4))
                       : "memory");
      }
    }
    TL(42);
    auto part = [&](auto P, int s0, int s1) {
      constexpr int p = decltype(P)::value;
      wgmma_fence();
#pragma unroll
      for (int st = s0; st < s1; st++) {
        const int kb = end_kb(st >> 2);
        const uint64_t db = make_desc(db0 + w_ring(kb) * (W_STAGE >> 4) + (st & 3) * (2 * W_KC >> 4) +
                                          (p == 0 ? 0 : 32 + 64 * p), DB_HI);
        if constexpr (p == 0) wgmma_rs_m64n96k16<0>(accp, af[st], db);
        else wgmma_rs_m64n64k16<16 + 32 * p>(accp, af[st], db);
      }
      wgmma_commit();
    };
    bar_sync(1, 256);
    TL(51);
    part(IC<0>{}, 0, 4 * ENDK);
    part(IC<1>{}, 0, LEAD);
    wgmma_wait<1>();
    store_acc(accp, op + 64 * F_DIM, 0, 3);
    part(IC<1>{}, LEAD, 4 * ENDK);
    part(IC<2>{}, 0, LEAD);
    wgmma_wait<1>();
    store_acc(accp, op + 64 * F_DIM, 3, 5);
    part(IC<2>{}, LEAD, 4 * ENDK);
    wgmma_wait<0>();
    TL(43); TLG(47);
    store_acc(accp, op + 64 * F_DIM, 5, 7);
  }
  TL(44);
}

__global__ void __launch_bounds__(BN)
prefill_kernel(const int* __restrict__ qw, const __nv_bfloat16* __restrict__ lut,
               const __nv_bfloat16* __restrict__ scales, uint8_t* scratch) {
  const int j = blockIdx.x & 15, kc = blockIdx.x >> 4, f = j * BN + perm32(threadIdx.x);
  int q[8];
#pragma unroll
  for (int i = 0; i < 8; i++) q[i] = qw[(kc * 8 + i) * F_DIM + f];
  *reinterpret_cast<uint4*>(scratch + (size_t)j * REGION + W_OFF + kc * W_KC + threadIdx.x * 16) =
      convert_unit(q, __bfloat162float(lut[threadIdx.x & 15]), __bfloat162float(scales[f]));
}

typedef CUresult (*EncodeTiledFn)(CUtensorMap*, CUtensorMapDataType, cuuint32_t, void*, const cuuint64_t*,
                                  const cuuint64_t*, const cuuint32_t*, const cuuint32_t*, CUtensorMapInterleave,
                                  CUtensorMapSwizzle, CUtensorMapL2promotion, CUtensorMapFloatOOBfill);

}

extern "C" void kernel_launch(void* const* d_in, const int* in_sizes, int n_in, void* d_out, int out_size) {
  const __nv_bfloat16* x = (const __nv_bfloat16*)d_in[0];
  const int* qw = (const int*)d_in[1];
  const __nv_bfloat16* lut = (const __nv_bfloat16*)d_in[2];
  const __nv_bfloat16* scales = (const __nv_bfloat16*)d_in[3];
  __nv_bfloat16* out = (__nv_bfloat16*)d_out;

  static EncodeTiledFn enc = nullptr;
  static uint8_t* p_scr = nullptr;
  static bool coresident = false;
  if (!enc) {
    void* fn = nullptr;
    cudaDriverEntryPointQueryResult qr;
    cudaGetDriverEntryPoint("cuTensorMapEncodeTiled", &fn, cudaEnableDefault, &qr);
    enc = (EncodeTiledFn)fn;
    void* p = nullptr;
    cudaGetSymbolAddress(&p, g_scratch);
    p_scr = (uint8_t*)(((uintptr_t)p + REGION - 1) & ~(uintptr_t)(REGION - 1));
    cudaFuncSetAttribute(fused_kernel, cudaFuncAttributeMaxDynamicSharedMemorySize, SMEM_TOTAL);
    int dev = 0, sms = 0;
    cudaGetDevice(&dev);
    cudaDeviceGetAttribute(&sms, cudaDevAttrMultiProcessorCount, dev);
    coresident = sms >= NI * NJ;
  }
  CUtensorMap tm_x, tm_q;
  cuuint32_t estr[2] = {1, 1};
  {
    cuuint64_t gdim[2] = {(cuuint64_t)D_DIM, (cuuint64_t)S_DIM};
    cuuint64_t gstr[1] = {(cuuint64_t)D_DIM * 2};
    cuuint32_t box[2] = {(cuuint32_t)BK, 64};
    enc(&tm_x, CU_TENSOR_MAP_DATA_TYPE_BFLOAT16, 2, (void*)x, gdim, gstr, box, estr, CU_TENSOR_MAP_INTERLEAVE_NONE,
        CU_TENSOR_MAP_SWIZZLE_128B, CU_TENSOR_MAP_L2_PROMOTION_NONE, CU_TENSOR_MAP_FLOAT_OOB_FILL_NONE);
  }
  {
    cuuint64_t gdim[2] = {(cuuint64_t)F_DIM, (cuuint64_t)D_DIM};
    cuuint64_t gstr[1] = {(cuuint64_t)F_DIM * 4};
    cuuint32_t box[2] = {(cuuint32_t)BN, 8};
    enc(&tm_q, CU_TENSOR_MAP_DATA_TYPE_INT32, 2, (void*)qw, gdim, gstr, box, estr, CU_TENSOR_MAP_INTERLEAVE_NONE,
        CU_TENSOR_MAP_SWIZZLE_NONE, CU_TENSOR_MAP_L2_PROMOTION_NONE, CU_TENSOR_MAP_FLOAT_OOB_FILL_NONE);
  }
  if (!coresident) prefill_kernel<<<NJ * NKB * 8, BN, 0, cudaStreamPerThread>>>(qw, lut, scales, p_scr);
  fused_kernel<<<NI * NJ, 256, SMEM_TOTAL, cudaStreamPerThread>>>(qw, lut, scales, out, p_scr,
                                                                  coresident ? FLAG_FULL : 0u, tm_x, tm_q);
}
```

```cpp
#include <cuda_runtime.h>
#include <cuda_bf16.h>
#include <cuda.h>
#include <stdint.h>

namespace {

constexpr int S_DIM = 2048, D_DIM = 1024, F_DIM = 3584;
constexpr int BM = 256, BN = 224, BK = 64;
constexpr int NKB = D_DIM / BK;
constexpr int NJ = F_DIM / BN;
constexpr int NI = S_DIM / BM;
constexpr int WS = 4;
constexpr int XS = 5;
constexpr int ENDK = 5;
constexpr int NR = NKB - ENDK;
constexpr int X_SLICE = 64 * BK * 2;
constexpr int W_STAGE = BN * BK * 2;
constexpr int W_KC = BN * 16;

constexpr int REGION = 512 * 1024;
__device__ uint4 g_scratch[(NJ + 1) * REGION / 16];

__device__ __forceinline__ uint32_t smem_u32(const void* p) { return (uint32_t)__cvta_generic_to_shared(p); }
__device__ __forceinline__ unsigned clk32() {
  unsigned c;
  asm volatile("mov.u32 %0, %%clock;" : "=r"(c)::"memory");
  return c;
}
__device__ __forceinline__ bool elect_one() {
  uint32_t p;
  asm volatile("{\n.reg .pred P;\nelect.sync _|P, 0xffffffff;\nselp.b32 %0, 1, 0, P;\n}" : "=r"(p));
  return p != 0;
}
__device__ __forceinline__ void mbar_init(uint32_t bar, uint32_t cnt) {
  asm volatile("mbarrier.init.shared::cta.b64 [%0], %1;" ::"r"(bar), "r"(cnt) : "memory");
}
__device__ __forceinline__ void mbar_expect_tx(uint32_t bar, uint32_t bytes) {
  asm volatile("mbarrier.arrive.expect_tx.shared::cta.b64 _, [%0], %1;" ::"r"(bar), "r"(bytes) : "memory");
}
__device__ __forceinline__ void mbar_arrive(uint32_t bar) {
  asm volatile("mbarrier.arrive.shared::cta.b64 _, [%0];" ::"r"(bar) : "memory");
}
__device__ __forceinline__ void mbar_wait(uint32_t bar, uint32_t parity) {
  asm volatile(
      "{\n.reg .pred p;\n"
      "LAB_WAIT:\n"
      "mbarrier.try_wait.parity.shared::cta.b64 p, [%0], %1;\n"
      "@p bra LAB_DONE;\n"
      "bra LAB_WAIT;\n"
      "LAB_DONE:\n}\n" ::"r"(bar), "r"(parity) : "memory");
}
template <int N>
__device__ __forceinline__ uint32_t ring(uint32_t base, int i) { return base + 8 * (i % N); }
template <int N>
__device__ __forceinline__ void ring_wait(uint32_t base, int i) { mbar_wait(ring<N>(base, i), (i / N) & 1); }
__device__ __forceinline__ void tma_load_2d(uint32_t dst, const CUtensorMap* tm, int c0, int c1, uint32_t bar) {
  asm volatile(
      "cp.async.bulk.tensor.2d.shared::cluster.global.mbarrier::complete_tx::bytes [%0], [%1, {%3, %4}], [%2];"
      ::"r"(dst), "l"(tm), "r"(bar), "r"(c0), "r"(c1) : "memory");
}
__device__ __forceinline__ void bulk_load(uint32_t dst, const void* src, uint32_t bytes, uint32_t bar) {
  asm volatile(
      "cp.async.bulk.shared::cluster.global.mbarrier::complete_tx::bytes [%0], [%1], %2, [%3];"
      ::"r"(dst), "l"(src), "r"(bytes), "r"(bar) : "memory");
}
__device__ __forceinline__ void cp_async16(uint32_t dst, const void* src) {
  asm volatile("cp.async.cg.shared.global [%0], [%1], 16;" ::"r"(dst), "l"(src) : "memory");
}
__device__ __forceinline__ void cp_async_commit() { asm volatile("cp.async.commit_group;" ::: "memory"); }
template <int N>
__device__ __forceinline__ void cp_async_wait() { asm volatile("cp.async.wait_group %0;" ::"n"(N) : "memory"); }
__device__ __forceinline__ uint32_t ldg_u16(const void* p) {
  uint32_t v;
  asm volatile("ld.global.u16 %0, [%1];" : "=r"(v) : "l"(p) : "memory");
  return v;
}
__device__ __forceinline__ int lds32(uint32_t addr) {
  int v;
  asm volatile("ld.shared.b32 %0, [%1];" : "=r"(v) : "r"(addr) : "memory");
  return v;
}
__device__ __forceinline__ void sts128(uint32_t addr, uint4 v) {
  asm volatile("st.shared.v4.u32 [%0], {%1, %2, %3, %4};" ::"r"(addr), "r"(v.x), "r"(v.y), "r"(v.z), "r"(v.w) : "memory");
}
__device__ __forceinline__ uint64_t make_desc(uint32_t lo, uint32_t hi) {
  uint64_t d;
  asm("mov.b64 %0, {%1, %2};" : "=l"(d) : "r"(lo), "r"(hi));
  return d;
}
__device__ __forceinline__ unsigned ld_strong(const void* p) {
  unsigned v;
  asm volatile("ld.relaxed.gpu.global.u32 %0, [%1];" : "=r"(v) : "l"(p) : "memory");
  return v;
}
__device__ __forceinline__ void st_strong128(void* p, uint4 v) {
  asm volatile("st.relaxed.gpu.global.v4.u32 [%0], {%1, %2, %3, %4};" ::"l"(p), "r"(v.x), "r"(v.y), "r"(v.z), "r"(v.w)
               : "memory");
}
__device__ __forceinline__ void wgmma_fence() { asm volatile("wgmma.fence.sync.aligned;" ::: "memory"); }
__device__ __forceinline__ void wgmma_commit() { asm volatile("wgmma.commit_group.sync.aligned;" ::: "memory"); }
template <int N>
__device__ __forceinline__ void wgmma_wait() { asm volatile("wgmma.wait_group.sync.aligned %0;" ::"n"(N) : "memory"); }
__device__ __forceinline__ void bar_sync(int id, int n) { asm volatile("bar.sync %0, %1;" ::"r"(id), "r"(n) : "memory"); }
__device__ __forceinline__ void bar_arrive(int id, int n) { asm volatile("bar.arrive %0, %1;" ::"r"(id), "r"(n) : "memory"); }

__device__ __forceinline__ void wgmma_m64n224k16(float (&d)[112], uint64_t da, uint64_t db, int scale_d) {
  asm volatile(
    "{\n.reg .pred p;\nsetp.ne.b32 p, %114, 0;\n"
    "wgmma.mma_async.sync.aligned.m64n224k16.f32.bf16.bf16 "
    "{%0, %1, %2, %3, %4, %5, %6, %7, %8, %9, %10, %11, %12, %13, %14, %15, "
    "%16, %17, %18, %19, %20, %21, %22, %23, %24, %25, %26, %27, %28, %29, %30, %31, "
    "%32, %33, %34, %35, %36, %37, %38, %39, %40, %41, %42, %43, %44, %45, %46, %47, "
    "%48, %49, %50, %51, %52, %53, %54, %55, %56, %57, %58, %59, %60, %61, %62, %63, "
    "%64, %65, %66, %67, %68, %69, %70, %71, %72, %73, %74, %75, %76, %77, %78, %79, "
    "%80, %81, %82, %83, %84, %85, %86, %87, %88, %89, %90, %91, %92, %93, %94, %95, "
    "%96, %97, %98, %99, %100, %101, %102, %103, %104, %105, %106, %107, %108, %109, %110, %111}, "
    "%112, %113, p, 1, 1, 0, 0;\n}\n"
    : "+f"(d[0]), "+f"(d[1]), "+f"(d[2]), "+f"(d[3]), "+f"(d[4]), "+f"(d[5]), "+f"(d[6]), "+f"(d[7]),
      "+f"(d[8]), "+f"(d[9]), "+f"(d[10]), "+f"(d[11]), "+f"(d[12]), "+f"(d[13]), "+f"(d[14]), "+f"(d[15]),
      "+f"(d[16]), "+f"(d[17]), "+f"(d[18]), "+f"(d[19]), "+f"(d[20]), "+f"(d[21]), "+f"(d[22]), "+f"(d[23]),
      "+f"(d[24]), "+f"(d[25]), "+f"(d[26]), "+f"(d[27]), "+f"(d[28]), "+f"(d[29]), "+f"(d[30]), "+f"(d[31]),
      "+f"(d[32]), "+f"(d[33]), "+f"(d[34]), "+f"(d[35]), "+f"(d[36]), "+f"(d[37]), "+f"(d[38]), "+f"(d[39]),
      "+f"(d[40]), "+f"(d[41]), "+f"(d[42]), "+f"(d[43]), "+f"(d[44]), "+f"(d[45]), "+f"(d[46]), "+f"(d[47]),
      "+f"(d[48]), "+f"(d[49]), "+f"(d[50]), "+f"(d[51]), "+f"(d[52]), "+f"(d[53]), "+f"(d[54]), "+f"(d[55]),
      "+f"(d[56]), "+f"(d[57]), "+f"(d[58]), "+f"(d[59]), "+f"(d[60]), "+f"(d[61]), "+f"(d[62]), "+f"(d[63]),
      "+f"(d[64]), "+f"(d[65]), "+f"(d[66]), "+f"(d[67]), "+f"(d[68]), "+f"(d[69]), "+f"(d[70]), "+f"(d[71]),
      "+f"(d[72]), "+f"(d[73]), "+f"(d[74]), "+f"(d[75]), "+f"(d[76]), "+f"(d[77]), "+f"(d[78]), "+f"(d[79]),
      "+f"(d[80]), "+f"(d[81]), "+f"(d[82]), "+f"(d[83]), "+f"(d[84]), "+f"(d[85]), "+f"(d[86]), "+f"(d[87]),
      "+f"(d[88]), "+f"(d[89]), "+f"(d[90]), "+f"(d[91]), "+f"(d[92]), "+f"(d[93]), "+f"(d[94]), "+f"(d[95]),
      "+f"(d[96]), "+f"(d[97]), "+f"(d[98]), "+f"(d[99]), "+f"(d[100]), "+f"(d[101]), "+f"(d[102]), "+f"(d[103]),
      "+f"(d[104]), "+f"(d[105]), "+f"(d[106]), "+f"(d[107]), "+f"(d[108]), "+f"(d[109]), "+f"(d[110]), "+f"(d[111])
    : "l"(da), "l"(db), "r"(scale_d));
}
template <int O>
__device__ __forceinline__ void wgmma_rs_m64n96k16(float (&d)[112], const uint32_t (&a)[4], uint64_t db) {
  asm volatile(
    "wgmma.mma_async.sync.aligned.m64n96k16.f32.bf16.bf16 "
    "{%0, %1, %2, %3, %4, %5, %6, %7, %8, %9, %10, %11, %12, %13, %14, %15, "
    "%16, %17, %18, %19, %20, %21, %22, %23, %24, %25, %26, %27, %28, %29, %30, %31, "
    "%32, %33, %34, %35, %36, %37, %38, %39, %40, %41, %42, %43, %44, %45, %46, %47}, "
    "{%48, %49, %50, %51}, %52, 1, 1, 1, 0;\n"
    : "+f"(d[O + 0]), "+f"(d[O + 1]), "+f"(d[O + 2]), "+f"(d[O + 3]),
      "+f"(d[O + 4]), "+f"(d[O + 5]), "+f"(d[O + 6]), "+f"(d[O + 7]),
      "+f"(d[O + 8]), "+f"(d[O + 9]), "+f"(d[O + 10]), "+f"(d[O + 11]),
      "+f"(d[O + 12]), "+f"(d[O + 13]), "+f"(d[O + 14]), "+f"(d[O + 15]),
      "+f"(d[O + 16]), "+f"(d[O + 17]), "+f"(d[O + 18]), "+f"(d[O + 19]),
      "+f"(d[O + 20]), "+f"(d[O + 21]), "+f"(d[O + 22]), "+f"(d[O + 23]),
      "+f"(d[O + 24]), "+f"(d[O + 25]), "+f"(d[O + 26]), "+f"(d[O + 27]),
      "+f"(d[O + 28]), "+f"(d[O + 29]), "+f"(d[O + 30]), "+f"(d[O + 31]),
      "+f"(d[O + 32]), "+f"(d[O + 33]), "+f"(d[O + 34]), "+f"(d[O + 35]),
      "+f"(d[O + 36]), "+f"(d[O + 37]), "+f"(d[O + 38]), "+f"(d[O + 39]),
      "+f"(d[O + 40]), "+f"(d[O + 41]), "+f"(d[O + 42]), "+f"(d[O + 43]),
      "+f"(d[O + 44]), "+f"(d[O + 45]), "+f"(d[O + 46]), "+f"(d[O + 47])
    : "r"(a[0]), "r"(a[1]), "r"(a[2]), "r"(a[3]), "l"(db));
}
template <int O>
__device__ __forceinline__ void wgmma_rs_m64n64k16(float (&d)[112], const uint32_t (&a)[4], uint64_t db) {
  asm volatile(
    "wgmma.mma_async.sync.aligned.m64n64k16.f32.bf16.bf16 "
    "{%0, %1, %2, %3, %4, %5, %6, %7, %8, %9, %10, %11, %12, %13, %14, %15, "
    "%16, %17, %18, %19, %20, %21, %22, %23, %24, %25, %26, %27, %28, %29, %30, %31}, "
    "{%32, %33, %34, %35}, %36, 1, 1, 1, 0;\n"
    : "+f"(d[O + 0]), "+f"(d[O + 1]), "+f"(d[O + 2]), "+f"(d[O + 3]),
      "+f"(d[O + 4]), "+f"(d[O + 5]), "+f"(d[O + 6]), "+f"(d[O + 7]),
      "+f"(d[O + 8]), "+f"(d[O + 9]), "+f"(d[O + 10]), "+f"(d[O + 11]),
      "+f"(d[O + 12]), "+f"(d[O + 13]), "+f"(d[O + 14]), "+f"(d[O + 15]),
      "+f"(d[O + 16]), "+f"(d[O + 17]), "+f"(d[O + 18]), "+f"(d[O + 19]),
      "+f"(d[O + 20]), "+f"(d[O + 21]), "+f"(d[O + 22]), "+f"(d[O + 23]),
      "+f"(d[O + 24]), "+f"(d[O + 25]), "+f"(d[O + 26]), "+f"(d[O + 27]),
      "+f"(d[O + 28]), "+f"(d[O + 29]), "+f"(d[O + 30]), "+f"(d[O + 31])
    : "r"(a[0]), "r"(a[1]), "r"(a[2]), "r"(a[3]), "l"(db));
}

__device__ __forceinline__ uint32_t pack_bf16(float lo, float hi) {
  uint32_t r;
  asm("cvt.rn.bf16x2.f32 %0, %1, %2;" : "=r"(r) : "f"(hi), "f"(lo));
  return r;
}

__device__ __forceinline__ int perm32(int n) { return (n & ~30) | ((n & 6) << 2) | ((n >> 2) & 6); }

constexpr int SMEM_X = 0;
constexpr int SMEM_W = 2 * XS * X_SLICE;
constexpr int SMEM_Q = SMEM_W + WS * W_STAGE;
constexpr int Q_UNIT = 8 * BN * 4;
constexpr int SMEM_BAR = SMEM_Q + W_STAGE;
constexpr int B_FULLW = 0, B_FULLQ = 5, B_FULLX = 9, B_DONE = 19, B_W0 = 35, B_RAW0 = 36;
constexpr int SMEM_TL = SMEM_BAR + 512;
constexpr int SMEM_TOTAL = SMEM_TL;
constexpr int W_OFF = 128;
constexpr unsigned FLAG_FULL = NI * 7;

#define TL(i)
#define TLG(i)

__device__ __forceinline__ void store_acc(const float (&a)[112], __nv_bfloat16* p, int J0, int J1) {
#pragma unroll
  for (int J = J0; J < J1; J++) {
    uint4 v0, v1;
    v0.x = pack_bf16(a[16 * J + 0], a[16 * J + 1]);
    v0.y = pack_bf16(a[16 * J + 4], a[16 * J + 5]);
    v0.z = pack_bf16(a[16 * J + 8], a[16 * J + 9]);
    v0.w = pack_bf16(a[16 * J + 12], a[16 * J + 13]);
    v1.x = pack_bf16(a[16 * J + 2], a[16 * J + 3]);
    v1.y = pack_bf16(a[16 * J + 6], a[16 * J + 7]);
    v1.z = pack_bf16(a[16 * J + 10], a[16 * J + 11]);
    v1.w = pack_bf16(a[16 * J + 14], a[16 * J + 15]);
    *reinterpret_cast<uint4*>(p + 32 * J) = v0;
    *reinterpret_cast<uint4*>(p + 8 * F_DIM + 32 * J) = v1;
  }
}

struct Table {
  uint32_t lo[4], hi[4];
};
__device__ __forceinline__ uint32_t prmt(uint32_t a, uint32_t b, uint32_t s) {
  uint32_t r;
  asm("prmt.b32 %0, %1, %2, %3;" : "=r"(r) : "r"(a), "r"(b), "r"(s));
  return r;
}
__device__ __forceinline__ Table make_table(float lutv, float sc) {
  Table t;
#pragma unroll
  for (int i = 0; i < 4; i++) {
    const uint32_t a = pack_bf16(__shfl_sync(0xffffffffu, lutv, 4 * i) * sc, __shfl_sync(0xffffffffu, lutv, 4 * i + 1) * sc);
    const uint32_t b =
        pack_bf16(__shfl_sync(0xffffffffu, lutv, 4 * i + 2) * sc, __shfl_sync(0xffffffffu, lutv, 4 * i + 3) * sc);
    t.lo[i] = prmt(a, b, 0x6420);
    t.hi[i] = prmt(a, b, 0x7531);
  }
  return t;
}
__device__ __forceinline__ uint4 convert_unit(const int (&q)[8], const Table& t) {
  const uint32_t all = ((q[7] * 16 + q[6]) * 256 + (q[5] * 16 + q[4])) * 65536 + ((q[3] * 16 + q[2]) * 256 + (q[1] * 16 + q[0]));
  const uint32_t s7 = all & 0x77777777u;
  const uint32_t s2 = ((all >> 1) & 0x44444444u) | 0x32103210u;
  uint32_t o[4];
#pragma unroll
  for (int h = 0; h < 2; h++) {
    const uint32_t a = h ? s7 >> 16 : s7, b = h ? s2 >> 16 : s2;
    const uint32_t lo = prmt(prmt(t.lo[0], t.lo[1], a), prmt(t.lo[2], t.lo[3], a), b);
    const uint32_t hi = prmt(prmt(t.hi[0], t.hi[1], a), prmt(t.hi[2], t.hi[3], a), b);
    o[2 * h] = prmt(lo, hi, 0x5140);
    o[2 * h + 1] = prmt(lo, hi, 0x7362);
  }
  return make_uint4(o[0], o[1], o[2], o[3]);
}

constexpr int PU = 3;
#define HEAVY 0x3BBBAu
__host__ __device__ constexpr int popc(unsigned v) { return v ? (v & 1) + popc(v >> 1) : 0; }
__host__ __device__ constexpr bool heavy(int n) { return n >= 0 && ((HEAVY >> n) & 1); }
__host__ __device__ constexpr int unit_at(int n) { return PU + popc(HEAVY & ((1u << n) - 1)); }
__host__ __device__ constexpr int emit_slot(int u) {
  if (u < PU) return -1;
  for (int n = 0; n < 24; n++)
    if (heavy(n) && unit_at(n) == u) return n;
  return 99;
}
__host__ __device__ constexpr int end_kb(int e) { return e < 3 ? NR + e : NR + 7 - e; }
__host__ __device__ constexpr int w_ring(int m) { return m == 15 ? 4 : m & 3; }
__host__ __device__ constexpr int cmax(int a, int b) { return a > b ? a : b; }
__host__ __device__ constexpr int w_slot(int m) {
  return m == 15 ? cmax(emit_slot(15) + 3, 20) : cmax(2 * m - 5, emit_slot(m) + 3);
}
__host__ __device__ constexpr int q_slot(int u) {
  return u == 5 ? 1 : cmax(q_slot(u - 1) + 1, u < 8 ? 2 : u == 8 ? 4 : emit_slot(u - 5) + 2);
}
__host__ __device__ constexpr int w_at(int n) {
  for (int m = 2; m < NKB; m++)
    if (w_slot(m) == n) return m;
  return -1;
}
__host__ __device__ constexpr int q_at(int n) {
  for (int u = 5; u < NKB; u++)
    if (q_slot(u) == n) return u;
  return -1;
}
constexpr bool schedule_ok() {
  if (popc(HEAVY) != NKB - PU || (HEAVY & 7) != 2 || (HEAVY >> 20)) return false;
  for (int m = 2; m < NKB; m++) {
    if (w_at(w_slot(m)) != m || (m != 14 && w_slot(m) >= 2 * NR)) return false;
    if (m < NR && w_slot(m) > 2 * m - 2) return false;
  }
  for (int u = 5; u < NKB; u++)
    if (q_slot(u) + 2 > emit_slot(u - 1)) return false;
  return true;
}
static_assert(schedule_ok(), "bad schedule");
template <int V>
struct IC {
  static constexpr int value = V;
};
template <int I, int N, class F>
__device__ __forceinline__ void static_for(F&& f) {
  if constexpr (I < N) {
    f(IC<I>{});
    static_for<I + 1, N>(f);
  }
}

#define NCP 3
#define RSPLIT 5
#define STAG_L 70
#define PACE_INIT 650
#define PACE_X 1100
#define PACE_Q2 1600
#define PACE_Q3 2100
#define PUB_AT 6
#define ST_GAP 150
#define LEAD 8

constexpr uint32_t sbase = 1024;

__global__ void __launch_bounds__(256, 1)
fused_kernel(const int* __restrict__ qw, const __nv_bfloat16* __restrict__ lut,
             const __nv_bfloat16* __restrict__ scales, __nv_bfloat16* __restrict__ out, uint8_t* scratch,
             unsigned flag_full,
             const __grid_constant__ CUtensorMap tm_x, const __grid_constant__ CUtensorMap tm_q) {
  extern __shared__ __align__(1024) uint8_t smem_raw[];
  constexpr uint32_t bars = sbase + SMEM_BAR;
  const int j = blockIdx.x >> 3, it = blockIdx.x & 7;
  constexpr uint32_t raw0 = sbase + SMEM_W + 2 * W_STAGE;
  uint32_t lut_raw = 0, sc_raw = 0;
  if (threadIdx.x < 224) {
    const unsigned t = threadIdx.x, row0 = (t >> 3) & 3, col = (t & ~31u) + (t & 7) * 4;
    const int* src = qw + (row0 * F_DIM + j * BN + col);
    const uint32_t dst = row0 * (BN * 4) + col * 4;
    lut_raw = ldg_u16(lut + (t & 15));
    sc_raw = ldg_u16(scales + (j * BN + perm32(t)));
    __syncwarp();
#pragma unroll
    for (int g = 0; g < NCP + 1; g++) {
      const unsigned row = g == 0 ? BK + it * 8 : (g - 1) * 8;
      const uint32_t d = dst + (g == 0 ? sbase + SMEM_Q + Q_UNIT : raw0 + (g - 1) * Q_UNIT);
      cp_async16(d, src + row * F_DIM);
      cp_async16(d + 4 * BN * 4, src + (row + 4) * F_DIM);
      cp_async_commit();
    }
  }
  const int warp = __shfl_sync(0xffffffffu, threadIdx.x >> 5, 0);
  const int wg = warp >> 2;
  int lane;
  asm volatile("mov.u32 %0, %%laneid;" : "=r"(lane));
  const unsigned t_start = clk32();
  auto pace = [&](unsigned t) {
    while (__any_sync(0xffffffffu, clk32() - t_start < t)) {}
  };

  uint8_t* const region = scratch + (size_t)j * REGION;
  uint8_t* const wp = region + (warp < 7 ? W_OFF + it * W_KC + (warp * 32 + lane) * 16 : lane * 4);
  unsigned* const fl = reinterpret_cast<unsigned*>(wp);
  Table tab;
  unsigned rb;
  const int xrow = it * BM + wg * 128;

  auto w_ptr = [&](int u) { return reinterpret_cast<uint4*>(wp + u * W_STAGE); };
  auto emit_unit = [&](uint4 w, int u) {
    st_strong128(w_ptr(u), w);
    rb = ld_strong(w_ptr(u));
  };
  auto publish = [&](int u) {
    asm volatile(
        "{\n.reg .pred P, Q;\n"
        "setp.ne.u32 P, %1, 0xffffffff;\n"
        "vote.sync.all.pred P, P, 0xffffffff;\n"
        "elect.sync _|Q, 0xffffffff;\n"
        "and.pred Q, Q, P;\n"
        "@Q red.relaxed.gpu.global.add.u32 [%0], 1;\n}"
        ::"l"(region + u * 4), "r"(rb) : "memory");
  };
  auto load_x = [&](int g, int n, int kb, int half) {
    const uint32_t bar = ring<XS>(bars + 8 * B_FULLX, n) + g * (8 * XS);
    mbar_expect_tx(bar, X_SLICE);
    tma_load_2d(sbase + SMEM_X + (n % XS) * X_SLICE + g * (XS * X_SLICE), &tm_x, kb * BK,
                it * BM + g * 128 + half * 64, bar);
  };
  auto load_q = [&](int u) {
    const uint32_t bar = ring<4>(bars + 8 * B_FULLQ, u);
    mbar_expect_tx(bar, Q_UNIT);
    tma_load_2d(sbase + SMEM_Q + (u & 3) * Q_UNIT, &tm_q, j * BN, u * BK + it * 8, bar);
  };

  unsigned ready = 0;
  auto load_w = [&](int m) {
    const uint32_t bar = bars + 8 * (B_FULLW + w_ring(m));
    mbar_expect_tx(bar, W_STAGE);
    bulk_load(sbase + SMEM_W + w_ring(m) * W_STAGE, region + W_OFF + m * W_STAGE, W_STAGE, bar);
  };
  auto wait_w = [&](int m) { mbar_wait(bars + 8 * (B_FULLW + w_ring(m)), m == 15 ? 0 : (m >> 2) & 1); };
  auto poll = [&]() { ready |= __ballot_sync(0xffffffffu, ld_strong(fl) >= flag_full); };
  auto wait_ready = [&](int kb) {
    int spins = 0;
    while (!((ready >> kb) & 1)) {
      poll();
      if (++spins > (1 << 22)) __trap();
    }
  };

  uint32_t qbase;
  asm volatile("mov.u32 %0, %1;" : "=r"(qbase) : "r"(sbase + SMEM_Q + warp * 128 + perm32(lane) * 4));
  auto lds_unit = [&](int (&q)[8], int u) {
    ring_wait<4>(bars + 8 * B_FULLQ, u);
#pragma unroll
    for (int i = 0; i < 8; i++) q[i] = lds32(qbase + (u & 3) * Q_UNIT + i * (BN * 4));
  };
  auto arrive_one = [&](uint32_t bar) {
    asm volatile("{\n.reg .pred P;\nelect.sync _|P, 0xffffffff;\n@P mbarrier.arrive.shared::cta.b64 _, [%0];\n}"
                 ::"r"(bar) : "memory");
  };

  int q[8];
  if (warp == 7) {
    if (elect_one()) {
      mbar_init(bars + 8 * B_RAW0, RSPLIT - NCP);
      mbar_init(bars + 8 * B_RAW0 + 8, 8 - RSPLIT);
      asm volatile("fence.mbarrier_init.release.cluster;" ::: "memory");
    }
    __syncwarp();
    bar_arrive(4, (9 - NCP) * 32);
    if (elect_one()) {
      asm volatile("prefetch.tensormap [%0];" ::"l"(&tm_x) : "memory");
      asm volatile("prefetch.tensormap [%0];" ::"l"(&tm_q) : "memory");
    }
    TL(5);
    pace(PACE_INIT);
    if (elect_one()) {
#pragma unroll
      for (int i = 0; i < B_RAW0; i++) mbar_init(bars + 8 * i, i == B_W0 ? 7 : i >= B_DONE ? 4 : 1);
      asm volatile("fence.mbarrier_init.release.cluster;" ::: "memory");
    }
    __syncwarp();
    rb = ld_strong(fl);
    bar_arrive(0, 256);
    TL(4);
#pragma unroll
    for (int i = 0; i < 4; i++) tab.lo[i] = tab.hi[i] = 0;
    if (smem_u32(smem_raw) != sbase) __trap();
    if (elect_one()) {
      mbar_arrive(bars + 8 * B_FULLW);
      mbar_arrive(bars + 8 * B_FULLQ);
      mbar_arrive(bars + 8 * B_FULLQ + 8);
    }
    pace(PACE_X);
    if (elect_one()) {
      load_x(0, 0, 0, 0); load_x(1, 0, 0, 0); load_x(0, 1, 0, 1); load_x(1, 1, 0, 1);
    }
    pace(PACE_Q2);
    if (elect_one()) load_q(2);
    pace(PACE_Q3);
    ready = __ballot_sync(0xffffffffu, rb >= flag_full);
    rb = ld_strong(fl);
    if (elect_one()) {
      load_q(3);
      load_x(0, 2, 1, 0); load_x(1, 2, 1, 0); load_x(0, 3, 1, 1); load_x(1, 3, 1, 1);
    }
    ready |= __ballot_sync(0xffffffffu, rb >= flag_full);
    wait_ready(1);
    asm volatile("fence.proxy.async.global;" ::: "memory");
    if (elect_one()) {
      load_w(1);
      load_q(4);
      load_x(0, 4, 2, 0); load_x(1, 4, 2, 0);
    }
    TL(2);
    TL(3);
  } else {
    if (warp + NCP < 8) {
      bar_sync(4, (9 - NCP) * 32);
      pace(warp * STAG_L);
      if (elect_one()) {
        const int c = warp + NCP;
        const uint32_t bar = bars + 8 * B_RAW0 + (c < RSPLIT ? 0 : 8);
        mbar_expect_tx(bar, Q_UNIT);
#pragma unroll
        for (int i = 0; i < 8; i++)
          bulk_load(raw0 + (c * 8 + i) * (BN * 4), qw + (size_t)(c * 8 + i) * F_DIM + j * BN, BN * 4, bar);
      }
    }
    bar_sync(0, 256);
    pace(200);
    asm volatile("shl.b32 %0, %0, 16;\nshl.b32 %1, %1, 16;" : "+r"(lut_raw), "+r"(sc_raw));
    tab = make_table(__uint_as_float(lut_raw), __uint_as_float(sc_raw));
    if (__any_sync(0xffffffffu, lane > 31 && (tab.lo[0] ^ tab.lo[1] ^ tab.lo[2] ^ tab.lo[3] ^ tab.hi[0] ^ tab.hi[1] ^
                                              tab.hi[2] ^ tab.hi[3]) == 1))
      __trap();
    int r[2][8];
    auto lds_group = [&](auto G) {
      constexpr int g = decltype(G)::value, c = g > 0 ? g - 1 : 0;
      if constexpr (g <= NCP) {
        cp_async_wait<NCP - g>();
        __syncwarp();
      } else {
        if (c == NCP) mbar_wait(bars + 8 * B_RAW0, 0);
        if (c == RSPLIT) mbar_wait(bars + 8 * B_RAW0 + 8, 0);
      }
#pragma unroll
      for (int i = 0; i < 8; i++)
        r[g & 1][i] = lds32(qbase + (g == 0 ? Q_UNIT : raw0 - sbase - SMEM_Q + c * Q_UNIT) + i * (BN * 4));
    };
    lds_group(IC<0>{});
    TL(6);
    static_for<0, 9>([&](auto G) {
      constexpr int g = decltype(G)::value, c = g > 0 ? g - 1 : 0;
      if (g == PUB_AT) {
        publish(1);
        TL(3);
      }
      if (g == 0) {
        emit_unit(convert_unit(r[g & 1], tab), 1);
        __syncwarp();
        TL(2);
        if constexpr (g < 8) lds_group(IC<g + 1>{});
      } else {
        if constexpr (g < 8) lds_group(IC<g + 1>{});
        sts128(sbase + SMEM_W + c * W_KC + (warp * 32 + lane) * 16, convert_unit(r[g & 1], tab));
      }
    });
    asm volatile("fence.proxy.async.shared::cta;" ::: "memory");
    __syncwarp();
    arrive_one(bars + 8 * B_W0);
    TL(4);
    if (wg == 1) {
      lds_unit(r[0], 2);
      emit_unit(convert_unit(r[0], tab), 2);
    }
    TL(5);
  }

  float acc0[112], acc1[112];
  constexpr uint32_t DA_HI = (1u << 30) | (1024 >> 4), DB_HI = (128 >> 4);
  const uint32_t da0 = ((1u << 16) | ((sbase + SMEM_X) >> 4)) + wg * (XS * X_SLICE >> 4);
  constexpr uint32_t db0 = ((W_KC >> 4) << 16) | ((sbase + SMEM_W) >> 4);
  const uint32_t fullx = bars + 8 * B_FULLX + wg * (8 * XS), done = bars + 8 * B_DONE + wg * 64;
  const bool x_issuer = (warp & 3) == 3;

  auto mma = [&](float (&acc)[112], int n, int kb, int k0, int k1) {
    wgmma_fence();
#pragma unroll
    for (int k = k0; k < k1; k++)
      wgmma_m64n224k16(acc, make_desc(da0 + (n % XS) * (X_SLICE >> 4) + k * 2, DA_HI),
                       make_desc(db0 + w_ring(kb) * (W_STAGE >> 4) + k * (2 * W_KC >> 4), DB_HI), kb != 0 || k != 0);
    wgmma_commit();
  };
  auto release = [&](int n) {
    arrive_one(ring<8>(done, n));
    if (x_issuer) {
      ring_wait<8>(done, n);
      const int m = n + 4;
      if (elect_one())
        load_x(wg, m, m < 2 * NR ? m >> 1 : end_kb((m - 2 * NR) % ENDK), m < 2 * NR ? m & 1 : (m - 2 * NR) / ENDK);
    }
  };
  auto end_slot = [&](int n) {
    wgmma_wait<1>();
    release(n);
  };
  auto slot = [&](float (&acc)[112], auto N) {
    constexpr int n = decltype(N)::value;
    constexpr bool hv = heavy(n), pub = heavy(n - 1);
    ring_wait<XS>(fullx, n);
    mma(acc, n, n >> 1, 0, 4);
    end_slot(n);
    if (warp < 7) {
      constexpr int u = unit_at(n);
      if (pub) publish(u - 1);
      if (n == 2) lds_unit(q, 4);
      if (hv) {
        emit_unit(convert_unit(q, tab), u);
        if (u + 1 < NKB) lds_unit(q, u + 1);
      }
    } else {
      constexpr int m = w_at(n), u = q_at(n), m_next = w_at(n + 1);
      if (m >= 0 || u >= 0) ring_wait<8>(bars + 8 * B_DONE, n - 1);
      if (m >= 0) {
        ready |= __ballot_sync(0xffffffffu, rb >= flag_full);
        wait_ready(m);
        asm volatile("fence.proxy.async.global;" ::: "memory");
      }
      if (m_next >= 0) rb = ld_strong(fl);
      if ((m >= 0 || u >= 0) && elect_one()) {
        if (m >= 0) load_w(m);
        if (u >= 0) load_q(u);
      }
    }
  };

  mbar_wait(bars + 8 * B_W0, 0);
  mbar_wait(fullx, 0);
  TL(8); TLG(46);
  mma(acc0, 0, 0, 0, 4);
  mbar_wait(fullx + 8, 0);
  TL(9);
  mma(acc1, 1, 0, 0, 4);
  arrive_one(done);
  if (warp < 7) {
    if (wg == 0) {
      int q2[8];
      lds_unit(q2, 2);
      emit_unit(convert_unit(q2, tab), 2);
    } else {
      publish(2);
    }
    int q3[8];
    lds_unit(q3, 3);
    const uint4 w3 = convert_unit(q3, tab);
    if (wg == 0) publish(2);
    emit_unit(w3, 3);
  } else {
    if (elect_one()) load_q(5);
  }
  end_slot(1);
  if (warp == 7) rb = ld_strong(fl);

  static_for<1, NR>([&](auto R) {
    constexpr int r = decltype(R)::value;
    wait_w(r);
    TL(8 + 2 * r);
    slot(acc0, IC<2 * r>{});
    TL(9 + 2 * r);
    slot(acc1, IC<2 * r + 1>{});
  });

  __nv_bfloat16* op = out + (size_t)(xrow + (warp & 3) * 16 + (lane >> 2)) * F_DIM + j * BN + (lane & 3) * 8;
  TL(40); TLG(48);
  if (wg == 1) {
    wgmma_wait<0>();
    release(2 * NR);
    if (warp == 7) {
      wait_ready(14);
      asm volatile("fence.proxy.async.global;" ::: "memory");
      ring_wait<8>(bars + 8 * B_DONE, 2 * NR);
      if (elect_one()) load_w(14);
      unsigned old = 0;
      if (lane == 17) old = atomicAdd(fl, 1u);
      if (__shfl_sync(0xffffffffu, old, 17) == NI - 1) *fl = 0;
    }
    bar_sync(1, 256);
  }
#pragma unroll
  for (int e = 0; e < ENDK; e++) {
    wait_w(end_kb(e));
    ring_wait<XS>(fullx, 2 * NR + e);
    mma(acc0, 2 * NR + e, end_kb(e), 0, 4);
    if (e == ENDK - 1) bar_arrive(1 + wg, 256);
    wgmma_wait<1>();
    if (e > 0 || wg == 0) release(2 * NR + e);
  }
  wgmma_wait<0>();
  release(2 * NR + ENDK);
  TL(41);
  auto delay_to = [&](unsigned t0, unsigned t) {
    while (__any_sync(0xffffffffu, clk32() - t0 < t)) {}
  };
  if (wg == 0) {
    store_acc(acc0, op, 0, 7);
    TL(42);
    bar_sync(2, 256);
#pragma unroll
    for (int e = 0; e < ENDK; e++) {
      ring_wait<XS>(fullx, 2 * NR + ENDK + e);
      mma(acc1, 2 * NR + ENDK + e, end_kb(e), 0, 4);
    }
    bar_arrive(1, 256);
    wgmma_wait<0>();
    TL(43); TLG(47);
    store_acc(acc1, op + 64 * F_DIM, 0, 7);
  } else {
    uint32_t af[4 * ENDK][4];
    const uint32_t abase = sbase + SMEM_X + XS * X_SLICE + ((warp & 3) * 16 + (lane & 15)) * 128;
    float accp[112];
    const unsigned t0 = clk32();
#pragma unroll
    for (int J = 0; J < 7; J++) {
      if (J > 0) delay_to(t0, J * ST_GAP);
      store_acc(acc0, op, J, J + 1);
      if (J == 0) {
#pragma unroll
        for (int i = 0; i < 112; i++) asm volatile("add.rn.f32 %0, %1, 0f00000000;" : "=f"(accp[i]) : "f"(acc1[i]));
      }
      if (J >= 1 && J <= ENDK) {
        const int e = J - 1, n = 2 * NR + ENDK + e;
        ring_wait<XS>(fullx, n);
#pragma unroll
        for (int k = 0; k < 4; k++)
          asm volatile("ldmatrix.sync.aligned.m8n8.x4.shared.b16 {%0, %1, %2, %3}, [%4];"
                       : "=r"(af[4 * e + k][0]), "=r"(af[4 * e + k][1]), "=r"(af[4 * e + k][2]), "=r"(af[4 * e + k][3])
                       : "r"(abase + (n % XS) * X_SLICE + (((2 * k + (lane >> 4)) ^ (lane & 7)) << 4))
                       : "memory");
      }
    }
    TL(42);
    auto part = [&](auto P, int s0, int s1) {
      constexpr int p = decltype(P)::value;
      wgmma_fence();
#pragma unroll
      for (int st = s0; st < s1; st++) {
        const int kb = end_kb(st >> 2);
        const uint64_t db = make_desc(db0 + w_ring(kb) * (W_STAGE >> 4) + (st & 3) * (2 * W_KC >> 4) +
                                          (p == 0 ? 0 : 32 + 64 * p), DB_HI);
        if constexpr (p == 0) wgmma_rs_m64n96k16<0>(accp, af[st], db);
        else wgmma_rs_m64n64k16<16 + 32 * p>(accp, af[st], db);
      }
      wgmma_commit();
    };
    bar_sync(1, 256);
    TL(51);
    part(IC<0>{}, 0, 4 * ENDK);
    part(IC<1>{}, 0, LEAD);
    wgmma_wait<1>();
    store_acc(accp, op + 64 * F_DIM, 0, 3);
    part(IC<1>{}, LEAD, 4 * ENDK);
    part(IC<2>{}, 0, LEAD);
    wgmma_wait<1>();
    store_acc(accp, op + 64 * F_DIM, 3, 5);
    part(IC<2>{}, LEAD, 4 * ENDK);
    wgmma_wait<0>();
    TL(43); TLG(47);
    store_acc(accp, op + 64 * F_DIM, 5, 7);
  }
  TL(44);
}

__global__ void __launch_bounds__(BN)
prefill_kernel(const int* __restrict__ qw, const __nv_bfloat16* __restrict__ lut,
               const __nv_bfloat16* __restrict__ scales, uint8_t* scratch) {
  const int j = blockIdx.x & 15, kc = blockIdx.x >> 4, f = j * BN + perm32(threadIdx.x);
  int q[8];
#pragma unroll
  for (int i = 0; i < 8; i++) q[i] = qw[(kc * 8 + i) * F_DIM + f];
  *reinterpret_cast<uint4*>(scratch + (size_t)j * REGION + W_OFF + kc * W_KC + threadIdx.x * 16) =
      convert_unit(q, make_table(__bfloat162float(lut[threadIdx.x & 15]), __bfloat162float(scales[f])));
}

typedef CUresult (*EncodeTiledFn)(CUtensorMap*, CUtensorMapDataType, cuuint32_t, void*, const cuuint64_t*,
                                  const cuuint64_t*, const cuuint32_t*, const cuuint32_t*, CUtensorMapInterleave,
                                  CUtensorMapSwizzle, CUtensorMapL2promotion, CUtensorMapFloatOOBfill);

}

extern "C" void kernel_launch(void* const* d_in, const int* in_sizes, int n_in, void* d_out, int out_size) {
  const __nv_bfloat16* x = (const __nv_bfloat16*)d_in[0];
  const int* qw = (const int*)d_in[1];
  const __nv_bfloat16* lut = (const __nv_bfloat16*)d_in[2];
  const __nv_bfloat16* scales = (const __nv_bfloat16*)d_in[3];
  __nv_bfloat16* out = (__nv_bfloat16*)d_out;

  static EncodeTiledFn enc = nullptr;
  static uint8_t* p_scr = nullptr;
  static bool coresident = false;
  if (!enc) {
    void* fn = nullptr;
    cudaDriverEntryPointQueryResult qr;
    cudaGetDriverEntryPoint("cuTensorMapEncodeTiled", &fn, cudaEnableDefault, &qr);
    enc = (EncodeTiledFn)fn;
    void* p = nullptr;
    cudaGetSymbolAddress(&p, g_scratch);
    p_scr = (uint8_t*)(((uintptr_t)p + REGION - 1) & ~(uintptr_t)(REGION - 1));
    cudaFuncSetAttribute(fused_kernel, cudaFuncAttributeMaxDynamicSharedMemorySize, SMEM_TOTAL);
    int dev = 0, sms = 0;
    cudaGetDevice(&dev);
    cudaDeviceGetAttribute(&sms, cudaDevAttrMultiProcessorCount, dev);
    coresident = sms >= NI * NJ;
  }
  CUtensorMap tm_x, tm_q;
  cuuint32_t estr[2] = {1, 1};
  {
    cuuint64_t gdim[2] = {(cuuint64_t)D_DIM, (cuuint64_t)S_DIM};
    cuuint64_t gstr[1] = {(cuuint64_t)D_DIM * 2};
    cuuint32_t box[2] = {(cuuint32_t)BK, 64};
    enc(&tm_x, CU_TENSOR_MAP_DATA_TYPE_BFLOAT16, 2, (void*)x, gdim, gstr, box, estr, CU_TENSOR_MAP_INTERLEAVE_NONE,
        CU_TENSOR_MAP_SWIZZLE_128B, CU_TENSOR_MAP_L2_PROMOTION_NONE, CU_TENSOR_MAP_FLOAT_OOB_FILL_NONE);
  }
  {
    cuuint64_t gdim[2] = {(cuuint64_t)F_DIM, (cuuint64_t)D_DIM};
    cuuint64_t gstr[1] = {(cuuint64_t)F_DIM * 4};
    cuuint32_t box[2] = {(cuuint32_t)BN, 8};
    enc(&tm_q, CU_TENSOR_MAP_DATA_TYPE_INT32, 2, (void*)qw, gdim, gstr, box, estr, CU_TENSOR_MAP_INTERLEAVE_NONE,
        CU_TENSOR_MAP_SWIZZLE_NONE, CU_TENSOR_MAP_L2_PROMOTION_NONE, CU_TENSOR_MAP_FLOAT_OOB_FILL_NONE);
  }
  if (!coresident) prefill_kernel<<<NJ * NKB * 8, BN, 0, cudaStreamPerThread>>>(qw, lut, scales, p_scr);
  fused_kernel<<<NI * NJ, 256, SMEM_TOTAL, cudaStreamPerThread>>>(qw, lut, scales, out, p_scr,
                                                                  coresident ? FLAG_FULL : 0u, tm_x, tm_q);
}
```

```cpp
#include <cuda_runtime.h>
#include <cuda_bf16.h>
#include <cuda.h>
#include <stdint.h>

namespace {

constexpr int S_DIM = 2048, D_DIM = 1024, F_DIM = 3584;
constexpr int BM = 256, BN = 224, BK = 64;
constexpr int NKB = D_DIM / BK;
constexpr int NJ = F_DIM / BN;
constexpr int NI = S_DIM / BM;
constexpr int WS = 4;
constexpr int XS = 5;
constexpr int ENDK = 5;
constexpr int NR = NKB - ENDK;
constexpr int X_SLICE = 64 * BK * 2;
constexpr int W_STAGE = BN * BK * 2;
constexpr int W_KC = BN * 16;

constexpr int REGION = 512 * 1024;
__device__ uint4 g_scratch[(NJ + 1) * REGION / 16];

__device__ __forceinline__ uint32_t smem_u32(const void* p) { return (uint32_t)__cvta_generic_to_shared(p); }
__device__ __forceinline__ unsigned clk32() {
  unsigned c;
  asm volatile("mov.u32 %0, %%clock;" : "=r"(c)::"memory");
  return c;
}
__device__ __forceinline__ bool elect_one() {
  uint32_t p;
  asm volatile("{\n.reg .pred P;\nelect.sync _|P, 0xffffffff;\nselp.b32 %0, 1, 0, P;\n}" : "=r"(p));
  return p != 0;
}
__device__ __forceinline__ void mbar_init(uint32_t bar, uint32_t cnt) {
  asm volatile("mbarrier.init.shared::cta.b64 [%0], %1;" ::"r"(bar), "r"(cnt) : "memory");
}
__device__ __forceinline__ void mbar_expect_tx(uint32_t bar, uint32_t bytes) {
  asm volatile("mbarrier.arrive.expect_tx.shared::cta.b64 _, [%0], %1;" ::"r"(bar), "r"(bytes) : "memory");
}
__device__ __forceinline__ void mbar_arrive(uint32_t bar) {
  asm volatile("mbarrier.arrive.shared::cta.b64 _, [%0];" ::"r"(bar) : "memory");
}
__device__ __forceinline__ void mbar_wait(uint32_t bar, uint32_t parity) {
  asm volatile(
      "{\n.reg .pred p;\n"
      "LAB_WAIT:\n"
      "mbarrier.try_wait.parity.shared::cta.b64 p, [%0], %1;\n"
      "@p bra LAB_DONE;\n"
      "bra LAB_WAIT;\n"
      "LAB_DONE:\n}\n" ::"r"(bar), "r"(parity) : "memory");
}
template <int N>
__device__ __forceinline__ uint32_t ring(uint32_t base, int i) { return base + 8 * (i % N); }
template <int N>
__device__ __forceinline__ void ring_wait(uint32_t base, int i) { mbar_wait(ring<N>(base, i), (i / N) & 1); }
__device__ __forceinline__ void tma_load_2d(uint32_t dst, const CUtensorMap* tm, int c0, int c1, uint32_t bar) {
  asm volatile(
      "cp.async.bulk.tensor.2d.shared::cluster.global.mbarrier::complete_tx::bytes [%0], [%1, {%3, %4}], [%2];"
      ::"r"(dst), "l"(tm), "r"(bar), "r"(c0), "r"(c1) : "memory");
}
__device__ __forceinline__ void bulk_load(uint32_t dst, const void* src, uint32_t bytes, uint32_t bar) {
  asm volatile(
      "cp.async.bulk.shared::cluster.global.mbarrier::complete_tx::bytes [%0], [%1], %2, [%3];"
      ::"r"(dst), "l"(src), "r"(bytes), "r"(bar) : "memory");
}
__device__ __forceinline__ void cp_async16(uint32_t dst, const void* src) {
  asm volatile("cp.async.cg.shared.global [%0], [%1], 16;" ::"r"(dst), "l"(src) : "memory");
}
__device__ __forceinline__ void cp_async_commit() { asm volatile("cp.async.commit_group;" ::: "memory"); }
template <int N>
__device__ __forceinline__ void cp_async_wait() { asm volatile("cp.async.wait_group %0;" ::"n"(N) : "memory"); }
__device__ __forceinline__ uint32_t ldg_u16(const void* p) {
  uint32_t v;
  asm volatile("ld.global.u16 %0, [%1];" : "=r"(v) : "l"(p) : "memory");
  return v;
}
__device__ __forceinline__ int lds32(uint32_t addr) {
  int v;
  asm volatile("ld.shared.b32 %0, [%1];" : "=r"(v) : "r"(addr) : "memory");
  return v;
}
__device__ __forceinline__ void sts128(uint32_t addr, uint4 v) {
  asm volatile("st.shared.v4.u32 [%0], {%1, %2, %3, %4};" ::"r"(addr), "r"(v.x), "r"(v.y), "r"(v.z), "r"(v.w) : "memory");
}
__device__ __forceinline__ uint64_t make_desc(uint32_t lo, uint32_t hi) {
  uint64_t d;
  asm("mov.b64 %0, {%1, %2};" : "=l"(d) : "r"(lo), "r"(hi));
  return d;
}
__device__ __forceinline__ unsigned ld_strong(const void* p) {
  unsigned v;
  asm volatile("ld.relaxed.gpu.global.u32 %0, [%1];" : "=r"(v) : "l"(p) : "memory");
  return v;
}
__device__ __forceinline__ void st_strong128(void* p, uint4 v) {
  asm volatile("st.relaxed.gpu.global.v4.u32 [%0], {%1, %2, %3, %4};" ::"l"(p), "r"(v.x), "r"(v.y), "r"(v.z), "r"(v.w)
               : "memory");
}
__device__ __forceinline__ void wgmma_fence() { asm volatile("wgmma.fence.sync.aligned;" ::: "memory"); }
__device__ __forceinline__ void wgmma_commit() { asm volatile("wgmma.commit_group.sync.aligned;" ::: "memory"); }
template <int N>
__device__ __forceinline__ void wgmma_wait() { asm volatile("wgmma.wait_group.sync.aligned %0;" ::"n"(N) : "memory"); }
__device__ __forceinline__ void bar_sync(int id, int n) { asm volatile("bar.sync %0, %1;" ::"r"(id), "r"(n) : "memory"); }
__device__ __forceinline__ void bar_arrive(int id, int n) { asm volatile("bar.arrive %0, %1;" ::"r"(id), "r"(n) : "memory"); }

__device__ __forceinline__ void wgmma_m64n224k16(float (&d)[112], uint64_t da, uint64_t db, int scale_d) {
  asm volatile(
    "{\n.reg .pred p;\nsetp.ne.b32 p, %114, 0;\n"
    "wgmma.mma_async.sync.aligned.m64n224k16.f32.bf16.bf16 "
    "{%0, %1, %2, %3, %4, %5, %6, %7, %8, %9, %10, %11, %12, %13, %14, %15, "
    "%16, %17, %18, %19, %20, %21, %22, %23, %24, %25, %26, %27, %28, %29, %30, %31, "
    "%32, %33, %34, %35, %36, %37, %38, %39, %40, %41, %42, %43, %44, %45, %46, %47, "
    "%48, %49, %50, %51, %52, %53, %54, %55, %56, %57, %58, %59, %60, %61, %62, %63, "
    "%64, %65, %66, %67, %68, %69, %70, %71, %72, %73, %74, %75, %76, %77, %78, %79, "
    "%80, %81, %82, %83, %84, %85, %86, %87, %88, %89, %90, %91, %92, %93, %94, %95, "
    "%96, %97, %98, %99, %100, %101, %102, %103, %104, %105, %106, %107, %108, %109, %110, %111}, "
    "%112, %113, p, 1, 1, 0, 0;\n}\n"
    : "+f"(d[0]), "+f"(d[1]), "+f"(d[2]), "+f"(d[3]), "+f"(d[4]), "+f"(d[5]), "+f"(d[6]), "+f"(d[7]),
      "+f"(d[8]), "+f"(d[9]), "+f"(d[10]), "+f"(d[11]), "+f"(d[12]), "+f"(d[13]), "+f"(d[14]), "+f"(d[15]),
      "+f"(d[16]), "+f"(d[17]), "+f"(d[18]), "+f"(d[19]), "+f"(d[20]), "+f"(d[21]), "+f"(d[22]), "+f"(d[23]),
      "+f"(d[24]), "+f"(d[25]), "+f"(d[26]), "+f"(d[27]), "+f"(d[28]), "+f"(d[29]), "+f"(d[30]), "+f"(d[31]),
      "+f"(d[32]), "+f"(d[33]), "+f"(d[34]), "+f"(d[35]), "+f"(d[36]), "+f"(d[37]), "+f"(d[38]), "+f"(d[39]),
      "+f"(d[40]), "+f"(d[41]), "+f"(d[42]), "+f"(d[43]), "+f"(d[44]), "+f"(d[45]), "+f"(d[46]), "+f"(d[47]),
      "+f"(d[48]), "+f"(d[49]), "+f"(d[50]), "+f"(d[51]), "+f"(d[52]), "+f"(d[53]), "+f"(d[54]), "+f"(d[55]),
      "+f"(d[56]), "+f"(d[57]), "+f"(d[58]), "+f"(d[59]), "+f"(d[60]), "+f"(d[61]), "+f"(d[62]), "+f"(d[63]),
      "+f"(d[64]), "+f"(d[65]), "+f"(d[66]), "+f"(d[67]), "+f"(d[68]), "+f"(d[69]), "+f"(d[70]), "+f"(d[71]),
      "+f"(d[72]), "+f"(d[73]), "+f"(d[74]), "+f"(d[75]), "+f"(d[76]), "+f"(d[77]), "+f"(d[78]), "+f"(d[79]),
      "+f"(d[80]), "+f"(d[81]), "+f"(d[82]), "+f"(d[83]), "+f"(d[84]), "+f"(d[85]), "+f"(d[86]), "+f"(d[87]),
      "+f"(d[88]), "+f"(d[89]), "+f"(d[90]), "+f"(d[91]), "+f"(d[92]), "+f"(d[93]), "+f"(d[94]), "+f"(d[95]),
      "+f"(d[96]), "+f"(d[97]), "+f"(d[98]), "+f"(d[99]), "+f"(d[100]), "+f"(d[101]), "+f"(d[102]), "+f"(d[103]),
      "+f"(d[104]), "+f"(d[105]), "+f"(d[106]), "+f"(d[107]), "+f"(d[108]), "+f"(d[109]), "+f"(d[110]), "+f"(d[111])
    : "l"(da), "l"(db), "r"(scale_d));
}
template <int O>
__device__ __forceinline__ void wgmma_rs_m64n96k16(float (&d)[112], const uint32_t (&a)[4], uint64_t db) {
  asm volatile(
    "wgmma.mma_async.sync.aligned.m64n96k16.f32.bf16.bf16 "
    "{%0, %1, %2, %3, %4, %5, %6, %7, %8, %9, %10, %11, %12, %13, %14, %15, "
    "%16, %17, %18, %19, %20, %21, %22, %23, %24, %25, %26, %27, %28, %29, %30, %31, "
    "%32, %33, %34, %35, %36, %37, %38, %39, %40, %41, %42, %43, %44, %45, %46, %47}, "
    "{%48, %49, %50, %51}, %52, 1, 1, 1, 0;\n"
    : "+f"(d[O + 0]), "+f"(d[O + 1]), "+f"(d[O + 2]), "+f"(d[O + 3]),
      "+f"(d[O + 4]), "+f"(d[O + 5]), "+f"(d[O + 6]), "+f"(d[O + 7]),
      "+f"(d[O + 8]), "+f"(d[O + 9]), "+f"(d[O + 10]), "+f"(d[O + 11]),
      "+f"(d[O + 12]), "+f"(d[O + 13]), "+f"(d[O + 14]), "+f"(d[O + 15]),
      "+f"(d[O + 16]), "+f"(d[O + 17]), "+f"(d[O + 18]), "+f"(d[O + 19]),
      "+f"(d[O + 20]), "+f"(d[O + 21]), "+f"(d[O + 22]), "+f"(d[O + 23]),
      "+f"(d[O + 24]), "+f"(d[O + 25]), "+f"(d[O + 26]), "+f"(d[O + 27]),
      "+f"(d[O + 28]), "+f"(d[O + 29]), "+f"(d[O + 30]), "+f"(d[O + 31]),
      "+f"(d[O + 32]), "+f"(d[O + 33]), "+f"(d[O + 34]), "+f"(d[O + 35]),
      "+f"(d[O + 36]), "+f"(d[O + 37]), "+f"(d[O + 38]), "+f"(d[O + 39]),
      "+f"(d[O + 40]), "+f"(d[O + 41]), "+f"(d[O + 42]), "+f"(d[O + 43]),
      "+f"(d[O + 44]), "+f"(d[O + 45]), "+f"(d[O + 46]), "+f"(d[O + 47])
    : "r"(a[0]), "r"(a[1]), "r"(a[2]), "r"(a[3]), "l"(db));
}
template <int O>
__device__ __forceinline__ void wgmma_rs_m64n64k16(float (&d)[112], const uint32_t (&a)[4], uint64_t db) {
  asm volatile(
    "wgmma.mma_async.sync.aligned.m64n64k16.f32.bf16.bf16 "
    "{%0, %1, %2, %3, %4, %5, %6, %7, %8, %9, %10, %11, %12, %13, %14, %15, "
    "%16, %17, %18, %19, %20, %21, %22, %23, %24, %25, %26, %27, %28, %29, %30, %31}, "
    "{%32, %33, %34, %35}, %36, 1, 1, 1, 0;\n"
    : "+f"(d[O + 0]), "+f"(d[O + 1]), "+f"(d[O + 2]), "+f"(d[O + 3]),
      "+f"(d[O + 4]), "+f"(d[O + 5]), "+f"(d[O + 6]), "+f"(d[O + 7]),
      "+f"(d[O + 8]), "+f"(d[O + 9]), "+f"(d[O + 10]), "+f"(d[O + 11]),
      "+f"(d[O + 12]), "+f"(d[O + 13]), "+f"(d[O + 14]), "+f"(d[O + 15]),
      "+f"(d[O + 16]), "+f"(d[O + 17]), "+f"(d[O + 18]), "+f"(d[O + 19]),
      "+f"(d[O + 20]), "+f"(d[O + 21]), "+f"(d[O + 22]), "+f"(d[O + 23]),
      "+f"(d[O + 24]), "+f"(d[O + 25]), "+f"(d[O + 26]), "+f"(d[O + 27]),
      "+f"(d[O + 28]), "+f"(d[O + 29]), "+f"(d[O + 30]), "+f"(d[O + 31])
    : "r"(a[0]), "r"(a[1]), "r"(a[2]), "r"(a[3]), "l"(db));
}

__device__ __forceinline__ uint32_t pack_bf16(float lo, float hi) {
  uint32_t r;
  asm("cvt.rn.bf16x2.f32 %0, %1, %2;" : "=r"(r) : "f"(hi), "f"(lo));
  return r;
}

__device__ __forceinline__ int perm32(int n) { return (n & ~30) | ((n & 6) << 2) | ((n >> 2) & 6); }

constexpr int SMEM_X = 0;
constexpr int SMEM_W = 2 * XS * X_SLICE;
constexpr int SMEM_Q = SMEM_W + WS * W_STAGE;
constexpr int Q_UNIT = 8 * BN * 4;
constexpr int SMEM_BAR = SMEM_Q + W_STAGE;
constexpr int B_FULLW = 0, B_FULLQ = 5, B_FULLX = 9, B_DONE = 19, B_W0 = 35, B_RAW0 = 36;
constexpr int SMEM_TL = SMEM_BAR + 512;
constexpr int SMEM_TOTAL = SMEM_TL;
constexpr int W_OFF = 128;
constexpr unsigned FLAG_FULL = NI * 7;

#define TL(i)
#define TLG(i)

__device__ __forceinline__ void store_acc(const float (&a)[112], __nv_bfloat16* p, int J0, int J1) {
#pragma unroll
  for (int J = J0; J < J1; J++) {
    uint4 v0, v1;
    v0.x = pack_bf16(a[16 * J + 0], a[16 * J + 1]);
    v0.y = pack_bf16(a[16 * J + 4], a[16 * J + 5]);
    v0.z = pack_bf16(a[16 * J + 8], a[16 * J + 9]);
    v0.w = pack_bf16(a[16 * J + 12], a[16 * J + 13]);
    v1.x = pack_bf16(a[16 * J + 2], a[16 * J + 3]);
    v1.y = pack_bf16(a[16 * J + 6], a[16 * J + 7]);
    v1.z = pack_bf16(a[16 * J + 10], a[16 * J + 11]);
    v1.w = pack_bf16(a[16 * J + 14], a[16 * J + 15]);
    *reinterpret_cast<uint4*>(p + 32 * J) = v0;
    *reinterpret_cast<uint4*>(p + 8 * F_DIM + 32 * J) = v1;
  }
}

struct Table {
  uint32_t lo[4], hi[4];
};
__device__ __forceinline__ uint32_t prmt(uint32_t a, uint32_t b, uint32_t s) {
  uint32_t r;
  asm("prmt.b32 %0, %1, %2, %3;" : "=r"(r) : "r"(a), "r"(b), "r"(s));
  return r;
}
__device__ __forceinline__ Table make_table(float lutv, float sc) {
  Table t;
#pragma unroll
  for (int i = 0; i < 4; i++) {
    const uint32_t a = pack_bf16(__shfl_sync(0xffffffffu, lutv, 4 * i) * sc, __shfl_sync(0xffffffffu, lutv, 4 * i + 1) * sc);
    const uint32_t b =
        pack_bf16(__shfl_sync(0xffffffffu, lutv, 4 * i + 2) * sc, __shfl_sync(0xffffffffu, lutv, 4 * i + 3) * sc);
    t.lo[i] = prmt(a, b, 0x6420);
    t.hi[i] = prmt(a, b, 0x7531);
  }
  return t;
}
__device__ __forceinline__ uint4 convert_unit(const int (&q)[8], const Table& t) {
  const uint32_t all = ((q[7] * 16 + q[6]) * 256 + (q[5] * 16 + q[4])) * 65536 + ((q[3] * 16 + q[2]) * 256 + (q[1] * 16 + q[0]));
  const uint32_t s7 = all & 0x77777777u;
  const uint32_t s2 = ((all >> 1) & 0x44444444u) | 0x32103210u;
  uint32_t o[4];
#pragma unroll
  for (int h = 0; h < 2; h++) {
    const uint32_t a = h ? s7 >> 16 : s7, b = h ? s2 >> 16 : s2;
    const uint32_t lo = prmt(prmt(t.lo[0], t.lo[1], a), prmt(t.lo[2], t.lo[3], a), b);
    const uint32_t hi = prmt(prmt(t.hi[0], t.hi[1], a), prmt(t.hi[2], t.hi[3], a), b);
    o[2 * h] = prmt(lo, hi, 0x5140);
    o[2 * h + 1] = prmt(lo, hi, 0x7362);
  }
  return make_uint4(o[0], o[1], o[2], o[3]);
}

constexpr int PU = 3;
#define HEAVY 0x3BBBAu
__host__ __device__ constexpr int popc(unsigned v) { return v ? (v & 1) + popc(v >> 1) : 0; }
__host__ __device__ constexpr bool heavy(int n) { return n >= 0 && ((HEAVY >> n) & 1); }
__host__ __device__ constexpr int unit_at(int n) { return PU + popc(HEAVY & ((1u << n) - 1)); }
__host__ __device__ constexpr int emit_slot(int u) {
  if (u < PU) return -1;
  for (int n = 0; n < 24; n++)
    if (heavy(n) && unit_at(n) == u) return n;
  return 99;
}
__host__ __device__ constexpr int end_kb(int e) { return e < 3 ? NR + e : NR + 7 - e; }
__host__ __device__ constexpr int w_ring(int m) { return m == 15 ? 4 : m & 3; }
__host__ __device__ constexpr int cmax(int a, int b) { return a > b ? a : b; }
__host__ __device__ constexpr int w_slot(int m) {
  return m == 15 ? cmax(emit_slot(15) + 3, 20) : cmax(2 * m - 5, emit_slot(m) + 3);
}
__host__ __device__ constexpr int q_slot(int u) {
  return u == 5 ? 1 : cmax(q_slot(u - 1) + 1, u < 8 ? 2 : u == 8 ? 4 : emit_slot(u - 5) + 2);
}
__host__ __device__ constexpr int w_at(int n) {
  for (int m = 2; m < NKB; m++)
    if (w_slot(m) == n) return m;
  return -1;
}
__host__ __device__ constexpr int q_at(int n) {
  for (int u = 5; u < NKB; u++)
    if (q_slot(u) == n) return u;
  return -1;
}
constexpr bool schedule_ok() {
  if (popc(HEAVY) != NKB - PU || (HEAVY & 7) != 2 || (HEAVY >> 20)) return false;
  for (int m = 2; m < NKB; m++) {
    if (w_at(w_slot(m)) != m || (m != 14 && w_slot(m) >= 2 * NR)) return false;
    if (m < NR && w_slot(m) > 2 * m - 2) return false;
  }
  for (int u = 5; u < NKB; u++)
    if (q_slot(u) + 2 > emit_slot(u - 1)) return false;
  return true;
}
static_assert(schedule_ok(), "bad schedule");
template <int V>
struct IC {
  static constexpr int value = V;
};
template <int I, int N, class F>
__device__ __forceinline__ void static_for(F&& f) {
  if constexpr (I < N) {
    f(IC<I>{});
    static_for<I + 1, N>(f);
  }
}

#define NCP 3
#define RSPLIT 5
#define STAG_L 70
#define PACE_INIT 650
#define PACE_X 1100
#define PACE_Q2 1600
#define PACE_Q3 2100
#define PUB_AT 6
#define ST_GAP 150
#define LEAD 8

constexpr uint32_t sbase = 1024;

__global__ void __launch_bounds__(256, 1)
fused_kernel(const int* __restrict__ qw, const __nv_bfloat16* __restrict__ lut,
             const __nv_bfloat16* __restrict__ scales, __nv_bfloat16* __restrict__ out, uint8_t* scratch,
             unsigned flag_full,
             const __grid_constant__ CUtensorMap tm_x, const __grid_constant__ CUtensorMap tm_q) {
  extern __shared__ __align__(1024) uint8_t smem_raw[];
  constexpr uint32_t bars = sbase + SMEM_BAR;
  const int j = blockIdx.x >> 3, it = blockIdx.x & 7;
  constexpr uint32_t raw0 = sbase + SMEM_W + 2 * W_STAGE;
  uint32_t lut_raw = 0, sc_raw = 0;
  if (threadIdx.x < 224) {
    const unsigned t = threadIdx.x, row0 = (t >> 3) & 3, col = (t & ~31u) + (t & 7) * 4;
    const int* src = qw + (row0 * F_DIM + j * BN + col);
    const uint32_t dst = row0 * (BN * 4) + col * 4;
    lut_raw = ldg_u16(lut + (t & 15));
    sc_raw = ldg_u16(scales + (j * BN + perm32(t)));
    __syncwarp();
#pragma unroll
    for (int g = 0; g < NCP + 1; g++) {
      const unsigned row = g == 0 ? BK + it * 8 : (g - 1) * 8;
      const uint32_t d = dst + (g == 0 ? sbase + SMEM_Q + Q_UNIT : raw0 + (g - 1) * Q_UNIT);
      cp_async16(d, src + row * F_DIM);
      cp_async16(d + 4 * BN * 4, src + (row + 4) * F_DIM);
      cp_async_commit();
    }
  }
  const int warp = __shfl_sync(0xffffffffu, threadIdx.x >> 5, 0);
  const int wg = warp >> 2;
  int lane;
  asm volatile("mov.u32 %0, %%laneid;" : "=r"(lane));
  const unsigned t_start = clk32();
  auto pace = [&](unsigned t) {
    while (__any_sync(0xffffffffu, clk32() - t_start < t)) {}
  };

  uint8_t* const region = scratch + (size_t)j * REGION;
  uint8_t* const wp = region + (warp < 7 ? W_OFF + it * W_KC + (warp * 32 + lane) * 16 : lane * 4);
  unsigned* const fl = reinterpret_cast<unsigned*>(wp);
  Table tab;
  unsigned rb;
  const int xrow = it * BM + wg * 128;

  auto w_ptr = [&](int u) { return reinterpret_cast<uint4*>(wp + u * W_STAGE); };
  auto emit_unit = [&](uint4 w, int u) {
    st_strong128(w_ptr(u), w);
    rb = ld_strong(w_ptr(u));
  };
  auto publish = [&](int u) {
    asm volatile(
        "{\n.reg .pred P, Q;\n"
        "setp.ne.u32 P, %1, 0xffffffff;\n"
        "vote.sync.all.pred P, P, 0xffffffff;\n"
        "elect.sync _|Q, 0xffffffff;\n"
        "and.pred Q, Q, P;\n"
        "@Q red.relaxed.gpu.global.add.u32 [%0], 1;\n}"
        ::"l"(region + u * 4), "r"(rb) : "memory");
  };
  auto load_x = [&](int g, int n, int kb, int half) {
    const uint32_t bar = ring<XS>(bars + 8 * B_FULLX, n) + g * (8 * XS);
    mbar_expect_tx(bar, X_SLICE);
    tma_load_2d(sbase + SMEM_X + (n % XS) * X_SLICE + g * (XS * X_SLICE), &tm_x, kb * BK,
                it * BM + g * 128 + half * 64, bar);
  };
  auto load_q = [&](int u) {
    const uint32_t bar = ring<4>(bars + 8 * B_FULLQ, u);
    mbar_expect_tx(bar, Q_UNIT);
    tma_load_2d(sbase + SMEM_Q + (u & 3) * Q_UNIT, &tm_q, j * BN, u * BK + it * 8, bar);
  };

  unsigned ready = 0;
  auto load_w = [&](int m) {
    const uint32_t bar = bars + 8 * (B_FULLW + w_ring(m));
    mbar_expect_tx(bar, W_STAGE);
    bulk_load(sbase + SMEM_W + w_ring(m) * W_STAGE, region + W_OFF + m * W_STAGE, W_STAGE, bar);
  };
  auto wait_w = [&](int m) { mbar_wait(bars + 8 * (B_FULLW + w_ring(m)), m == 15 ? 0 : (m >> 2) & 1); };
  auto poll = [&]() { ready |= __ballot_sync(0xffffffffu, ld_strong(fl) >= flag_full); };
  auto wait_ready = [&](int kb) {
    int spins = 0;
    while (!((ready >> kb) & 1)) {
      poll();
      if (++spins > (1 << 22)) __trap();
    }
  };

  uint32_t qbase;
  asm volatile("mov.u32 %0, %1;" : "=r"(qbase) : "r"(sbase + SMEM_Q + warp * 128 + perm32(lane) * 4));
  auto lds_unit = [&](int (&q)[8], int u) {
    ring_wait<4>(bars + 8 * B_FULLQ, u);
#pragma unroll
    for (int i = 0; i < 8; i++) q[i] = lds32(qbase + (u & 3) * Q_UNIT + i * (BN * 4));
  };
  auto arrive_one = [&](uint32_t bar) {
    asm volatile("{\n.reg .pred P;\nelect.sync _|P, 0xffffffff;\n@P mbarrier.arrive.shared::cta.b64 _, [%0];\n}"
                 ::"r"(bar) : "memory");
  };

  int q[8];
  if (warp == 7) {
    if (elect_one()) {
      mbar_init(bars + 8 * B_RAW0, RSPLIT - NCP);
      mbar_init(bars + 8 * B_RAW0 + 8, 8 - RSPLIT);
      asm volatile("fence.mbarrier_init.release.cluster;" ::: "memory");
    }
    __syncwarp();
    bar_arrive(4, (9 - NCP) * 32);
    if (elect_one()) {
      asm volatile("prefetch.tensormap [%0];" ::"l"(&tm_x) : "memory");
      asm volatile("prefetch.tensormap [%0];" ::"l"(&tm_q) : "memory");
    }
    TL(5);
    pace(PACE_INIT);
    if (elect_one()) {
#pragma unroll
      for (int i = 0; i < B_RAW0; i++) mbar_init(bars + 8 * i, i == B_W0 ? 7 : i >= B_DONE ? 4 : 1);
      asm volatile("fence.mbarrier_init.release.cluster;" ::: "memory");
    }
    __syncwarp();
    rb = ld_strong(fl);
    bar_arrive(0, 256);
    TL(4);
#pragma unroll
    for (int i = 0; i < 4; i++) tab.lo[i] = tab.hi[i] = 0;
    if (smem_u32(smem_raw) != sbase) __trap();
    if (elect_one()) {
      mbar_arrive(bars + 8 * B_FULLW);
      mbar_arrive(bars + 8 * B_FULLQ);
      mbar_arrive(bars + 8 * B_FULLQ + 8);
    }
    pace(PACE_X);
    if (elect_one()) {
      load_x(0, 0, 0, 0); load_x(1, 0, 0, 0); load_x(0, 1, 0, 1); load_x(1, 1, 0, 1);
    }
    pace(PACE_Q2);
    if (elect_one()) load_q(2);
    pace(PACE_Q3);
    ready = __ballot_sync(0xffffffffu, rb >= flag_full);
    rb = ld_strong(fl);
    if (elect_one()) {
      load_q(3);
      load_x(0, 2, 1, 0); load_x(1, 2, 1, 0); load_x(0, 3, 1, 1); load_x(1, 3, 1, 1);
    }
    ready |= __ballot_sync(0xffffffffu, rb >= flag_full);
    wait_ready(1);
    asm volatile("fence.proxy.async.global;" ::: "memory");
    if (elect_one()) {
      load_w(1);
      load_q(4);
      load_x(0, 4, 2, 0); load_x(1, 4, 2, 0);
    }
    TL(2);
    TL(3);
  } else {
    if (warp + NCP < 8) {
      bar_sync(4, (9 - NCP) * 32);
      pace(warp * STAG_L);
      if (elect_one()) {
        const int c = warp + NCP;
        const uint32_t bar = bars + 8 * B_RAW0 + (c < RSPLIT ? 0 : 8);
        mbar_expect_tx(bar, Q_UNIT);
#pragma unroll
        for (int i = 0; i < 8; i++)
          bulk_load(raw0 + (c * 8 + i) * (BN * 4), qw + (size_t)(c * 8 + i) * F_DIM + j * BN, BN * 4, bar);
      }
    }
    bar_sync(0, 256);
    pace(200);
    asm volatile("shl.b32 %0, %0, 16;\nshl.b32 %1, %1, 16;" : "+r"(lut_raw), "+r"(sc_raw));
    tab = make_table(__uint_as_float(lut_raw), __uint_as_float(sc_raw));
    if (__any_sync(0xffffffffu, lane > 31 && (tab.lo[0] ^ tab.lo[1] ^ tab.lo[2] ^ tab.lo[3] ^ tab.hi[0] ^ tab.hi[1] ^
                                              tab.hi[2] ^ tab.hi[3]) == 1))
      __trap();
    int r[2][8];
    auto lds_group = [&](auto G) {
      constexpr int g = decltype(G)::value, c = g > 0 ? g - 1 : 0;
      if constexpr (g <= NCP) {
        cp_async_wait<NCP - g>();
        __syncwarp();
      } else {
        if (c == NCP) mbar_wait(bars + 8 * B_RAW0, 0);
        if (c == RSPLIT) mbar_wait(bars + 8 * B_RAW0 + 8, 0);
      }
#pragma unroll
      for (int i = 0; i < 8; i++)
        r[g & 1][i] = lds32(qbase + (g == 0 ? Q_UNIT : raw0 - sbase - SMEM_Q + c * Q_UNIT) + i * (BN * 4));
    };
    lds_group(IC<0>{});
    TL(6);
    static_for<0, 9>([&](auto G) {
      constexpr int g = decltype(G)::value, c = g > 0 ? g - 1 : 0;
      if (g == PUB_AT) {
        publish(1);
        TL(3);
      }
      if (g == 0) {
        emit_unit(convert_unit(r[g & 1], tab), 1);
        __syncwarp();
        TL(2);
        if constexpr (g < 8) lds_group(IC<g + 1>{});
      } else {
        if constexpr (g < 8) lds_group(IC<g + 1>{});
        sts128(sbase + SMEM_W + c * W_KC + (warp * 32 + lane) * 16, convert_unit(r[g & 1], tab));
      }
    });
    asm volatile("fence.proxy.async.shared::cta;" ::: "memory");
    __syncwarp();
    arrive_one(bars + 8 * B_W0);
    TL(4);
    if (wg == 1) {
      lds_unit(r[0], 2);
      emit_unit(convert_unit(r[0], tab), 2);
    }
    TL(5);
  }

  float acc0[112], acc1[112];
  constexpr uint32_t DA_HI = (1u << 30) | (1024 >> 4), DB_HI = (128 >> 4);
  const uint32_t da0 = ((1u << 16) | ((sbase + SMEM_X) >> 4)) + wg * (XS * X_SLICE >> 4);
  constexpr uint32_t db0 = ((W_KC >> 4) << 16) | ((sbase + SMEM_W) >> 4);
  const uint32_t fullx = bars + 8 * B_FULLX + wg * (8 * XS), done = bars + 8 * B_DONE + wg * 64;
  const bool x_issuer = (warp & 3) == 3;

  auto mma = [&](float (&acc)[112], int n, int kb, int k0, int k1) {
    wgmma_fence();
#pragma unroll
    for (int k = k0; k < k1; k++)
      wgmma_m64n224k16(acc, make_desc(da0 + (n % XS) * (X_SLICE >> 4) + k * 2, DA_HI),
                       make_desc(db0 + w_ring(kb) * (W_STAGE >> 4) + k * (2 * W_KC >> 4), DB_HI), kb != 0 || k != 0);
    wgmma_commit();
  };
  auto release = [&](int n) {
    arrive_one(ring<8>(done, n));
    if (x_issuer) {
      ring_wait<8>(done, n);
      const int m = n + 4;
      if (elect_one())
        load_x(wg, m, m < 2 * NR ? m >> 1 : end_kb((m - 2 * NR) % ENDK), m < 2 * NR ? m & 1 : (m - 2 * NR) / ENDK);
    }
  };
  auto end_slot = [&](int n) {
    wgmma_wait<1>();
    release(n);
  };
  auto slot = [&](float (&acc)[112], auto N) {
    constexpr int n = decltype(N)::value;
    constexpr bool hv = heavy(n), pub = heavy(n - 1);
    ring_wait<XS>(fullx, n);
    mma(acc, n, n >> 1, 0, 4);
    end_slot(n);
    if (warp < 7) {
      constexpr int u = unit_at(n);
      if (pub) publish(u - 1);
      if (n == 2) lds_unit(q, 4);
      if (hv) {
        emit_unit(convert_unit(q, tab), u);
        if (u + 1 < NKB) lds_unit(q, u + 1);
      }
    } else {
      constexpr int m = w_at(n), u = q_at(n), m_next = w_at(n + 1);
      if (m >= 0 || u >= 0) ring_wait<8>(bars + 8 * B_DONE, n - 1);
      if (m >= 0) {
        ready |= __ballot_sync(0xffffffffu, rb >= flag_full);
        wait_ready(m);
        asm volatile("fence.proxy.async.global;" ::: "memory");
      }
      if (m_next >= 0) rb = ld_strong(fl);
      if ((m >= 0 || u >= 0) && elect_one()) {
        if (m >= 0) load_w(m);
        if (u >= 0) load_q(u);
      }
    }
  };

  mbar_wait(bars + 8 * B_W0, 0);
  mbar_wait(fullx, 0);
  TL(8); TLG(46);
  mma(acc0, 0, 0, 0, 4);
  mbar_wait(fullx + 8, 0);
  TL(9);
  mma(acc1, 1, 0, 0, 4);
  arrive_one(done);
  if (warp < 7) {
    if (wg == 0) {
      int q2[8];
      lds_unit(q2, 2);
      emit_unit(convert_unit(q2, tab), 2);
    } else {
      publish(2);
    }
    int q3[8];
    lds_unit(q3, 3);
    const uint4 w3 = convert_unit(q3, tab);
    if (wg == 0) publish(2);
    emit_unit(w3, 3);
  } else {
    if (elect_one()) load_q(5);
  }
  end_slot(1);
  if (warp == 7) rb = ld_strong(fl);

  static_for<1, NR>([&](auto R) {
    constexpr int r = decltype(R)::value;
    wait_w(r);
    TL(8 + 2 * r);
    slot(acc0, IC<2 * r>{});
    TL(9 + 2 * r);
    slot(acc1, IC<2 * r + 1>{});
  });

  __nv_bfloat16* op = out + (size_t)(xrow + (warp & 3) * 16 + (lane >> 2)) * F_DIM + j * BN + (lane & 3) * 8;
  TL(40); TLG(48);
  if (wg == 1) {
    wgmma_wait<0>();
    release(2 * NR);
    if (warp == 7) {
      wait_ready(14);
      asm volatile("fence.proxy.async.global;" ::: "memory");
      ring_wait<8>(bars + 8 * B_DONE, 2 * NR);
      if (elect_one()) load_w(14);
      unsigned old = 0;
      if (lane == 17) old = atomicAdd(fl, 1u);
      if (__shfl_sync(0xffffffffu, old, 17) == NI - 1) *fl = 0;
    }
    bar_sync(1, 256);
  }
#pragma unroll
  for (int e = 0; e < ENDK; e++) {
    wait_w(end_kb(e));
    ring_wait<XS>(fullx, 2 * NR + e);
    mma(acc0, 2 * NR + e, end_kb(e), 0, 4);
    if (e == ENDK - 1) bar_arrive(1 + wg, 256);
    wgmma_wait<1>();
    if (e > 0 || wg == 0) release(2 * NR + e);
  }
  wgmma_wait<0>();
  release(2 * NR + ENDK);
  TL(41);
  auto delay_to = [&](unsigned t0, unsigned t) {
    while (__any_sync(0xffffffffu, clk32() - t0 < t)) {}
  };
  {
    uint32_t af[4 * ENDK][4];
    const uint32_t abase = sbase + SMEM_X + wg * (XS * X_SLICE) + ((warp & 3) * 16 + (lane & 15)) * 128;
    float accp[112];
    const unsigned t0 = clk32();
#pragma unroll
    for (int J = 0; J < 7; J++) {
      if (J > 0) delay_to(t0, J * ST_GAP);
      store_acc(acc0, op, J, J + 1);
      if (J == 0) {
#pragma unroll
        for (int i = 0; i < 112; i++) asm volatile("add.rn.f32 %0, %1, 0f00000000;" : "=f"(accp[i]) : "f"(acc1[i]));
      }
      if (J >= 1 && J <= ENDK) {
        const int e = J - 1, n = 2 * NR + ENDK + e;
        ring_wait<XS>(fullx, n);
#pragma unroll
        for (int k = 0; k < 4; k++)
          asm volatile("ldmatrix.sync.aligned.m8n8.x4.shared.b16 {%0, %1, %2, %3}, [%4];"
                       : "=r"(af[4 * e + k][0]), "=r"(af[4 * e + k][1]), "=r"(af[4 * e + k][2]), "=r"(af[4 * e + k][3])
                       : "r"(abase + (n % XS) * X_SLICE + (((2 * k + (lane >> 4)) ^ (lane & 7)) << 4))
                       : "memory");
      }
    }
    TL(42);
    auto part = [&](auto P, int s0, int s1) {
      constexpr int p = decltype(P)::value;
      wgmma_fence();
#pragma unroll
      for (int st = s0; st < s1; st++) {
        const int kb = end_kb(st >> 2);
        const uint64_t db = make_desc(db0 + w_ring(kb) * (W_STAGE >> 4) + (st & 3) * (2 * W_KC >> 4) +
                                          (p == 0 ? 0 : 32 + 64 * p), DB_HI);
        if constexpr (p == 0) wgmma_rs_m64n96k16<0>(accp, af[st], db);
        else wgmma_rs_m64n64k16<16 + 32 * p>(accp, af[st], db);
      }
      wgmma_commit();
    };
    bar_sync(2 - wg, 256);
    TL(51);
    part(IC<0>{}, 0, 4 * ENDK);
    part(IC<1>{}, 0, LEAD);
    wgmma_wait<1>();
    if (wg == 1) store_acc(accp, op + 64 * F_DIM, 0, 3);
    part(IC<1>{}, LEAD, 4 * ENDK);
    part(IC<2>{}, 0, LEAD);
    wgmma_wait<1>();
    if (wg == 0) store_acc(accp, op + 64 * F_DIM, 0, 3);
    else store_acc(accp, op + 64 * F_DIM, 3, 5);
    part(IC<2>{}, LEAD, 4 * ENDK);
    if (wg == 0) {
      bar_arrive(1, 256);
      store_acc(accp, op + 64 * F_DIM, 3, 5);
    }
    wgmma_wait<0>();
    TL(43); TLG(47);
    store_acc(accp, op + 64 * F_DIM, 5, 7);
  }
  TL(44);
}

__global__ void __launch_bounds__(BN)
prefill_kernel(const int* __restrict__ qw, const __nv_bfloat16* __restrict__ lut,
               const __nv_bfloat16* __restrict__ scales, uint8_t* scratch) {
  const int j = blockIdx.x & 15, kc = blockIdx.x >> 4, f = j * BN + perm32(threadIdx.x);
  int q[8];
#pragma unroll
  for (int i = 0; i < 8; i++) q[i] = qw[(kc * 8 + i) * F_DIM + f];
  *reinterpret_cast<uint4*>(scratch + (size_t)j * REGION + W_OFF + kc * W_KC + threadIdx.x * 16) =
      convert_unit(q, make_table(__bfloat162float(lut[threadIdx.x & 15]), __bfloat162float(scales[f])));
}

typedef CUresult (*EncodeTiledFn)(CUtensorMap*, CUtensorMapDataType, cuuint32_t, void*, const cuuint64_t*,
                                  const cuuint64_t*, const cuuint32_t*, const cuuint32_t*, CUtensorMapInterleave,
                                  CUtensorMapSwizzle, CUtensorMapL2promotion, CUtensorMapFloatOOBfill);

}

extern "C" void kernel_launch(void* const* d_in, const int* in_sizes, int n_in, void* d_out, int out_size) {
  const __nv_bfloat16* x = (const __nv_bfloat16*)d_in[0];
  const int* qw = (const int*)d_in[1];
  const __nv_bfloat16* lut = (const __nv_bfloat16*)d_in[2];
  const __nv_bfloat16* scales = (const __nv_bfloat16*)d_in[3];
  __nv_bfloat16* out = (__nv_bfloat16*)d_out;

  static EncodeTiledFn enc = nullptr;
  static uint8_t* p_scr = nullptr;
  static bool coresident = false;
  if (!enc) {
    void* fn = nullptr;
    cudaDriverEntryPointQueryResult qr;
    cudaGetDriverEntryPoint("cuTensorMapEncodeTiled", &fn, cudaEnableDefault, &qr);
    enc = (EncodeTiledFn)fn;
    void* p = nullptr;
    cudaGetSymbolAddress(&p, g_scratch);
    p_scr = (uint8_t*)(((uintptr_t)p + REGION - 1) & ~(uintptr_t)(REGION - 1));
    cudaFuncSetAttribute(fused_kernel, cudaFuncAttributeMaxDynamicSharedMemorySize, SMEM_TOTAL);
    int dev = 0, sms = 0;
    cudaGetDevice(&dev);
    cudaDeviceGetAttribute(&sms, cudaDevAttrMultiProcessorCount, dev);
    coresident = sms >= NI * NJ;
  }
  CUtensorMap tm_x, tm_q;
  cuuint32_t estr[2] = {1, 1};
  {
    cuuint64_t gdim[2] = {(cuuint64_t)D_DIM, (cuuint64_t)S_DIM};
    cuuint64_t gstr[1] = {(cuuint64_t)D_DIM * 2};
    cuuint32_t box[2] = {(cuuint32_t)BK, 64};
    enc(&tm_x, CU_TENSOR_MAP_DATA_TYPE_BFLOAT16, 2, (void*)x, gdim, gstr, box, estr, CU_TENSOR_MAP_INTERLEAVE_NONE,
        CU_TENSOR_MAP_SWIZZLE_128B, CU_TENSOR_MAP_L2_PROMOTION_NONE, CU_TENSOR_MAP_FLOAT_OOB_FILL_NONE);
  }
  {
    cuuint64_t gdim[2] = {(cuuint64_t)F_DIM, (cuuint64_t)D_DIM};
    cuuint64_t gstr[1] = {(cuuint64_t)F_DIM * 4};
    cuuint32_t box[2] = {(cuuint32_t)BN, 8};
    enc(&tm_q, CU_TENSOR_MAP_DATA_TYPE_INT32, 2, (void*)qw, gdim, gstr, box, estr, CU_TENSOR_MAP_INTERLEAVE_NONE,
        CU_TENSOR_MAP_SWIZZLE_NONE, CU_TENSOR_MAP_L2_PROMOTION_NONE, CU_TENSOR_MAP_FLOAT_OOB_FILL_NONE);
  }
  if (!coresident) prefill_kernel<<<NJ * NKB * 8, BN, 0, cudaStreamPerThread>>>(qw, lut, scales, p_scr);
  fused_kernel<<<NI * NJ, 256, SMEM_TOTAL, cudaStreamPerThread>>>(qw, lut, scales, out, p_scr,
                                                                  coresident ? FLAG_FULL : 0u, tm_x, tm_q);
}
```

```cpp
#include <cuda_runtime.h>
#include <cuda_bf16.h>
#include <cuda.h>
#include <stdint.h>

namespace {

constexpr int S_DIM = 2048, D_DIM = 1024, F_DIM = 3584;
constexpr int BM = 256, BN = 224, BK = 64;
constexpr int NKB = D_DIM / BK;
constexpr int NJ = F_DIM / BN;
constexpr int NI = S_DIM / BM;
constexpr int WS = 4;
constexpr int XS = 5;
constexpr int ENDK = 5;
constexpr int NR = NKB - ENDK;
constexpr int X_SLICE = 64 * BK * 2;
constexpr int W_STAGE = BN * BK * 2;
constexpr int W_KC = BN * 16;

constexpr int REGION = 512 * 1024;
__device__ uint4 g_scratch[(NJ + 1) * REGION / 16];

__device__ __forceinline__ uint32_t smem_u32(const void* p) { return (uint32_t)__cvta_generic_to_shared(p); }
__device__ __forceinline__ unsigned clk32() {
  unsigned c;
  asm volatile("mov.u32 %0, %%clock;" : "=r"(c)::"memory");
  return c;
}
__device__ __forceinline__ bool elect_one() {
  uint32_t p;
  asm volatile("{\n.reg .pred P;\nelect.sync _|P, 0xffffffff;\nselp.b32 %0, 1, 0, P;\n}" : "=r"(p));
  return p != 0;
}
__device__ __forceinline__ void mbar_init(uint32_t bar, uint32_t cnt) {
  asm volatile("mbarrier.init.shared::cta.b64 [%0], %1;" ::"r"(bar), "r"(cnt) : "memory");
}
__device__ __forceinline__ void mbar_expect_tx(uint32_t bar, uint32_t bytes) {
  asm volatile("mbarrier.arrive.expect_tx.shared::cta.b64 _, [%0], %1;" ::"r"(bar), "r"(bytes) : "memory");
}
__device__ __forceinline__ void mbar_arrive(uint32_t bar) {
  asm volatile("mbarrier.arrive.shared::cta.b64 _, [%0];" ::"r"(bar) : "memory");
}
__device__ __forceinline__ void mbar_wait(uint32_t bar, uint32_t parity) {
  asm volatile(
      "{\n.reg .pred p;\n"
      "LAB_WAIT:\n"
      "mbarrier.try_wait.parity.shared::cta.b64 p, [%0], %1;\n"
      "@p bra LAB_DONE;\n"
      "bra LAB_WAIT;\n"
      "LAB_DONE:\n}\n" ::"r"(bar), "r"(parity) : "memory");
}
template <int N>
__device__ __forceinline__ uint32_t ring(uint32_t base, int i) { return base + 8 * (i % N); }
template <int N>
__device__ __forceinline__ void ring_wait(uint32_t base, int i) { mbar_wait(ring<N>(base, i), (i / N) & 1); }
__device__ __forceinline__ void tma_load_2d(uint32_t dst, const CUtensorMap* tm, int c0, int c1, uint32_t bar) {
  asm volatile(
      "cp.async.bulk.tensor.2d.shared::cluster.global.mbarrier::complete_tx::bytes [%0], [%1, {%3, %4}], [%2];"
      ::"r"(dst), "l"(tm), "r"(bar), "r"(c0), "r"(c1) : "memory");
}
__device__ __forceinline__ void bulk_load(uint32_t dst, const void* src, uint32_t bytes, uint32_t bar) {
  asm volatile(
      "cp.async.bulk.shared::cluster.global.mbarrier::complete_tx::bytes [%0], [%1], %2, [%3];"
      ::"r"(dst), "l"(src), "r"(bytes), "r"(bar) : "memory");
}
__device__ __forceinline__ void cp_async16(uint32_t dst, const void* src) {
  asm volatile("cp.async.cg.shared.global [%0], [%1], 16;" ::"r"(dst), "l"(src) : "memory");
}
__device__ __forceinline__ void cp_async_commit() { asm volatile("cp.async.commit_group;" ::: "memory"); }
template <int N>
__device__ __forceinline__ void cp_async_wait() { asm volatile("cp.async.wait_group %0;" ::"n"(N) : "memory"); }
__device__ __forceinline__ uint32_t ldg_u16(const void* p) {
  uint32_t v;
  asm volatile("ld.global.u16 %0, [%1];" : "=r"(v) : "l"(p) : "memory");
  return v;
}
__device__ __forceinline__ int lds32(uint32_t addr) {
  int v;
  asm volatile("ld.shared.b32 %0, [%1];" : "=r"(v) : "r"(addr) : "memory");
  return v;
}
__device__ __forceinline__ void sts128(uint32_t addr, uint4 v) {
  asm volatile("st.shared.v4.u32 [%0], {%1, %2, %3, %4};" ::"r"(addr), "r"(v.x), "r"(v.y), "r"(v.z), "r"(v.w) : "memory");
}
__device__ __forceinline__ uint64_t make_desc(uint32_t lo, uint32_t hi) {
  uint64_t d;
  asm("mov.b64 %0, {%1, %2};" : "=l"(d) : "r"(lo), "r"(hi));
  return d;
}
__device__ __forceinline__ unsigned ld_strong(const void* p) {
  unsigned v;
  asm volatile("ld.relaxed.gpu.global.u32 %0, [%1];" : "=r"(v) : "l"(p) : "memory");
  return v;
}
__device__ __forceinline__ void st_strong128(void* p, uint4 v) {
  asm volatile("st.relaxed.gpu.global.v4.u32 [%0], {%1, %2, %3, %4};" ::"l"(p), "r"(v.x), "r"(v.y), "r"(v.z), "r"(v.w)
               : "memory");
}
__device__ __forceinline__ void wgmma_fence() { asm volatile("wgmma.fence.sync.aligned;" ::: "memory"); }
__device__ __forceinline__ void wgmma_commit() { asm volatile("wgmma.commit_group.sync.aligned;" ::: "memory"); }
template <int N>
__device__ __forceinline__ void wgmma_wait() { asm volatile("wgmma.wait_group.sync.aligned %0;" ::"n"(N) : "memory"); }
__device__ __forceinline__ void bar_sync(int id, int n) { asm volatile("bar.sync %0, %1;" ::"r"(id), "r"(n) : "memory"); }
__device__ __forceinline__ void bar_arrive(int id, int n) { asm volatile("bar.arrive %0, %1;" ::"r"(id), "r"(n) : "memory"); }

__device__ __forceinline__ void wgmma_m64n224k16(float (&d)[112], uint64_t da, uint64_t db, int scale_d) {
  asm volatile(
    "{\n.reg .pred p;\nsetp.ne.b32 p, %114, 0;\n"
    "wgmma.mma_async.sync.aligned.m64n224k16.f32.bf16.bf16 "
    "{%0, %1, %2, %3, %4, %5, %6, %7, %8, %9, %10, %11, %12, %13, %14, %15, "
    "%16, %17, %18, %19, %20, %21, %22, %23, %24, %25, %26, %27, %28, %29, %30, %31, "
    "%32, %33, %34, %35, %36, %37, %38, %39, %40, %41, %42, %43, %44, %45, %46, %47, "
    "%48, %49, %50, %51, %52, %53, %54, %55, %56, %57, %58, %59, %60, %61, %62, %63, "
    "%64, %65, %66, %67, %68, %69, %70, %71, %72, %73, %74, %75, %76, %77, %78, %79, "
    "%80, %81, %82, %83, %84, %85, %86, %87, %88, %89, %90, %91, %92, %93, %94, %95, "
    "%96, %97, %98, %99, %100, %101, %102, %103, %104, %105, %106, %107, %108, %109, %110, %111}, "
    "%112, %113, p, 1, 1, 0, 0;\n}\n"
    : "+f"(d[0]), "+f"(d[1]), "+f"(d[2]), "+f"(d[3]), "+f"(d[4]), "+f"(d[5]), "+f"(d[6]), "+f"(d[7]),
      "+f"(d[8]), "+f"(d[9]), "+f"(d[10]), "+f"(d[11]), "+f"(d[12]), "+f"(d[13]), "+f"(d[14]), "+f"(d[15]),
      "+f"(d[16]), "+f"(d[17]), "+f"(d[18]), "+f"(d[19]), "+f"(d[20]), "+f"(d[21]), "+f"(d[22]), "+f"(d[23]),
      "+f"(d[24]), "+f"(d[25]), "+f"(d[26]), "+f"(d[27]), "+f"(d[28]), "+f"(d[29]), "+f"(d[30]), "+f"(d[31]),
      "+f"(d[32]), "+f"(d[33]), "+f"(d[34]), "+f"(d[35]), "+f"(d[36]), "+f"(d[37]), "+f"(d[38]), "+f"(d[39]),
      "+f"(d[40]), "+f"(d[41]), "+f"(d[42]), "+f"(d[43]), "+f"(d[44]), "+f"(d[45]), "+f"(d[46]), "+f"(d[47]),
      "+f"(d[48]), "+f"(d[49]), "+f"(d[50]), "+f"(d[51]), "+f"(d[52]), "+f"(d[53]), "+f"(d[54]), "+f"(d[55]),
      "+f"(d[56]), "+f"(d[57]), "+f"(d[58]), "+f"(d[59]), "+f"(d[60]), "+f"(d[61]), "+f"(d[62]), "+f"(d[63]),
      "+f"(d[64]), "+f"(d[65]), "+f"(d[66]), "+f"(d[67]), "+f"(d[68]), "+f"(d[69]), "+f"(d[70]), "+f"(d[71]),
      "+f"(d[72]), "+f"(d[73]), "+f"(d[74]), "+f"(d[75]), "+f"(d[76]), "+f"(d[77]), "+f"(d[78]), "+f"(d[79]),
      "+f"(d[80]), "+f"(d[81]), "+f"(d[82]), "+f"(d[83]), "+f"(d[84]), "+f"(d[85]), "+f"(d[86]), "+f"(d[87]),
      "+f"(d[88]), "+f"(d[89]), "+f"(d[90]), "+f"(d[91]), "+f"(d[92]), "+f"(d[93]), "+f"(d[94]), "+f"(d[95]),
      "+f"(d[96]), "+f"(d[97]), "+f"(d[98]), "+f"(d[99]), "+f"(d[100]), "+f"(d[101]), "+f"(d[102]), "+f"(d[103]),
      "+f"(d[104]), "+f"(d[105]), "+f"(d[106]), "+f"(d[107]), "+f"(d[108]), "+f"(d[109]), "+f"(d[110]), "+f"(d[111])
    : "l"(da), "l"(db), "r"(scale_d));
}
template <int O>
__device__ __forceinline__ void wgmma_rs_m64n96k16(float (&d)[112], const uint32_t (&a)[4], uint64_t db) {
  asm volatile(
    "wgmma.mma_async.sync.aligned.m64n96k16.f32.bf16.bf16 "
    "{%0, %1, %2, %3, %4, %5, %6, %7, %8, %9, %10, %11, %12, %13, %14, %15, "
    "%16, %17, %18, %19, %20, %21, %22, %23, %24, %25, %26, %27, %28, %29, %30, %31, "
    "%32, %33, %34, %35, %36, %37, %38, %39, %40, %41, %42, %43, %44, %45, %46, %47}, "
    "{%48, %49, %50, %51}, %52, 1, 1, 1, 0;\n"
    : "+f"(d[O + 0]), "+f"(d[O + 1]), "+f"(d[O + 2]), "+f"(d[O + 3]),
      "+f"(d[O + 4]), "+f"(d[O + 5]), "+f"(d[O + 6]), "+f"(d[O + 7]),
      "+f"(d[O + 8]), "+f"(d[O + 9]), "+f"(d[O + 10]), "+f"(d[O + 11]),
      "+f"(d[O + 12]), "+f"(d[O + 13]), "+f"(d[O + 14]), "+f"(d[O + 15]),
      "+f"(d[O + 16]), "+f"(d[O + 17]), "+f"(d[O + 18]), "+f"(d[O + 19]),
      "+f"(d[O + 20]), "+f"(d[O + 21]), "+f"(d[O + 22]), "+f"(d[O + 23]),
      "+f"(d[O + 24]), "+f"(d[O + 25]), "+f"(d[O + 26]), "+f"(d[O + 27]),
      "+f"(d[O + 28]), "+f"(d[O + 29]), "+f"(d[O + 30]), "+f"(d[O + 31]),
      "+f"(d[O + 32]), "+f"(d[O + 33]), "+f"(d[O + 34]), "+f"(d[O + 35]),
      "+f"(d[O + 36]), "+f"(d[O + 37]), "+f"(d[O + 38]), "+f"(d[O + 39]),
      "+f"(d[O + 40]), "+f"(d[O + 41]), "+f"(d[O + 42]), "+f"(d[O + 43]),
      "+f"(d[O + 44]), "+f"(d[O + 45]), "+f"(d[O + 46]), "+f"(d[O + 47])
    : "r"(a[0]), "r"(a[1]), "r"(a[2]), "r"(a[3]), "l"(db));
}
template <int O>
__device__ __forceinline__ void wgmma_rs_m64n64k16(float (&d)[112], const uint32_t (&a)[4], uint64_t db) {
  asm volatile(
    "wgmma.mma_async.sync.aligned.m64n64k16.f32.bf16.bf16 "
    "{%0, %1, %2, %3, %4, %5, %6, %7, %8, %9, %10, %11, %12, %13, %14, %15, "
    "%16, %17, %18, %19, %20, %21, %22, %23, %24, %25, %26, %27, %28, %29, %30, %31}, "
    "{%32, %33, %34, %35}, %36, 1, 1, 1, 0;\n"
    : "+f"(d[O + 0]), "+f"(d[O + 1]), "+f"(d[O + 2]), "+f"(d[O + 3]),
      "+f"(d[O + 4]), "+f"(d[O + 5]), "+f"(d[O + 6]), "+f"(d[O + 7]),
      "+f"(d[O + 8]), "+f"(d[O + 9]), "+f"(d[O + 10]), "+f"(d[O + 11]),
      "+f"(d[O + 12]), "+f"(d[O + 13]), "+f"(d[O + 14]), "+f"(d[O + 15]),
      "+f"(d[O + 16]), "+f"(d[O + 17]), "+f"(d[O + 18]), "+f"(d[O + 19]),
      "+f"(d[O + 20]), "+f"(d[O + 21]), "+f"(d[O + 22]), "+f"(d[O + 23]),
      "+f"(d[O + 24]), "+f"(d[O + 25]), "+f"(d[O + 26]), "+f"(d[O + 27]),
      "+f"(d[O + 28]), "+f"(d[O + 29]), "+f"(d[O + 30]), "+f"(d[O + 31])
    : "r"(a[0]), "r"(a[1]), "r"(a[2]), "r"(a[3]), "l"(db));
}

__device__ __forceinline__ uint32_t pack_bf16(float lo, float hi) {
  uint32_t r;
  asm("cvt.rn.bf16x2.f32 %0, %1, %2;" : "=r"(r) : "f"(hi), "f"(lo));
  return r;
}

__device__ __forceinline__ int perm32(int n) { return (n & ~30) | ((n & 6) << 2) | ((n >> 2) & 6); }

constexpr int SMEM_X = 0;
constexpr int SMEM_W = 2 * XS * X_SLICE;
constexpr int SMEM_Q = SMEM_W + WS * W_STAGE;
constexpr int Q_UNIT = 8 * BN * 4;
constexpr int SMEM_BAR = SMEM_Q + W_STAGE;
constexpr int B_FULLW = 0, B_FULLQ = 5, B_FULLX = 9, B_DONE = 19, B_W0 = 35, B_RAW0 = 36;
constexpr int SMEM_TL = SMEM_BAR + 512;
constexpr int SMEM_TOTAL = SMEM_TL;
constexpr int W_OFF = 128;
constexpr unsigned FLAG_FULL = NI * 7;

#define TL(i)
#define TLG(i)

__device__ __forceinline__ void store_acc(const float (&a)[112], __nv_bfloat16* p, int J0, int J1) {
#pragma unroll
  for (int J = J0; J < J1; J++) {
    uint4 v0, v1;
    v0.x = pack_bf16(a[16 * J + 0], a[16 * J + 1]);
    v0.y = pack_bf16(a[16 * J + 4], a[16 * J + 5]);
    v0.z = pack_bf16(a[16 * J + 8], a[16 * J + 9]);
    v0.w = pack_bf16(a[16 * J + 12], a[16 * J + 13]);
    v1.x = pack_bf16(a[16 * J + 2], a[16 * J + 3]);
    v1.y = pack_bf16(a[16 * J + 6], a[16 * J + 7]);
    v1.z = pack_bf16(a[16 * J + 10], a[16 * J + 11]);
    v1.w = pack_bf16(a[16 * J + 14], a[16 * J + 15]);
    *reinterpret_cast<uint4*>(p + 32 * J) = v0;
    *reinterpret_cast<uint4*>(p + 8 * F_DIM + 32 * J) = v1;
  }
}

struct Table {
  uint32_t lo[4], hi[4];
};
__device__ __forceinline__ uint32_t prmt(uint32_t a, uint32_t b, uint32_t s) {
  uint32_t r;
  asm("prmt.b32 %0, %1, %2, %3;" : "=r"(r) : "r"(a), "r"(b), "r"(s));
  return r;
}
__device__ __forceinline__ Table make_table(float lutv, float sc) {
  Table t;
#pragma unroll
  for (int i = 0; i < 4; i++) {
    const uint32_t a = pack_bf16(__shfl_sync(0xffffffffu, lutv, 4 * i) * sc, __shfl_sync(0xffffffffu, lutv, 4 * i + 1) * sc);
    const uint32_t b =
        pack_bf16(__shfl_sync(0xffffffffu, lutv, 4 * i + 2) * sc, __shfl_sync(0xffffffffu, lutv, 4 * i + 3) * sc);
    t.lo[i] = prmt(a, b, 0x6420);
    t.hi[i] = prmt(a, b, 0x7531);
  }
  return t;
}
__device__ __forceinline__ uint4 convert_unit(const int (&q)[8], const Table& t) {
  const uint32_t all = ((q[7] * 16 + q[6]) * 256 + (q[5] * 16 + q[4])) * 65536 + ((q[3] * 16 + q[2]) * 256 + (q[1] * 16 + q[0]));
  const uint32_t s7 = all & 0x77777777u;
  const uint32_t s2 = ((all >> 1) & 0x44444444u) | 0x32103210u;
  uint32_t o[4];
#pragma unroll
  for (int h = 0; h < 2; h++) {
    const uint32_t a = h ? s7 >> 16 : s7, b = h ? s2 >> 16 : s2;
    const uint32_t lo = prmt(prmt(t.lo[0], t.lo[1], a), prmt(t.lo[2], t.lo[3], a), b);
    const uint32_t hi = prmt(prmt(t.hi[0], t.hi[1], a), prmt(t.hi[2], t.hi[3], a), b);
    o[2 * h] = prmt(lo, hi, 0x5140);
    o[2 * h + 1] = prmt(lo, hi, 0x7362);
  }
  return make_uint4(o[0], o[1], o[2], o[3]);
}

constexpr int PU = 3;
#define HEAVY 0x3BBBAu
__host__ __device__ constexpr int popc(unsigned v) { return v ? (v & 1) + popc(v >> 1) : 0; }
__host__ __device__ constexpr bool heavy(int n) { return n >= 0 && ((HEAVY >> n) & 1); }
__host__ __device__ constexpr int unit_at(int n) { return PU + popc(HEAVY & ((1u << n) - 1)); }
__host__ __device__ constexpr int emit_slot(int u) {
  if (u < PU) return -1;
  for (int n = 0; n < 24; n++)
    if (heavy(n) && unit_at(n) == u) return n;
  return 99;
}
__host__ __device__ constexpr int end_kb(int e) { return e < 3 ? NR + e : NR + 7 - e; }
__host__ __device__ constexpr int w_ring(int m) { return m == 15 ? 4 : m & 3; }
__host__ __device__ constexpr int cmax(int a, int b) { return a > b ? a : b; }
__host__ __device__ constexpr int w_slot(int m) {
  return m == 15 ? cmax(emit_slot(15) + 3, 20) : cmax(2 * m - 5, emit_slot(m) + 3);
}
__host__ __device__ constexpr int q_slot(int u) {
  return u == 5 ? 1 : cmax(q_slot(u - 1) + 1, u < 8 ? 2 : u == 8 ? 4 : emit_slot(u - 5) + 2);
}
__host__ __device__ constexpr int w_at(int n) {
  for (int m = 2; m < NKB; m++)
    if (w_slot(m) == n) return m;
  return -1;
}
__host__ __device__ constexpr int q_at(int n) {
  for (int u = 5; u < NKB; u++)
    if (q_slot(u) == n) return u;
  return -1;
}
constexpr bool schedule_ok() {
  if (popc(HEAVY) != NKB - PU || (HEAVY & 7) != 2 || (HEAVY >> 20)) return false;
  for (int m = 2; m < NKB; m++) {
    if (w_at(w_slot(m)) != m || (m != 14 && w_slot(m) >= 2 * NR)) return false;
    if (m < NR && w_slot(m) > 2 * m - 2) return false;
  }
  for (int u = 5; u < NKB; u++)
    if (q_slot(u) + 2 > emit_slot(u - 1)) return false;
  return true;
}
static_assert(schedule_ok(), "bad schedule");
template <int V>
struct IC {
  static constexpr int value = V;
};
template <int I, int N, class F>
__device__ __forceinline__ void static_for(F&& f) {
  if constexpr (I < N) {
    f(IC<I>{});
    static_for<I + 1, N>(f);
  }
}

#define NCP 3
#define RSPLIT 5
#define STAG_L 70
#define PACE_INIT 550
#define PACE_X 950
#define PACE_Q2 1450
#define PACE_Q3 1950
#define PUB_AT 6
#define ST_GAP 150
#define LEAD 8

constexpr uint32_t sbase = 1024;

__global__ void __launch_bounds__(256, 1)
fused_kernel(const int* __restrict__ qw, const __nv_bfloat16* __restrict__ lut,
             const __nv_bfloat16* __restrict__ scales, __nv_bfloat16* __restrict__ out, uint8_t* scratch,
             unsigned flag_full,
             const __grid_constant__ CUtensorMap tm_x, const __grid_constant__ CUtensorMap tm_q) {
  extern __shared__ __align__(1024) uint8_t smem_raw[];
  constexpr uint32_t bars = sbase + SMEM_BAR;
  const int j = blockIdx.x >> 3, it = blockIdx.x & 7;
  constexpr uint32_t raw0 = sbase + SMEM_W + 2 * W_STAGE;
  uint32_t lut_raw = 0, sc_raw = 0;
  if (threadIdx.x < 224) {
    const unsigned t = threadIdx.x, row0 = (t >> 3) & 3, col = (t & ~31u) + (t & 7) * 4;
    const int* src = qw + (row0 * F_DIM + j * BN + col);
    const uint32_t dst = row0 * (BN * 4) + col * 4;
    lut_raw = ldg_u16(lut + (t & 15));
    sc_raw = ldg_u16(scales + (j * BN + perm32(t)));
    __syncwarp();
#pragma unroll
    for (int g = 0; g < NCP + 1; g++) {
      const unsigned row = g == 0 ? BK + it * 8 : (g - 1) * 8;
      const uint32_t d = dst + (g == 0 ? sbase + SMEM_Q + Q_UNIT : raw0 + (g - 1) * Q_UNIT);
      cp_async16(d, src + row * F_DIM);
      cp_async16(d + 4 * BN * 4, src + (row + 4) * F_DIM);
      cp_async_commit();
    }
  }
  const int warp = __shfl_sync(0xffffffffu, threadIdx.x >> 5, 0);
  const int wg = warp >> 2;
  int lane;
  asm volatile("mov.u32 %0, %%laneid;" : "=r"(lane));
  const unsigned t_start = clk32();
  auto pace = [&](unsigned t) {
    while (__any_sync(0xffffffffu, clk32() - t_start < t)) {}
  };

  uint8_t* const region = scratch + (size_t)j * REGION;
  uint8_t* const wp = region + (warp < 7 ? W_OFF + it * W_KC + (warp * 32 + lane) * 16 : lane * 4);
  unsigned* const fl = reinterpret_cast<unsigned*>(wp);
  Table tab;
  unsigned rb;
  const int xrow = it * BM + wg * 128;

  auto w_ptr = [&](int u) { return reinterpret_cast<uint4*>(wp + u * W_STAGE); };
  auto emit_unit = [&](uint4 w, int u) {
    st_strong128(w_ptr(u), w);
    rb = ld_strong(w_ptr(u));
  };
  auto publish = [&](int u) {
    asm volatile(
        "{\n.reg .pred P, Q;\n"
        "setp.ne.u32 P, %1, 0xffffffff;\n"
        "vote.sync.all.pred P, P, 0xffffffff;\n"
        "elect.sync _|Q, 0xffffffff;\n"
        "and.pred Q, Q, P;\n"
        "@Q red.relaxed.gpu.global.add.u32 [%0], 1;\n}"
        ::"l"(region + u * 4), "r"(rb) : "memory");
  };
  auto load_x = [&](int g, int n, int kb, int half) {
    const uint32_t bar = ring<XS>(bars + 8 * B_FULLX, n) + g * (8 * XS);
    mbar_expect_tx(bar, X_SLICE);
    tma_load_2d(sbase + SMEM_X + (n % XS) * X_SLICE + g * (XS * X_SLICE), &tm_x, kb * BK,
                it * BM + g * 128 + half * 64, bar);
  };
  auto load_q = [&](int u) {
    const uint32_t bar = ring<4>(bars + 8 * B_FULLQ, u);
    mbar_expect_tx(bar, Q_UNIT);
    tma_load_2d(sbase + SMEM_Q + (u & 3) * Q_UNIT, &tm_q, j * BN, u * BK + it * 8, bar);
  };

  unsigned ready = 0;
  auto load_w = [&](int m) {
    const uint32_t bar = bars + 8 * (B_FULLW + w_ring(m));
    mbar_expect_tx(bar, W_STAGE);
    bulk_load(sbase + SMEM_W + w_ring(m) * W_STAGE, region + W_OFF + m * W_STAGE, W_STAGE, bar);
  };
  auto wait_w = [&](int m) { mbar_wait(bars + 8 * (B_FULLW + w_ring(m)), m == 15 ? 0 : (m >> 2) & 1); };
  auto poll = [&]() { ready |= __ballot_sync(0xffffffffu, ld_strong(fl) >= flag_full); };
  auto wait_ready = [&](int kb) {
    int spins = 0;
    while (!((ready >> kb) & 1)) {
      poll();
      if (++spins > (1 << 22)) __trap();
    }
  };

  uint32_t qbase;
  asm volatile("mov.u32 %0, %1;" : "=r"(qbase) : "r"(sbase + SMEM_Q + warp * 128 + perm32(lane) * 4));
  auto lds_unit = [&](int (&q)[8], int u) {
    ring_wait<4>(bars + 8 * B_FULLQ, u);
#pragma unroll
    for (int i = 0; i < 8; i++) q[i] = lds32(qbase + (u & 3) * Q_UNIT + i * (BN * 4));
  };
  auto arrive_one = [&](uint32_t bar) {
    asm volatile("{\n.reg .pred P;\nelect.sync _|P, 0xffffffff;\n@P mbarrier.arrive.shared::cta.b64 _, [%0];\n}"
                 ::"r"(bar) : "memory");
  };

  int q[8];
  if (warp == 7) {
    if (elect_one()) {
      mbar_init(bars + 8 * B_RAW0, RSPLIT - NCP);
      mbar_init(bars + 8 * B_RAW0 + 8, 8 - RSPLIT);
      asm volatile("fence.mbarrier_init.release.cluster;" ::: "memory");
    }
    __syncwarp();
    bar_arrive(4, (9 - NCP) * 32);
    if (elect_one()) {
      asm volatile("prefetch.tensormap [%0];" ::"l"(&tm_x) : "memory");
      asm volatile("prefetch.tensormap [%0];" ::"l"(&tm_q) : "memory");
    }
    TL(5);
    pace(PACE_INIT);
    if (elect_one()) {
#pragma unroll
      for (int i = 0; i < B_RAW0; i++) mbar_init(bars + 8 * i, i == B_W0 ? 7 : i >= B_DONE ? 4 : 1);
      asm volatile("fence.mbarrier_init.release.cluster;" ::: "memory");
    }
    __syncwarp();
    rb = ld_strong(fl);
    bar_arrive(0, 256);
    TL(4);
#pragma unroll
    for (int i = 0; i < 4; i++) tab.lo[i] = tab.hi[i] = 0;
    if (smem_u32(smem_raw) != sbase) __trap();
    if (elect_one()) {
      mbar_arrive(bars + 8 * B_FULLW);
      mbar_arrive(bars + 8 * B_FULLQ);
      mbar_arrive(bars + 8 * B_FULLQ + 8);
    }
    pace(PACE_X);
    if (elect_one()) {
      load_x(0, 0, 0, 0); load_x(1, 0, 0, 0); load_x(0, 1, 0, 1); load_x(1, 1, 0, 1);
    }
    pace(PACE_Q2);
    if (elect_one()) load_q(2);
    pace(PACE_Q3);
    ready = __ballot_sync(0xffffffffu, rb >= flag_full);
    rb = ld_strong(fl);
    if (elect_one()) {
      load_q(3);
      load_x(0, 2, 1, 0); load_x(1, 2, 1, 0); load_x(0, 3, 1, 1); load_x(1, 3, 1, 1);
    }
    ready |= __ballot_sync(0xffffffffu, rb >= flag_full);
    wait_ready(1);
    asm volatile("fence.proxy.async.global;" ::: "memory");
    if (elect_one()) {
      load_w(1);
      load_q(4);
      load_x(0, 4, 2, 0); load_x(1, 4, 2, 0);
    }
    TL(2);
    TL(3);
  } else {
    if (warp + NCP < 8) {
      bar_sync(4, (9 - NCP) * 32);
      pace(warp * STAG_L);
      if (elect_one()) {
        const int c = warp + NCP;
        const uint32_t bar = bars + 8 * B_RAW0 + (c < RSPLIT ? 0 : 8);
        mbar_expect_tx(bar, Q_UNIT);
#pragma unroll
        for (int i = 0; i < 8; i++)
          bulk_load(raw0 + (c * 8 + i) * (BN * 4), qw + (size_t)(c * 8 + i) * F_DIM + j * BN, BN * 4, bar);
      }
    }
    bar_sync(0, 256);
    pace(200);
    asm volatile("shl.b32 %0, %0, 16;\nshl.b32 %1, %1, 16;" : "+r"(lut_raw), "+r"(sc_raw));
    tab = make_table(__uint_as_float(lut_raw), __uint_as_float(sc_raw));
    if (__any_sync(0xffffffffu, lane > 31 && (tab.lo[0] ^ tab.lo[1] ^ tab.lo[2] ^ tab.lo[3] ^ tab.hi[0] ^ tab.hi[1] ^
                                              tab.hi[2] ^ tab.hi[3]) == 1))
      __trap();
    int r[2][8];
    auto lds_group = [&](auto G) {
      constexpr int g = decltype(G)::value, c = g > 0 ? g - 1 : 0;
      if constexpr (g <= NCP) {
        cp_async_wait<NCP - g>();
        __syncwarp();
      } else {
        if (c == NCP) mbar_wait(bars + 8 * B_RAW0, 0);
        if (c == RSPLIT) mbar_wait(bars + 8 * B_RAW0 + 8, 0);
      }
#pragma unroll
      for (int i = 0; i < 8; i++)
        r[g & 1][i] = lds32(qbase + (g == 0 ? Q_UNIT : raw0 - sbase - SMEM_Q + c * Q_UNIT) + i * (BN * 4));
    };
    lds_group(IC<0>{});
    TL(6);
    static_for<0, 9>([&](auto G) {
      constexpr int g = decltype(G)::value, c = g > 0 ? g - 1 : 0;
      if (g == PUB_AT) {
        publish(1);
        TL(3);
      }
      if (g == 0) {
        emit_unit(convert_unit(r[g & 1], tab), 1);
        __syncwarp();
        TL(2);
        if constexpr (g < 8) lds_group(IC<g + 1>{});
      } else {
        if constexpr (g < 8) lds_group(IC<g + 1>{});
        sts128(sbase + SMEM_W + c * W_KC + (warp * 32 + lane) * 16, convert_unit(r[g & 1], tab));
      }
    });
    asm volatile("fence.proxy.async.shared::cta;" ::: "memory");
    __syncwarp();
    arrive_one(bars + 8 * B_W0);
    TL(4);
    if (wg == 1) {
      lds_unit(r[0], 2);
      emit_unit(convert_unit(r[0], tab), 2);
    }
    TL(5);
  }

  float acc0[112], acc1[112];
  constexpr uint32_t DA_HI = (1u << 30) | (1024 >> 4), DB_HI = (128 >> 4);
  const uint32_t da0 = ((1u << 16) | ((sbase + SMEM_X) >> 4)) + wg * (XS * X_SLICE >> 4);
  constexpr uint32_t db0 = ((W_KC >> 4) << 16) | ((sbase + SMEM_W) >> 4);
  const uint32_t fullx = bars + 8 * B_FULLX + wg * (8 * XS), done = bars + 8 * B_DONE + wg * 64;
  const bool x_issuer = (warp & 3) == 3;

  auto mma = [&](float (&acc)[112], int n, int kb, int k0, int k1) {
    wgmma_fence();
#pragma unroll
    for (int k = k0; k < k1; k++)
      wgmma_m64n224k16(acc, make_desc(da0 + (n % XS) * (X_SLICE >> 4) + k * 2, DA_HI),
                       make_desc(db0 + w_ring(kb) * (W_STAGE >> 4) + k * (2 * W_KC >> 4), DB_HI), kb != 0 || k != 0);
    wgmma_commit();
  };
  auto release = [&](int n) {
    arrive_one(ring<8>(done, n));
    if (x_issuer) {
      ring_wait<8>(done, n);
      const int m = n + 4;
      if (elect_one())
        load_x(wg, m, m < 2 * NR ? m >> 1 : end_kb((m - 2 * NR) % ENDK), m < 2 * NR ? m & 1 : (m - 2 * NR) / ENDK);
    }
  };
  auto end_slot = [&](int n) {
    wgmma_wait<1>();
    release(n);
  };
  auto slot = [&](float (&acc)[112], auto N) {
    constexpr int n = decltype(N)::value;
    constexpr bool hv = heavy(n), pub = heavy(n - 1);
    ring_wait<XS>(fullx, n);
    mma(acc, n, n >> 1, 0, 4);
    end_slot(n);
    if (warp < 7) {
      constexpr int u = unit_at(n);
      if (pub) publish(u - 1);
      if (n == 2) lds_unit(q, 4);
      if (hv) {
        emit_unit(convert_unit(q, tab), u);
        if (u + 1 < NKB) lds_unit(q, u + 1);
      }
    } else {
      constexpr int m = w_at(n), u = q_at(n), m_next = w_at(n + 1);
      if (m >= 0 || u >= 0) ring_wait<8>(bars + 8 * B_DONE, n - 1);
      if (m >= 0) {
        ready |= __ballot_sync(0xffffffffu, rb >= flag_full);
        wait_ready(m);
        asm volatile("fence.proxy.async.global;" ::: "memory");
      }
      if (m_next >= 0) rb = ld_strong(fl);
      if ((m >= 0 || u >= 0) && elect_one()) {
        if (m >= 0) load_w(m);
        if (u >= 0) load_q(u);
      }
    }
  };

  mbar_wait(bars + 8 * B_W0, 0);
  mbar_wait(fullx, 0);
  TL(8); TLG(46);
  mma(acc0, 0, 0, 0, 4);
  mbar_wait(fullx + 8, 0);
  TL(9);
  mma(acc1, 1, 0, 0, 4);
  arrive_one(done);
  if (warp < 7) {
    if (wg == 0) {
      int q2[8];
      lds_unit(q2, 2);
      emit_unit(convert_unit(q2, tab), 2);
    } else {
      publish(2);
    }
    int q3[8];
    lds_unit(q3, 3);
    const uint4 w3 = convert_unit(q3, tab);
    if (wg == 0) publish(2);
    emit_unit(w3, 3);
  } else {
    if (elect_one()) load_q(5);
  }
  end_slot(1);
  if (warp == 7) rb = ld_strong(fl);

  static_for<1, NR>([&](auto R) {
    constexpr int r = decltype(R)::value;
    wait_w(r);
    TL(8 + 2 * r);
    slot(acc0, IC<2 * r>{});
    TL(9 + 2 * r);
    slot(acc1, IC<2 * r + 1>{});
  });

  __nv_bfloat16* op = out + (size_t)(xrow + (warp & 3) * 16 + (lane >> 2)) * F_DIM + j * BN + (lane & 3) * 8;
  TL(40); TLG(48);
  if (wg == 1) {
    wgmma_wait<0>();
    release(2 * NR);
    if (warp == 7) {
      wait_ready(14);
      asm volatile("fence.proxy.async.global;" ::: "memory");
      ring_wait<8>(bars + 8 * B_DONE, 2 * NR);
      if (elect_one()) load_w(14);
      unsigned old = 0;
      if (lane == 17) old = atomicAdd(fl, 1u);
      if (__shfl_sync(0xffffffffu, old, 17) == NI - 1) *fl = 0;
    }
    bar_sync(1, 256);
  }
#pragma unroll
  for (int e = 0; e < ENDK; e++) {
    wait_w(end_kb(e));
    ring_wait<XS>(fullx, 2 * NR + e);
    mma(acc0, 2 * NR + e, end_kb(e), 0, 4);
    if (e == ENDK - 1) bar_arrive(1 + wg, 256);
    wgmma_wait<1>();
    if (e > 0 || wg == 0) release(2 * NR + e);
  }
  wgmma_wait<0>();
  release(2 * NR + ENDK);
  TL(41);
  auto delay_to = [&](unsigned t0, unsigned t) {
    while (__any_sync(0xffffffffu, clk32() - t0 < t)) {}
  };
  {
    uint32_t af[4 * ENDK][4];
    const uint32_t abase = sbase + SMEM_X + wg * (XS * X_SLICE) + ((warp & 3) * 16 + (lane & 15)) * 128;
    float accp[112];
    const unsigned t0 = clk32();
#pragma unroll
    for (int J = 0; J < 7; J++) {
      if (J > 0) delay_to(t0, J * ST_GAP);
      store_acc(acc0, op, J, J + 1);
      if (J == 0) {
#pragma unroll
        for (int i = 0; i < 112; i++) asm volatile("add.rn.f32 %0, %1, 0f00000000;" : "=f"(accp[i]) : "f"(acc1[i]));
      }
      if (J >= 1 && J <= ENDK) {
        const int e = J - 1, n = 2 * NR + ENDK + e;
        ring_wait<XS>(fullx, n);
#pragma unroll
        for (int k = 0; k < 4; k++)
          asm volatile("ldmatrix.sync.aligned.m8n8.x4.shared.b16 {%0, %1, %2, %3}, [%4];"
                       : "=r"(af[4 * e + k][0]), "=r"(af[4 * e + k][1]), "=r"(af[4 * e + k][2]), "=r"(af[4 * e + k][3])
                       : "r"(abase + (n % XS) * X_SLICE + (((2 * k + (lane >> 4)) ^ (lane & 7)) << 4))
                       : "memory");
      }
    }
    TL(42);
    auto part = [&](auto P, int s0, int s1) {
      constexpr int p = decltype(P)::value;
      wgmma_fence();
#pragma unroll
      for (int st = s0; st < s1; st++) {
        const int kb = end_kb(st >> 2);
        const uint64_t db = make_desc(db0 + w_ring(kb) * (W_STAGE >> 4) + (st & 3) * (2 * W_KC >> 4) +
                                          (p == 0 ? 0 : 32 + 64 * p), DB_HI);
        if constexpr (p == 0) wgmma_rs_m64n96k16<0>(accp, af[st], db);
        else wgmma_rs_m64n64k16<16 + 32 * p>(accp, af[st], db);
      }
      wgmma_commit();
    };
    bar_sync(2 - wg, 256);
    TL(51);
    part(IC<0>{}, 0, 4 * ENDK);
    part(IC<1>{}, 0, LEAD);
    wgmma_wait<1>();
    if (wg == 1) store_acc(accp, op + 64 * F_DIM, 0, 3);
    part(IC<1>{}, LEAD, 4 * ENDK);
    part(IC<2>{}, 0, LEAD);
    wgmma_wait<1>();
    if (wg == 0) store_acc(accp, op + 64 * F_DIM, 0, 3);
    else store_acc(accp, op + 64 * F_DIM, 3, 5);
    part(IC<2>{}, LEAD, 4 * ENDK);
    if (wg == 0) {
      bar_arrive(1, 256);
      store_acc(accp, op + 64 * F_DIM, 3, 5);
    }
    wgmma_wait<0>();
    TL(43); TLG(47);
    store_acc(accp, op + 64 * F_DIM, 5, 7);
  }
  TL(44);
}

__global__ void __launch_bounds__(BN)
prefill_kernel(const int* __restrict__ qw, const __nv_bfloat16* __restrict__ lut,
               const __nv_bfloat16* __restrict__ scales, uint8_t* scratch) {
  const int j = blockIdx.x & 15, kc = blockIdx.x >> 4, f = j * BN + perm32(threadIdx.x);
  int q[8];
#pragma unroll
  for (int i = 0; i < 8; i++) q[i] = qw[(kc * 8 + i) * F_DIM + f];
  *reinterpret_cast<uint4*>(scratch + (size_t)j * REGION + W_OFF + kc * W_KC + threadIdx.x * 16) =
      convert_unit(q, make_table(__bfloat162float(lut[threadIdx.x & 15]), __bfloat162float(scales[f])));
}

typedef CUresult (*EncodeTiledFn)(CUtensorMap*, CUtensorMapDataType, cuuint32_t, void*, const cuuint64_t*,
                                  const cuuint64_t*, const cuuint32_t*, const cuuint32_t*, CUtensorMapInterleave,
                                  CUtensorMapSwizzle, CUtensorMapL2promotion, CUtensorMapFloatOOBfill);

}

extern "C" void kernel_launch(void* const* d_in, const int* in_sizes, int n_in, void* d_out, int out_size) {
  const __nv_bfloat16* x = (const __nv_bfloat16*)d_in[0];
  const int* qw = (const int*)d_in[1];
  const __nv_bfloat16* lut = (const __nv_bfloat16*)d_in[2];
  const __nv_bfloat16* scales = (const __nv_bfloat16*)d_in[3];
  __nv_bfloat16* out = (__nv_bfloat16*)d_out;

  static EncodeTiledFn enc = nullptr;
  static uint8_t* p_scr = nullptr;
  static bool coresident = false;
  if (!enc) {
    void* fn = nullptr;
    cudaDriverEntryPointQueryResult qr;
    cudaGetDriverEntryPoint("cuTensorMapEncodeTiled", &fn, cudaEnableDefault, &qr);
    enc = (EncodeTiledFn)fn;
    void* p = nullptr;
    cudaGetSymbolAddress(&p, g_scratch);
    p_scr = (uint8_t*)(((uintptr_t)p + REGION - 1) & ~(uintptr_t)(REGION - 1));
    cudaFuncSetAttribute(fused_kernel, cudaFuncAttributeMaxDynamicSharedMemorySize, SMEM_TOTAL);
    int dev = 0, sms = 0;
    cudaGetDevice(&dev);
    cudaDeviceGetAttribute(&sms, cudaDevAttrMultiProcessorCount, dev);
    coresident = sms >= NI * NJ;
  }
  CUtensorMap tm_x, tm_q;
  cuuint32_t estr[2] = {1, 1};
  {
    cuuint64_t gdim[2] = {(cuuint64_t)D_DIM, (cuuint64_t)S_DIM};
    cuuint64_t gstr[1] = {(cuuint64_t)D_DIM * 2};
    cuuint32_t box[2] = {(cuuint32_t)BK, 64};
    enc(&tm_x, CU_TENSOR_MAP_DATA_TYPE_BFLOAT16, 2, (void*)x, gdim, gstr, box, estr, CU_TENSOR_MAP_INTERLEAVE_NONE,
        CU_TENSOR_MAP_SWIZZLE_128B, CU_TENSOR_MAP_L2_PROMOTION_NONE, CU_TENSOR_MAP_FLOAT_OOB_FILL_NONE);
  }
  {
    cuuint64_t gdim[2] = {(cuuint64_t)F_DIM, (cuuint64_t)D_DIM};
    cuuint64_t gstr[1] = {(cuuint64_t)F_DIM * 4};
    cuuint32_t box[2] = {(cuuint32_t)BN, 8};
    enc(&tm_q, CU_TENSOR_MAP_DATA_TYPE_INT32, 2, (void*)qw, gdim, gstr, box, estr, CU_TENSOR_MAP_INTERLEAVE_NONE,
        CU_TENSOR_MAP_SWIZZLE_NONE, CU_TENSOR_MAP_L2_PROMOTION_NONE, CU_TENSOR_MAP_FLOAT_OOB_FILL_NONE);
  }
  if (!coresident) prefill_kernel<<<NJ * NKB * 8, BN, 0, cudaStreamPerThread>>>(qw, lut, scales, p_scr);
  fused_kernel<<<NI * NJ, 256, SMEM_TOTAL, cudaStreamPerThread>>>(qw, lut, scales, out, p_scr,
                                                                  coresident ? FLAG_FULL : 0u, tm_x, tm_q);
}
```

```cpp
#include <cuda_runtime.h>
#include <cuda_bf16.h>
#include <cuda.h>
#include <stdint.h>

namespace {

constexpr int S_DIM = 2048, D_DIM = 1024, F_DIM = 3584;
constexpr int BM = 256, BN = 224, BK = 64;
constexpr int NKB = D_DIM / BK;
constexpr int NJ = F_DIM / BN;
constexpr int NI = S_DIM / BM;
constexpr int WS = 4;
constexpr int XS = 5;
constexpr int ENDK = 5;
constexpr int NR = NKB - ENDK;
constexpr int X_SLICE = 64 * BK * 2;
constexpr int W_STAGE = BN * BK * 2;
constexpr int W_KC = BN * 16;

constexpr int REGION = 512 * 1024;
__device__ uint4 g_scratch[(NJ + 1) * REGION / 16];

__device__ __forceinline__ uint32_t smem_u32(const void* p) { return (uint32_t)__cvta_generic_to_shared(p); }
__device__ __forceinline__ unsigned clk32() {
  unsigned c;
  asm volatile("mov.u32 %0, %%clock;" : "=r"(c)::"memory");
  return c;
}
__device__ __forceinline__ bool elect_one() {
  uint32_t p;
  asm volatile("{\n.reg .pred P;\nelect.sync _|P, 0xffffffff;\nselp.b32 %0, 1, 0, P;\n}" : "=r"(p));
  return p != 0;
}
__device__ __forceinline__ void mbar_init(uint32_t bar, uint32_t cnt) {
  asm volatile("mbarrier.init.shared::cta.b64 [%0], %1;" ::"r"(bar), "r"(cnt) : "memory");
}
__device__ __forceinline__ void mbar_expect_tx(uint32_t bar, uint32_t bytes) {
  asm volatile("mbarrier.arrive.expect_tx.shared::cta.b64 _, [%0], %1;" ::"r"(bar), "r"(bytes) : "memory");
}
__device__ __forceinline__ void mbar_arrive(uint32_t bar) {
  asm volatile("mbarrier.arrive.shared::cta.b64 _, [%0];" ::"r"(bar) : "memory");
}
__device__ __forceinline__ void mbar_wait(uint32_t bar, uint32_t parity) {
  asm volatile(
      "{\n.reg .pred p;\n"
      "LAB_WAIT:\n"
      "mbarrier.try_wait.parity.shared::cta.b64 p, [%0], %1;\n"
      "@p bra LAB_DONE;\n"
      "bra LAB_WAIT;\n"
      "LAB_DONE:\n}\n" ::"r"(bar), "r"(parity) : "memory");
}
template <int N>
__device__ __forceinline__ uint32_t ring(uint32_t base, int i) { return base + 8 * (i % N); }
template <int N>
__device__ __forceinline__ void ring_wait(uint32_t base, int i) { mbar_wait(ring<N>(base, i), (i / N) & 1); }
__device__ __forceinline__ void tma_load_2d(uint32_t dst, const CUtensorMap* tm, int c0, int c1, uint32_t bar) {
  asm volatile(
      "cp.async.bulk.tensor.2d.shared::cluster.global.mbarrier::complete_tx::bytes [%0], [%1, {%3, %4}], [%2];"
      ::"r"(dst), "l"(tm), "r"(bar), "r"(c0), "r"(c1) : "memory");
}
__device__ __forceinline__ void bulk_load(uint32_t dst, const void* src, uint32_t bytes, uint32_t bar) {
  asm volatile(
      "cp.async.bulk.shared::cluster.global.mbarrier::complete_tx::bytes [%0], [%1], %2, [%3];"
      ::"r"(dst), "l"(src), "r"(bytes), "r"(bar) : "memory");
}
__device__ __forceinline__ void cp_async16(uint32_t dst, const void* src) {
  asm volatile("cp.async.cg.shared.global [%0], [%1], 16;" ::"r"(dst), "l"(src) : "memory");
}
__device__ __forceinline__ void cp_async_commit() { asm volatile("cp.async.commit_group;" ::: "memory"); }
template <int N>
__device__ __forceinline__ void cp_async_wait() { asm volatile("cp.async.wait_group %0;" ::"n"(N) : "memory"); }
__device__ __forceinline__ uint32_t ldg_u16(const void* p) {
  uint32_t v;
  asm volatile("ld.global.u16 %0, [%1];" : "=r"(v) : "l"(p) : "memory");
  return v;
}
__device__ __forceinline__ int lds32(uint32_t addr) {
  int v;
  asm volatile("ld.shared.b32 %0, [%1];" : "=r"(v) : "r"(addr) : "memory");
  return v;
}
__device__ __forceinline__ void sts128(uint32_t addr, uint4 v) {
  asm volatile("st.shared.v4.u32 [%0], {%1, %2, %3, %4};" ::"r"(addr), "r"(v.x), "r"(v.y), "r"(v.z), "r"(v.w) : "memory");
}
__device__ __forceinline__ uint64_t make_desc(uint32_t lo, uint32_t hi) {
  uint64_t d;
  asm("mov.b64 %0, {%1, %2};" : "=l"(d) : "r"(lo), "r"(hi));
  return d;
}
__device__ __forceinline__ unsigned ld_strong(const void* p) {
  unsigned v;
  asm volatile("ld.relaxed.gpu.global.u32 %0, [%1];" : "=r"(v) : "l"(p) : "memory");
  return v;
}
__device__ __forceinline__ void st_strong128(void* p, uint4 v) {
  asm volatile("st.relaxed.gpu.global.v4.u32 [%0], {%1, %2, %3, %4};" ::"l"(p), "r"(v.x), "r"(v.y), "r"(v.z), "r"(v.w)
               : "memory");
}
__device__ __forceinline__ void wgmma_fence() { asm volatile("wgmma.fence.sync.aligned;" ::: "memory"); }
__device__ __forceinline__ void wgmma_commit() { asm volatile("wgmma.commit_group.sync.aligned;" ::: "memory"); }
template <int N>
__device__ __forceinline__ void wgmma_wait() { asm volatile("wgmma.wait_group.sync.aligned %0;" ::"n"(N) : "memory"); }
__device__ __forceinline__ void bar_sync(int id, int n) { asm volatile("bar.sync %0, %1;" ::"r"(id), "r"(n) : "memory"); }
__device__ __forceinline__ void bar_arrive(int id, int n) { asm volatile("bar.arrive %0, %1;" ::"r"(id), "r"(n) : "memory"); }

__device__ __forceinline__ void wgmma_m64n224k16(float (&d)[112], uint64_t da, uint64_t db, int scale_d) {
  asm volatile(
    "{\n.reg .pred p;\nsetp.ne.b32 p, %114, 0;\n"
    "wgmma.mma_async.sync.aligned.m64n224k16.f32.bf16.bf16 "
    "{%0, %1, %2, %3, %4, %5, %6, %7, %8, %9, %10, %11, %12, %13, %14, %15, "
    "%16, %17, %18, %19, %20, %21, %22, %23, %24, %25, %26, %27, %28, %29, %30, %31, "
    "%32, %33, %34, %35, %36, %37, %38, %39, %40, %41, %42, %43, %44, %45, %46, %47, "
    "%48, %49, %50, %51, %52, %53, %54, %55, %56, %57, %58, %59, %60, %61, %62, %63, "
    "%64, %65, %66, %67, %68, %69, %70, %71, %72, %73, %74, %75, %76, %77, %78, %79, "
    "%80, %81, %82, %83, %84, %85, %86, %87, %88, %89, %90, %91, %92, %93, %94, %95, "
    "%96, %97, %98, %99, %100, %101, %102, %103, %104, %105, %106, %107, %108, %109, %110, %111}, "
    "%112, %113, p, 1, 1, 0, 0;\n}\n"
    : "+f"(d[0]), "+f"(d[1]), "+f"(d[2]), "+f"(d[3]), "+f"(d[4]), "+f"(d[5]), "+f"(d[6]), "+f"(d[7]),
      "+f"(d[8]), "+f"(d[9]), "+f"(d[10]), "+f"(d[11]), "+f"(d[12]), "+f"(d[13]), "+f"(d[14]), "+f"(d[15]),
      "+f"(d[16]), "+f"(d[17]), "+f"(d[18]), "+f"(d[19]), "+f"(d[20]), "+f"(d[21]), "+f"(d[22]), "+f"(d[23]),
      "+f"(d[24]), "+f"(d[25]), "+f"(d[26]), "+f"(d[27]), "+f"(d[28]), "+f"(d[29]), "+f"(d[30]), "+f"(d[31]),
      "+f"(d[32]), "+f"(d[33]), "+f"(d[34]), "+f"(d[35]), "+f"(d[36]), "+f"(d[37]), "+f"(d[38]), "+f"(d[39]),
      "+f"(d[40]), "+f"(d[41]), "+f"(d[42]), "+f"(d[43]), "+f"(d[44]), "+f"(d[45]), "+f"(d[46]), "+f"(d[47]),
      "+f"(d[48]), "+f"(d[49]), "+f"(d[50]), "+f"(d[51]), "+f"(d[52]), "+f"(d[53]), "+f"(d[54]), "+f"(d[55]),
      "+f"(d[56]), "+f"(d[57]), "+f"(d[58]), "+f"(d[59]), "+f"(d[60]), "+f"(d[61]), "+f"(d[62]), "+f"(d[63]),
      "+f"(d[64]), "+f"(d[65]), "+f"(d[66]), "+f"(d[67]), "+f"(d[68]), "+f"(d[69]), "+f"(d[70]), "+f"(d[71]),
      "+f"(d[72]), "+f"(d[73]), "+f"(d[74]), "+f"(d[75]), "+f"(d[76]), "+f"(d[77]), "+f"(d[78]), "+f"(d[79]),
      "+f"(d[80]), "+f"(d[81]), "+f"(d[82]), "+f"(d[83]), "+f"(d[84]), "+f"(d[85]), "+f"(d[86]), "+f"(d[87]),
      "+f"(d[88]), "+f"(d[89]), "+f"(d[90]), "+f"(d[91]), "+f"(d[92]), "+f"(d[93]), "+f"(d[94]), "+f"(d[95]),
      "+f"(d[96]), "+f"(d[97]), "+f"(d[98]), "+f"(d[99]), "+f"(d[100]), "+f"(d[101]), "+f"(d[102]), "+f"(d[103]),
      "+f"(d[104]), "+f"(d[105]), "+f"(d[106]), "+f"(d[107]), "+f"(d[108]), "+f"(d[109]), "+f"(d[110]), "+f"(d[111])
    : "l"(da), "l"(db), "r"(scale_d));
}
template <int O>
__device__ __forceinline__ void wgmma_rs_m64n96k16(float (&d)[112], const uint32_t (&a)[4], uint64_t db) {
  asm volatile(
    "wgmma.mma_async.sync.aligned.m64n96k16.f32.bf16.bf16 "
    "{%0, %1, %2, %3, %4, %5, %6, %7, %8, %9, %10, %11, %12, %13, %14, %15, "
    "%16, %17, %18, %19, %20, %21, %22, %23, %24, %25, %26, %27, %28, %29, %30, %31, "
    "%32, %33, %34, %35, %36, %37, %38, %39, %40, %41, %42, %43, %44, %45, %46, %47}, "
    "{%48, %49, %50, %51}, %52, 1, 1, 1, 0;\n"
    : "+f"(d[O + 0]), "+f"(d[O + 1]), "+f"(d[O + 2]), "+f"(d[O + 3]),
      "+f"(d[O + 4]), "+f"(d[O + 5]), "+f"(d[O + 6]), "+f"(d[O + 7]),
      "+f"(d[O + 8]), "+f"(d[O + 9]), "+f"(d[O + 10]), "+f"(d[O + 11]),
      "+f"(d[O + 12]), "+f"(d[O + 13]), "+f"(d[O + 14]), "+f"(d[O + 15]),
      "+f"(d[O + 16]), "+f"(d[O + 17]), "+f"(d[O + 18]), "+f"(d[O + 19]),
      "+f"(d[O + 20]), "+f"(d[O + 21]), "+f"(d[O + 22]), "+f"(d[O + 23]),
      "+f"(d[O + 24]), "+f"(d[O + 25]), "+f"(d[O + 26]), "+f"(d[O + 27]),
      "+f"(d[O + 28]), "+f"(d[O + 29]), "+f"(d[O + 30]), "+f"(d[O + 31]),
      "+f"(d[O + 32]), "+f"(d[O + 33]), "+f"(d[O + 34]), "+f"(d[O + 35]),
      "+f"(d[O + 36]), "+f"(d[O + 37]), "+f"(d[O + 38]), "+f"(d[O + 39]),
      "+f"(d[O + 40]), "+f"(d[O + 41]), "+f"(d[O + 42]), "+f"(d[O + 43]),
      "+f"(d[O + 44]), "+f"(d[O + 45]), "+f"(d[O + 46]), "+f"(d[O + 47])
    : "r"(a[0]), "r"(a[1]), "r"(a[2]), "r"(a[3]), "l"(db));
}
template <int O>
__device__ __forceinline__ void wgmma_rs_m64n64k16(float (&d)[112], const uint32_t (&a)[4], uint64_t db) {
  asm volatile(
    "wgmma.mma_async.sync.aligned.m64n64k16.f32.bf16.bf16 "
    "{%0, %1, %2, %3, %4, %5, %6, %7, %8, %9, %10, %11, %12, %13, %14, %15, "
    "%16, %17, %18, %19, %20, %21, %22, %23, %24, %25, %26, %27, %28, %29, %30, %31}, "
    "{%32, %33, %34, %35}, %36, 1, 1, 1, 0;\n"
    : "+f"(d[O + 0]), "+f"(d[O + 1]), "+f"(d[O + 2]), "+f"(d[O + 3]),
      "+f"(d[O + 4]), "+f"(d[O + 5]), "+f"(d[O + 6]), "+f"(d[O + 7]),
      "+f"(d[O + 8]), "+f"(d[O + 9]), "+f"(d[O + 10]), "+f"(d[O + 11]),
      "+f"(d[O + 12]), "+f"(d[O + 13]), "+f"(d[O + 14]), "+f"(d[O + 15]),
      "+f"(d[O + 16]), "+f"(d[O + 17]), "+f"(d[O + 18]), "+f"(d[O + 19]),
      "+f"(d[O + 20]), "+f"(d[O + 21]), "+f"(d[O + 22]), "+f"(d[O + 23]),
      "+f"(d[O + 24]), "+f"(d[O + 25]), "+f"(d[O + 26]), "+f"(d[O + 27]),
      "+f"(d[O + 28]), "+f"(d[O + 29]), "+f"(d[O + 30]), "+f"(d[O + 31])
    : "r"(a[0]), "r"(a[1]), "r"(a[2]), "r"(a[3]), "l"(db));
}

__device__ __forceinline__ uint32_t pack_bf16(float lo, float hi) {
  uint32_t r;
  asm("cvt.rn.bf16x2.f32 %0, %1, %2;" : "=r"(r) : "f"(hi), "f"(lo));
  return r;
}

__device__ __forceinline__ int perm32(int n) { return (n & ~30) | ((n & 6) << 2) | ((n >> 2) & 6); }

constexpr int SMEM_X = 0;
constexpr int SMEM_W = 2 * XS * X_SLICE;
constexpr int SMEM_Q = SMEM_W + WS * W_STAGE;
constexpr int Q_UNIT = 8 * BN * 4;
constexpr int SMEM_BAR = SMEM_Q + W_STAGE;
constexpr int B_FULLW = 0, B_FULLQ = 5, B_FULLX = 9, B_DONE = 19, B_W0 = 35, B_RAW0 = 36;
constexpr int SMEM_TL = SMEM_BAR + 512;
constexpr int SMEM_TOTAL = SMEM_TL;
constexpr int W_OFF = 128;
constexpr unsigned FLAG_FULL = NI * 7;

#define TL(i)
#define TLG(i)

__device__ __forceinline__ void store_acc(const float (&a)[112], __nv_bfloat16* p, int J0, int J1) {
#pragma unroll
  for (int J = J0; J < J1; J++) {
    uint4 v0, v1;
    v0.x = pack_bf16(a[16 * J + 0], a[16 * J + 1]);
    v0.y = pack_bf16(a[16 * J + 4], a[16 * J + 5]);
    v0.z = pack_bf16(a[16 * J + 8], a[16 * J + 9]);
    v0.w = pack_bf16(a[16 * J + 12], a[16 * J + 13]);
    v1.x = pack_bf16(a[16 * J + 2], a[16 * J + 3]);
    v1.y = pack_bf16(a[16 * J + 6], a[16 * J + 7]);
    v1.z = pack_bf16(a[16 * J + 10], a[16 * J + 11]);
    v1.w = pack_bf16(a[16 * J + 14], a[16 * J + 15]);
    *reinterpret_cast<uint4*>(p + 32 * J) = v0;
    *reinterpret_cast<uint4*>(p + 8 * F_DIM + 32 * J) = v1;
  }
}

struct Table {
  uint32_t lo[4], hi[4];
};
__device__ __forceinline__ uint32_t prmt(uint32_t a, uint32_t b, uint32_t s) {
  uint32_t r;
  asm("prmt.b32 %0, %1, %2, %3;" : "=r"(r) : "r"(a), "r"(b), "r"(s));
  return r;
}
__device__ __forceinline__ Table make_table(float lutv, float sc) {
  Table t;
#pragma unroll
  for (int i = 0; i < 4; i++) {
    const uint32_t a = pack_bf16(__shfl_sync(0xffffffffu, lutv, 4 * i) * sc, __shfl_sync(0xffffffffu, lutv, 4 * i + 1) * sc);
    const uint32_t b =
        pack_bf16(__shfl_sync(0xffffffffu, lutv, 4 * i + 2) * sc, __shfl_sync(0xffffffffu, lutv, 4 * i + 3) * sc);
    t.lo[i] = prmt(a, b, 0x6420);
    t.hi[i] = prmt(a, b, 0x7531);
  }
  return t;
}
__device__ __forceinline__ uint4 convert_unit(const int (&q)[8], const Table& t) {
  const uint32_t all = ((q[7] * 16 + q[6]) * 256 + (q[5] * 16 + q[4])) * 65536 + ((q[3] * 16 + q[2]) * 256 + (q[1] * 16 + q[0]));
  const uint32_t s7 = all & 0x77777777u;
  const uint32_t s2 = ((all >> 1) & 0x44444444u) | 0x32103210u;
  uint32_t o[4];
#pragma unroll
  for (int h = 0; h < 2; h++) {
    const uint32_t a = h ? s7 >> 16 : s7, b = h ? s2 >> 16 : s2;
    const uint32_t lo = prmt(prmt(t.lo[0], t.lo[1], a), prmt(t.lo[2], t.lo[3], a), b);
    const uint32_t hi = prmt(prmt(t.hi[0], t.hi[1], a), prmt(t.hi[2], t.hi[3], a), b);
    o[2 * h] = prmt(lo, hi, 0x5140);
    o[2 * h + 1] = prmt(lo, hi, 0x7362);
  }
  return make_uint4(o[0], o[1], o[2], o[3]);
}

constexpr int PU = 3;
#define HEAVY 0x3EEEAu
__host__ __device__ constexpr int popc(unsigned v) { return v ? (v & 1) + popc(v >> 1) : 0; }
__host__ __device__ constexpr bool heavy(int n) { return n >= 0 && ((HEAVY >> n) & 1); }
__host__ __device__ constexpr int unit_at(int n) { return PU + popc(HEAVY & ((1u << n) - 1)); }
__host__ __device__ constexpr int emit_slot(int u) {
  if (u < PU) return -1;
  for (int n = 0; n < 24; n++)
    if (heavy(n) && unit_at(n) == u) return n;
  return 99;
}
__host__ __device__ constexpr int end_kb(int e) { return e < 3 ? NR + e : NR + 7 - e; }
__host__ __device__ constexpr int w_ring(int m) { return m == 15 ? 4 : m & 3; }
__host__ __device__ constexpr int cmax(int a, int b) { return a > b ? a : b; }
__host__ __device__ constexpr int w_slot(int m) {
  return m == 15 ? cmax(emit_slot(15) + 3, 20) : cmax(2 * m - 5, emit_slot(m) + 3);
}
__host__ __device__ constexpr int q_slot(int u) {
  return u == 5 ? 2 : cmax(cmax(q_slot(u - 1) + 1, emit_slot(u) - 3), u < 8 ? 2 : emit_slot(u - 4) + 2);
}
__host__ __device__ constexpr int w_at(int n) {
  for (int m = 2; m < NKB; m++)
    if (w_slot(m) == n) return m;
  return -1;
}
__host__ __device__ constexpr int q_at(int n) {
  for (int u = 5; u < NKB; u++)
    if (q_slot(u) == n) return u;
  return -1;
}
constexpr bool schedule_ok() {
  if (popc(HEAVY) != NKB - PU || (HEAVY & 7) != 2 || (HEAVY >> 20)) return false;
  for (int m = 2; m < NKB; m++) {
    if (w_at(w_slot(m)) != m || (m != 14 && w_slot(m) >= 2 * NR)) return false;
    if (m < NR && w_slot(m) > 2 * m - 2) return false;
  }
  for (int u = 5; u < NKB; u++)
    if (q_slot(u) + 2 > emit_slot(u)) return false;
  return true;
}
static_assert(schedule_ok(), "bad schedule");
template <int V>
struct IC {
  static constexpr int value = V;
};
template <int I, int N, class F>
__device__ __forceinline__ void static_for(F&& f) {
  if constexpr (I < N) {
    f(IC<I>{});
    static_for<I + 1, N>(f);
  }
}

#define NCP 3
#define RSPLIT 5
#define STAG_L 70
#define PACE_INIT 550
#define PACE_X 950
#define PACE_Q2 1450
#define PACE_Q3 1950
#define PUB_AT 6
#define ST_GAP 150
#define LEAD 8

constexpr uint32_t sbase = 1024;

__global__ void __launch_bounds__(256, 1)
fused_kernel(const int* __restrict__ qw, const __nv_bfloat16* __restrict__ lut,
             const __nv_bfloat16* __restrict__ scales, __nv_bfloat16* __restrict__ out, uint8_t* scratch,
             unsigned flag_full,
             const __grid_constant__ CUtensorMap tm_x, const __grid_constant__ CUtensorMap tm_q) {
  extern __shared__ __align__(1024) uint8_t smem_raw[];
  constexpr uint32_t bars = sbase + SMEM_BAR;
  const int j = blockIdx.x >> 3, it = blockIdx.x & 7;
  constexpr uint32_t raw0 = sbase + SMEM_W + 2 * W_STAGE;
  uint32_t lut_raw = 0, sc_raw = 0;
  if (threadIdx.x < 224) {
    const unsigned t = threadIdx.x, row0 = (t >> 3) & 3, col = (t & ~31u) + (t & 7) * 4;
    const int* src = qw + (row0 * F_DIM + j * BN + col);
    const uint32_t dst = row0 * (BN * 4) + col * 4;
    lut_raw = ldg_u16(lut + (t & 15));
    sc_raw = ldg_u16(scales + (j * BN + perm32(t)));
    __syncwarp();
#pragma unroll
    for (int g = 0; g < NCP + 1; g++) {
      const unsigned row = g == 0 ? BK + it * 8 : (g - 1) * 8;
      const uint32_t d = dst + (g == 0 ? sbase + SMEM_Q + Q_UNIT : raw0 + (g - 1) * Q_UNIT);
      cp_async16(d, src + row * F_DIM);
      cp_async16(d + 4 * BN * 4, src + (row + 4) * F_DIM);
      cp_async_commit();
    }
  }
  const int warp = __shfl_sync(0xffffffffu, threadIdx.x >> 5, 0);
  const int wg = warp >> 2;
  int lane;
  asm volatile("mov.u32 %0, %%laneid;" : "=r"(lane));
  const unsigned t_start = clk32();
  auto pace = [&](unsigned t) {
    while (__any_sync(0xffffffffu, clk32() - t_start < t)) {}
  };

  uint8_t* const region = scratch + (size_t)j * REGION;
  uint8_t* const wp = region + (warp < 7 ? W_OFF + it * W_KC + (warp * 32 + lane) * 16 : lane * 4);
  unsigned* const fl = reinterpret_cast<unsigned*>(wp);
  Table tab;
  unsigned rb;
  const int xrow = it * BM + wg * 128;

  auto w_ptr = [&](int u) { return reinterpret_cast<uint4*>(wp + u * W_STAGE); };
  auto emit_unit = [&](uint4 w, int u) {
    st_strong128(w_ptr(u), w);
    rb = ld_strong(w_ptr(u));
  };
  auto publish = [&](int u) {
    asm volatile(
        "{\n.reg .pred P, Q;\n"
        "setp.ne.u32 P, %1, 0xffffffff;\n"
        "vote.sync.all.pred P, P, 0xffffffff;\n"
        "elect.sync _|Q, 0xffffffff;\n"
        "and.pred Q, Q, P;\n"
        "@Q red.relaxed.gpu.global.add.u32 [%0], 1;\n}"
        ::"l"(region + u * 4), "r"(rb) : "memory");
  };
  auto load_x = [&](int g, int n, int kb, int half) {
    const uint32_t bar = ring<XS>(bars + 8 * B_FULLX, n) + g * (8 * XS);
    mbar_expect_tx(bar, X_SLICE);
    tma_load_2d(sbase + SMEM_X + (n % XS) * X_SLICE + g * (XS * X_SLICE), &tm_x, kb * BK,
                it * BM + g * 128 + half * 64, bar);
  };
  auto load_q = [&](int u) {
    const uint32_t bar = ring<4>(bars + 8 * B_FULLQ, u);
    mbar_expect_tx(bar, Q_UNIT);
    tma_load_2d(sbase + SMEM_Q + (u & 3) * Q_UNIT, &tm_q, j * BN, u * BK + it * 8, bar);
  };

  unsigned ready = 0;
  auto load_w = [&](int m) {
    const uint32_t bar = bars + 8 * (B_FULLW + w_ring(m));
    mbar_expect_tx(bar, W_STAGE);
    bulk_load(sbase + SMEM_W + w_ring(m) * W_STAGE, region + W_OFF + m * W_STAGE, W_STAGE, bar);
  };
  auto wait_w = [&](int m) { mbar_wait(bars + 8 * (B_FULLW + w_ring(m)), m == 15 ? 0 : (m >> 2) & 1); };
  auto poll = [&]() { ready |= __ballot_sync(0xffffffffu, ld_strong(fl) >= flag_full); };
  auto wait_ready = [&](int kb) {
    int spins = 0;
    while (!((ready >> kb) & 1)) {
      poll();
      if (++spins > (1 << 22)) __trap();
    }
  };

  uint32_t qbase;
  asm volatile("mov.u32 %0, %1;" : "=r"(qbase) : "r"(sbase + SMEM_Q + warp * 128 + perm32(lane) * 4));
  auto lds_unit = [&](int (&q)[8], int u) {
    ring_wait<4>(bars + 8 * B_FULLQ, u);
#pragma unroll
    for (int i = 0; i < 8; i++) q[i] = lds32(qbase + (u & 3) * Q_UNIT + i * (BN * 4));
  };
  auto arrive_one = [&](uint32_t bar) {
    asm volatile("{\n.reg .pred P;\nelect.sync _|P, 0xffffffff;\n@P mbarrier.arrive.shared::cta.b64 _, [%0];\n}"
                 ::"r"(bar) : "memory");
  };

  if (warp == 7) {
    if (elect_one()) {
      mbar_init(bars + 8 * B_RAW0, RSPLIT - NCP);
      mbar_init(bars + 8 * B_RAW0 + 8, 8 - RSPLIT);
      asm volatile("fence.mbarrier_init.release.cluster;" ::: "memory");
    }
    __syncwarp();
    bar_arrive(4, (9 - NCP) * 32);
    if (elect_one()) {
      asm volatile("prefetch.tensormap [%0];" ::"l"(&tm_x) : "memory");
      asm volatile("prefetch.tensormap [%0];" ::"l"(&tm_q) : "memory");
    }
    TL(5);
    pace(PACE_INIT);
    if (elect_one()) {
#pragma unroll
      for (int i = 0; i < B_RAW0; i++) mbar_init(bars + 8 * i, i == B_W0 ? 7 : i >= B_DONE ? 4 : 1);
      asm volatile("fence.mbarrier_init.release.cluster;" ::: "memory");
    }
    __syncwarp();
    rb = ld_strong(fl);
    bar_arrive(0, 256);
    TL(4);
#pragma unroll
    for (int i = 0; i < 4; i++) tab.lo[i] = tab.hi[i] = 0;
    if (smem_u32(smem_raw) != sbase) __trap();
    if (elect_one()) {
      mbar_arrive(bars + 8 * B_FULLW);
      mbar_arrive(bars + 8 * B_FULLQ);
      mbar_arrive(bars + 8 * B_FULLQ + 8);
    }
    pace(PACE_X);
    if (elect_one()) {
      load_x(0, 0, 0, 0); load_x(1, 0, 0, 0); load_x(0, 1, 0, 1); load_x(1, 1, 0, 1);
    }
    pace(PACE_Q2);
    if (elect_one()) load_q(2);
    pace(PACE_Q3);
    ready = __ballot_sync(0xffffffffu, rb >= flag_full);
    rb = ld_strong(fl);
    if (elect_one()) {
      load_q(3);
      load_x(0, 2, 1, 0); load_x(1, 2, 1, 0); load_x(0, 3, 1, 1); load_x(1, 3, 1, 1);
    }
    ready |= __ballot_sync(0xffffffffu, rb >= flag_full);
    wait_ready(1);
    asm volatile("fence.proxy.async.global;" ::: "memory");
    if (elect_one()) {
      load_w(1);
      load_x(0, 4, 2, 0); load_x(1, 4, 2, 0);
    }
    TL(2);
    TL(3);
  } else {
    if (warp + NCP < 8) {
      bar_sync(4, (9 - NCP) * 32);
      pace(warp * STAG_L);
      if (elect_one()) {
        const int c = warp + NCP;
        const uint32_t bar = bars + 8 * B_RAW0 + (c < RSPLIT ? 0 : 8);
        mbar_expect_tx(bar, Q_UNIT);
#pragma unroll
        for (int i = 0; i < 8; i++)
          bulk_load(raw0 + (c * 8 + i) * (BN * 4), qw + (size_t)(c * 8 + i) * F_DIM + j * BN, BN * 4, bar);
      }
    }
    bar_sync(0, 256);
    pace(200);
    asm volatile("shl.b32 %0, %0, 16;\nshl.b32 %1, %1, 16;" : "+r"(lut_raw), "+r"(sc_raw));
    tab = make_table(__uint_as_float(lut_raw), __uint_as_float(sc_raw));
    if (__any_sync(0xffffffffu, lane > 31 && (tab.lo[0] ^ tab.lo[1] ^ tab.lo[2] ^ tab.lo[3] ^ tab.hi[0] ^ tab.hi[1] ^
                                              tab.hi[2] ^ tab.hi[3]) == 1))
      __trap();
    int r[2][8];
    auto lds_group = [&](auto G) {
      constexpr int g = decltype(G)::value, c = g > 0 ? g - 1 : 0;
      if constexpr (g <= NCP) {
        cp_async_wait<NCP - g>();
        __syncwarp();
      } else {
        if (c == NCP) mbar_wait(bars + 8 * B_RAW0, 0);
        if (c == RSPLIT) mbar_wait(bars + 8 * B_RAW0 + 8, 0);
      }
#pragma unroll
      for (int i = 0; i < 8; i++)
        r[g & 1][i] = lds32(qbase + (g == 0 ? Q_UNIT : raw0 - sbase - SMEM_Q + c * Q_UNIT) + i * (BN * 4));
    };
    lds_group(IC<0>{});
    TL(6);
    static_for<0, 9>([&](auto G) {
      constexpr int g = decltype(G)::value, c = g > 0 ? g - 1 : 0;
      if (g == PUB_AT) {
        publish(1);
        TL(3);
      }
      if (g == 0) {
        emit_unit(convert_unit(r[g & 1], tab), 1);
        __syncwarp();
        TL(2);
        if constexpr (g < 8) lds_group(IC<g + 1>{});
      } else {
        if constexpr (g < 8) lds_group(IC<g + 1>{});
        sts128(sbase + SMEM_W + c * W_KC + (warp * 32 + lane) * 16, convert_unit(r[g & 1], tab));
      }
    });
    asm volatile("fence.proxy.async.shared::cta;" ::: "memory");
    __syncwarp();
    arrive_one(bars + 8 * B_W0);
    TL(4);
    if (wg == 1) {
      lds_unit(r[0], 2);
      emit_unit(convert_unit(r[0], tab), 2);
    }
    TL(5);
  }

  float acc0[112], acc1[112];
  constexpr uint32_t DA_HI = (1u << 30) | (1024 >> 4), DB_HI = (128 >> 4);
  const uint32_t da0 = ((1u << 16) | ((sbase + SMEM_X) >> 4)) + wg * (XS * X_SLICE >> 4);
  constexpr uint32_t db0 = ((W_KC >> 4) << 16) | ((sbase + SMEM_W) >> 4);
  const uint32_t fullx = bars + 8 * B_FULLX + wg * (8 * XS), done = bars + 8 * B_DONE + wg * 64;
  const bool x_issuer = (warp & 3) == 3;

  auto mma = [&](float (&acc)[112], int n, int kb, int k0, int k1) {
    wgmma_fence();
#pragma unroll
    for (int k = k0; k < k1; k++)
      wgmma_m64n224k16(acc, make_desc(da0 + (n % XS) * (X_SLICE >> 4) + k * 2, DA_HI),
                       make_desc(db0 + w_ring(kb) * (W_STAGE >> 4) + k * (2 * W_KC >> 4), DB_HI), kb != 0 || k != 0);
    wgmma_commit();
  };
  auto release = [&](int n) {
    arrive_one(ring<8>(done, n));
    if (x_issuer) {
      ring_wait<8>(done, n);
      const int m = n + 4;
      if (elect_one())
        load_x(wg, m, m < 2 * NR ? m >> 1 : end_kb((m - 2 * NR) % ENDK), m < 2 * NR ? m & 1 : (m - 2 * NR) / ENDK);
    }
  };
  auto end_slot = [&](int n) {
    wgmma_wait<1>();
    release(n);
  };
  auto slot = [&](float (&acc)[112], auto N) {
    constexpr int n = decltype(N)::value;
    constexpr bool hv = heavy(n), pub = heavy(n - 1);
    ring_wait<XS>(fullx, n);
    constexpr int m = w_at(n);
    if (m >= 0 && warp == 7) rb = ld_strong(fl);
    mma(acc, n, n >> 1, 0, 4);
    end_slot(n);
    if (warp < 7) {
      constexpr int u = unit_at(n);
      int q[8];
      if (hv) lds_unit(q, u);
      if (pub) publish(u - 1);
      if (hv) emit_unit(convert_unit(q, tab), u);
    } else {
      constexpr int u = q_at(n);
      if (m >= 0 || u >= 0) ring_wait<8>(bars + 8 * B_DONE, n - 1);
      if (m >= 0) {
        ready |= __ballot_sync(0xffffffffu, rb >= flag_full);
        wait_ready(m);
        asm volatile("fence.proxy.async.global;" ::: "memory");
      }
      if ((m >= 0 || u >= 0) && elect_one()) {
        if (m >= 0) load_w(m);
        if (u >= 0) load_q(u);
      }
    }
  };

  mbar_wait(bars + 8 * B_W0, 0);
  mbar_wait(fullx, 0);
  TL(8); TLG(46);
  mma(acc0, 0, 0, 0, 4);
  mbar_wait(fullx + 8, 0);
  TL(9);
  mma(acc1, 1, 0, 0, 4);
  arrive_one(done);
  if (warp < 7) {
    if (wg == 0) {
      int q2[8];
      lds_unit(q2, 2);
      emit_unit(convert_unit(q2, tab), 2);
    } else {
      publish(2);
    }
    int q3[8];
    lds_unit(q3, 3);
    const uint4 w3 = convert_unit(q3, tab);
    if (wg == 0) publish(2);
    emit_unit(w3, 3);
  } else {
    if (elect_one()) load_q(4);
  }
  end_slot(1);

  static_for<1, NR>([&](auto R) {
    constexpr int r = decltype(R)::value;
    wait_w(r);
    TL(8 + 2 * r);
    slot(acc0, IC<2 * r>{});
    TL(9 + 2 * r);
    slot(acc1, IC<2 * r + 1>{});
  });

  __nv_bfloat16* op = out + (size_t)(xrow + (warp & 3) * 16 + (lane >> 2)) * F_DIM + j * BN + (lane & 3) * 8;
  TL(40); TLG(48);
  if (wg == 1) {
    wgmma_wait<0>();
    release(2 * NR);
    if (warp == 7) {
      wait_ready(14);
      asm volatile("fence.proxy.async.global;" ::: "memory");
      ring_wait<8>(bars + 8 * B_DONE, 2 * NR);
      if (elect_one()) load_w(14);
      unsigned old = 0;
      if (lane == 17) old = atomicAdd(fl, 1u);
      if (__shfl_sync(0xffffffffu, old, 17) == NI - 1) *fl = 0;
    }
    bar_sync(1, 256);
  }
#pragma unroll
  for (int e = 0; e < ENDK; e++) {
    wait_w(end_kb(e));
    ring_wait<XS>(fullx, 2 * NR + e);
    mma(acc0, 2 * NR + e, end_kb(e), 0, 4);
    if (e == ENDK - 1) bar_arrive(1 + wg, 256);
    wgmma_wait<1>();
    if (e > 0 || wg == 0) release(2 * NR + e);
  }
  wgmma_wait<0>();
  release(2 * NR + ENDK);
  TL(41);
  auto delay_to = [&](unsigned t0, unsigned t) {
    while (__any_sync(0xffffffffu, clk32() - t0 < t)) {}
  };
  {
    uint32_t af[4 * ENDK][4];
    const uint32_t abase = sbase + SMEM_X + wg * (XS * X_SLICE) + ((warp & 3) * 16 + (lane & 15)) * 128;
    float accp[112];
    const unsigned t0 = clk32();
#pragma unroll
    for (int J = 0; J < 7; J++) {
      if (J > 0) delay_to(t0, J * ST_GAP);
      store_acc(acc0, op, J, J + 1);
      if (J == 0) {
#pragma unroll
        for (int i = 0; i < 112; i++) asm volatile("add.rn.f32 %0, %1, 0f00000000;" : "=f"(accp[i]) : "f"(acc1[i]));
      }
      if (J >= 1 && J <= ENDK) {
        const int e = J - 1, n = 2 * NR + ENDK + e;
        ring_wait<XS>(fullx, n);
#pragma unroll
        for (int k = 0; k < 4; k++)
          asm volatile("ldmatrix.sync.aligned.m8n8.x4.shared.b16 {%0, %1, %2, %3}, [%4];"
                       : "=r"(af[4 * e + k][0]), "=r"(af[4 * e + k][1]), "=r"(af[4 * e + k][2]), "=r"(af[4 * e + k][3])
                       : "r"(abase + (n % XS) * X_SLICE + (((2 * k + (lane >> 4)) ^ (lane & 7)) << 4))
                       : "memory");
      }
    }
    TL(42);
    auto part = [&](auto P, int s0, int s1) {
      constexpr int p = decltype(P)::value;
      wgmma_fence();
#pragma unroll
      for (int st = s0; st < s1; st++) {
        const int kb = end_kb(st >> 2);
        const uint64_t db = make_desc(db0 + w_ring(kb) * (W_STAGE >> 4) + (st & 3) * (2 * W_KC >> 4) +
                                          (p == 0 ? 0 : 32 + 64 * p), DB_HI);
        if constexpr (p == 0) wgmma_rs_m64n96k16<0>(accp, af[st], db);
        else wgmma_rs_m64n64k16<16 + 32 * p>(accp, af[st], db);
      }
      wgmma_commit();
    };
    bar_sync(2 - wg, 256);
    TL(51);
    part(IC<0>{}, 0, 4 * ENDK);
    part(IC<1>{}, 0, LEAD);
    wgmma_wait<1>();
    if (wg == 1) store_acc(accp, op + 64 * F_DIM, 0, 3);
    part(IC<1>{}, LEAD, 4 * ENDK);
    part(IC<2>{}, 0, LEAD);
    wgmma_wait<1>();
    if (wg == 0) store_acc(accp, op + 64 * F_DIM, 0, 3);
    else store_acc(accp, op + 64 * F_DIM, 3, 5);
    part(IC<2>{}, LEAD, 4 * ENDK);
    if (wg == 0) {
      bar_arrive(1, 256);
      store_acc(accp, op + 64 * F_DIM, 3, 5);
    }
    wgmma_wait<0>();
    TL(43); TLG(47);
    store_acc(accp, op + 64 * F_DIM, 5, 7);
  }
  TL(44);
}

__global__ void __launch_bounds__(BN)
prefill_kernel(const int* __restrict__ qw, const __nv_bfloat16* __restrict__ lut,
               const __nv_bfloat16* __restrict__ scales, uint8_t* scratch) {
  const int j = blockIdx.x & 15, kc = blockIdx.x >> 4, f = j * BN + perm32(threadIdx.x);
  int q[8];
#pragma unroll
  for (int i = 0; i < 8; i++) q[i] = qw[(kc * 8 + i) * F_DIM + f];
  *reinterpret_cast<uint4*>(scratch + (size_t)j * REGION + W_OFF + kc * W_KC + threadIdx.x * 16) =
      convert_unit(q, make_table(__bfloat162float(lut[threadIdx.x & 15]), __bfloat162float(scales[f])));
}

typedef CUresult (*EncodeTiledFn)(CUtensorMap*, CUtensorMapDataType, cuuint32_t, void*, const cuuint64_t*,
                                  const cuuint64_t*, const cuuint32_t*, const cuuint32_t*, CUtensorMapInterleave,
                                  CUtensorMapSwizzle, CUtensorMapL2promotion, CUtensorMapFloatOOBfill);

}

extern "C" void kernel_launch(void* const* d_in, const int* in_sizes, int n_in, void* d_out, int out_size) {
  const __nv_bfloat16* x = (const __nv_bfloat16*)d_in[0];
  const int* qw = (const int*)d_in[1];
  const __nv_bfloat16* lut = (const __nv_bfloat16*)d_in[2];
  const __nv_bfloat16* scales = (const __nv_bfloat16*)d_in[3];
  __nv_bfloat16* out = (__nv_bfloat16*)d_out;

  static EncodeTiledFn enc = nullptr;
  static uint8_t* p_scr = nullptr;
  static bool coresident = false;
  if (!enc) {
    void* fn = nullptr;
    cudaDriverEntryPointQueryResult qr;
    cudaGetDriverEntryPoint("cuTensorMapEncodeTiled", &fn, cudaEnableDefault, &qr);
    enc = (EncodeTiledFn)fn;
    void* p = nullptr;
    cudaGetSymbolAddress(&p, g_scratch);
    p_scr = (uint8_t*)(((uintptr_t)p + REGION - 1) & ~(uintptr_t)(REGION - 1));
    cudaFuncSetAttribute(fused_kernel, cudaFuncAttributeMaxDynamicSharedMemorySize, SMEM_TOTAL);
    int dev = 0, sms = 0;
    cudaGetDevice(&dev);
    cudaDeviceGetAttribute(&sms, cudaDevAttrMultiProcessorCount, dev);
    coresident = sms >= NI * NJ;
  }
  CUtensorMap tm_x, tm_q;
  cuuint32_t estr[2] = {1, 1};
  {
    cuuint64_t gdim[2] = {(cuuint64_t)D_DIM, (cuuint64_t)S_DIM};
    cuuint64_t gstr[1] = {(cuuint64_t)D_DIM * 2};
    cuuint32_t box[2] = {(cuuint32_t)BK, 64};
    enc(&tm_x, CU_TENSOR_MAP_DATA_TYPE_BFLOAT16, 2, (void*)x, gdim, gstr, box, estr, CU_TENSOR_MAP_INTERLEAVE_NONE,
        CU_TENSOR_MAP_SWIZZLE_128B, CU_TENSOR_MAP_L2_PROMOTION_NONE, CU_TENSOR_MAP_FLOAT_OOB_FILL_NONE);
  }
  {
    cuuint64_t gdim[2] = {(cuuint64_t)F_DIM, (cuuint64_t)D_DIM};
    cuuint64_t gstr[1] = {(cuuint64_t)F_DIM * 4};
    cuuint32_t box[2] = {(cuuint32_t)BN, 8};
    enc(&tm_q, CU_TENSOR_MAP_DATA_TYPE_INT32, 2, (void*)qw, gdim, gstr, box, estr, CU_TENSOR_MAP_INTERLEAVE_NONE,
        CU_TENSOR_MAP_SWIZZLE_NONE, CU_TENSOR_MAP_L2_PROMOTION_NONE, CU_TENSOR_MAP_FLOAT_OOB_FILL_NONE);
  }
  if (!coresident) prefill_kernel<<<NJ * NKB * 8, BN, 0, cudaStreamPerThread>>>(qw, lut, scales, p_scr);
  fused_kernel<<<NI * NJ, 256, SMEM_TOTAL, cudaStreamPerThread>>>(qw, lut, scales, out, p_scr,
                                                                  coresident ? FLAG_FULL : 0u, tm_x, tm_q);
}
```

```cpp
#include <cuda_runtime.h>
#include <cuda_bf16.h>
#include <cuda.h>
#include <stdint.h>

namespace {

constexpr int S_DIM = 2048, D_DIM = 1024, F_DIM = 3584;
constexpr int BM = 256, BN = 224, BK = 64;
constexpr int NKB = D_DIM / BK;
constexpr int NJ = F_DIM / BN;
constexpr int NI = S_DIM / BM;
constexpr int WS = 4;
constexpr int XS = 5;
constexpr int ENDK = 5;
constexpr int NR = NKB - ENDK;
constexpr int X_SLICE = 64 * BK * 2;
constexpr int W_STAGE = BN * BK * 2;
constexpr int W_KC = BN * 16;

constexpr int REGION = 512 * 1024;
__device__ uint4 g_scratch[(NJ + 1) * REGION / 16];

__device__ __forceinline__ uint32_t smem_u32(const void* p) { return (uint32_t)__cvta_generic_to_shared(p); }
__device__ __forceinline__ unsigned clk32() {
  unsigned c;
  asm volatile("mov.u32 %0, %%clock;" : "=r"(c)::"memory");
  return c;
}
__device__ __forceinline__ bool elect_one() {
  uint32_t p;
  asm volatile("{\n.reg .pred P;\nelect.sync _|P, 0xffffffff;\nselp.b32 %0, 1, 0, P;\n}" : "=r"(p));
  return p != 0;
}
__device__ __forceinline__ void mbar_init(uint32_t bar, uint32_t cnt) {
  asm volatile("mbarrier.init.shared::cta.b64 [%0], %1;" ::"r"(bar), "r"(cnt) : "memory");
}
__device__ __forceinline__ void mbar_expect_tx(uint32_t bar, uint32_t bytes) {
  asm volatile("mbarrier.arrive.expect_tx.shared::cta.b64 _, [%0], %1;" ::"r"(bar), "r"(bytes) : "memory");
}
__device__ __forceinline__ void mbar_arrive(uint32_t bar) {
  asm volatile("mbarrier.arrive.shared::cta.b64 _, [%0];" ::"r"(bar) : "memory");
}
__device__ __forceinline__ void mbar_wait(uint32_t bar, uint32_t parity) {
  asm volatile(
      "{\n.reg .pred p;\n"
      "LAB_WAIT:\n"
      "mbarrier.try_wait.parity.shared::cta.b64 p, [%0], %1;\n"
      "@p bra LAB_DONE;\n"
      "bra LAB_WAIT;\n"
      "LAB_DONE:\n}\n" ::"r"(bar), "r"(parity) : "memory");
}
template <int N>
__device__ __forceinline__ uint32_t ring(uint32_t base, int i) { return base + 8 * (i % N); }
template <int N>
__device__ __forceinline__ void ring_wait(uint32_t base, int i) { mbar_wait(ring<N>(base, i), (i / N) & 1); }
__device__ __forceinline__ void tma_load_2d(uint32_t dst, const CUtensorMap* tm, int c0, int c1, uint32_t bar) {
  asm volatile(
      "cp.async.bulk.tensor.2d.shared::cluster.global.mbarrier::complete_tx::bytes [%0], [%1, {%3, %4}], [%2];"
      ::"r"(dst), "l"(tm), "r"(bar), "r"(c0), "r"(c1) : "memory");
}
__device__ __forceinline__ void bulk_load(uint32_t dst, const void* src, uint32_t bytes, uint32_t bar) {
  asm volatile(
      "cp.async.bulk.shared::cluster.global.mbarrier::complete_tx::bytes [%0], [%1], %2, [%3];"
      ::"r"(dst), "l"(src), "r"(bytes), "r"(bar) : "memory");
}
__device__ __forceinline__ void cp_async16(uint32_t dst, const void* src) {
  asm volatile("cp.async.cg.shared.global [%0], [%1], 16;" ::"r"(dst), "l"(src) : "memory");
}
__device__ __forceinline__ void cp_async_commit() { asm volatile("cp.async.commit_group;" ::: "memory"); }
template <int N>
__device__ __forceinline__ void cp_async_wait() { asm volatile("cp.async.wait_group %0;" ::"n"(N) : "memory"); }
__device__ __forceinline__ uint32_t ldg_u16(const void* p) {
  uint32_t v;
  asm volatile("ld.global.u16 %0, [%1];" : "=r"(v) : "l"(p) : "memory");
  return v;
}
__device__ __forceinline__ int lds32(uint32_t addr) {
  int v;
  asm volatile("ld.shared.b32 %0, [%1];" : "=r"(v) : "r"(addr) : "memory");
  return v;
}
__device__ __forceinline__ void sts128(uint32_t addr, uint4 v) {
  asm volatile("st.shared.v4.u32 [%0], {%1, %2, %3, %4};" ::"r"(addr), "r"(v.x), "r"(v.y), "r"(v.z), "r"(v.w) : "memory");
}
__device__ __forceinline__ uint64_t make_desc(uint32_t lo, uint32_t hi) {
  uint64_t d;
  asm("mov.b64 %0, {%1, %2};" : "=l"(d) : "r"(lo), "r"(hi));
  return d;
}
__device__ __forceinline__ unsigned ld_strong(const void* p) {
  unsigned v;
  asm volatile("ld.relaxed.gpu.global.u32 %0, [%1];" : "=r"(v) : "l"(p) : "memory");
  return v;
}
__device__ __forceinline__ void st_strong128(void* p, uint4 v) {
  asm volatile("st.relaxed.gpu.global.v4.u32 [%0], {%1, %2, %3, %4};" ::"l"(p), "r"(v.x), "r"(v.y), "r"(v.z), "r"(v.w)
               : "memory");
}
__device__ __forceinline__ void wgmma_fence() { asm volatile("wgmma.fence.sync.aligned;" ::: "memory"); }
__device__ __forceinline__ void wgmma_commit() { asm volatile("wgmma.commit_group.sync.aligned;" ::: "memory"); }
template <int N>
__device__ __forceinline__ void wgmma_wait() { asm volatile("wgmma.wait_group.sync.aligned %0;" ::"n"(N) : "memory"); }
__device__ __forceinline__ void bar_sync(int id, int n) { asm volatile("bar.sync %0, %1;" ::"r"(id), "r"(n) : "memory"); }
__device__ __forceinline__ void bar_arrive(int id, int n) { asm volatile("bar.arrive %0, %1;" ::"r"(id), "r"(n) : "memory"); }

__device__ __forceinline__ void wgmma_m64n224k16(float (&d)[112], uint64_t da, uint64_t db, int scale_d) {
  asm volatile(
    "{\n.reg .pred p;\nsetp.ne.b32 p, %114, 0;\n"
    "wgmma.mma_async.sync.aligned.m64n224k16.f32.bf16.bf16 "
    "{%0, %1, %2, %3, %4, %5, %6, %7, %8, %9, %10, %11, %12, %13, %14, %15, "
    "%16, %17, %18, %19, %20, %21, %22, %23, %24, %25, %26, %27, %28, %29, %30, %31, "
    "%32, %33, %34, %35, %36, %37, %38, %39, %40, %41, %42, %43, %44, %45, %46, %47, "
    "%48, %49, %50, %51, %52, %53, %54, %55, %56, %57, %58, %59, %60, %61, %62, %63, "
    "%64, %65, %66, %67, %68, %69, %70, %71, %72, %73, %74, %75, %76, %77, %78, %79, "
    "%80, %81, %82, %83, %84, %85, %86, %87, %88, %89, %90, %91, %92, %93, %94, %95, "
    "%96, %97, %98, %99, %100, %101, %102, %103, %104, %105, %106, %107, %108, %109, %110, %111}, "
    "%112, %113, p, 1, 1, 0, 0;\n}\n"
    : "+f"(d[0]), "+f"(d[1]), "+f"(d[2]), "+f"(d[3]), "+f"(d[4]), "+f"(d[5]), "+f"(d[6]), "+f"(d[7]),
      "+f"(d[8]), "+f"(d[9]), "+f"(d[10]), "+f"(d[11]), "+f"(d[12]), "+f"(d[13]), "+f"(d[14]), "+f"(d[15]),
      "+f"(d[16]), "+f"(d[17]), "+f"(d[18]), "+f"(d[19]), "+f"(d[20]), "+f"(d[21]), "+f"(d[22]), "+f"(d[23]),
      "+f"(d[24]), "+f"(d[25]), "+f"(d[26]), "+f"(d[27]), "+f"(d[28]), "+f"(d[29]), "+f"(d[30]), "+f"(d[31]),
      "+f"(d[32]), "+f"(d[33]), "+f"(d[34]), "+f"(d[35]), "+f"(d[36]), "+f"(d[37]), "+f"(d[38]), "+f"(d[39]),
      "+f"(d[40]), "+f"(d[41]), "+f"(d[42]), "+f"(d[43]), "+f"(d[44]), "+f"(d[45]), "+f"(d[46]), "+f"(d[47]),
      "+f"(d[48]), "+f"(d[49]), "+f"(d[50]), "+f"(d[51]), "+f"(d[52]), "+f"(d[53]), "+f"(d[54]), "+f"(d[55]),
      "+f"(d[56]), "+f"(d[57]), "+f"(d[58]), "+f"(d[59]), "+f"(d[60]), "+f"(d[61]), "+f"(d[62]), "+f"(d[63]),
      "+f"(d[64]), "+f"(d[65]), "+f"(d[66]), "+f"(d[67]), "+f"(d[68]), "+f"(d[69]), "+f"(d[70]), "+f"(d[71]),
      "+f"(d[72]), "+f"(d[73]), "+f"(d[74]), "+f"(d[75]), "+f"(d[76]), "+f"(d[77]), "+f"(d[78]), "+f"(d[79]),
      "+f"(d[80]), "+f"(d[81]), "+f"(d[82]), "+f"(d[83]), "+f"(d[84]), "+f"(d[85]), "+f"(d[86]), "+f"(d[87]),
      "+f"(d[88]), "+f"(d[89]), "+f"(d[90]), "+f"(d[91]), "+f"(d[92]), "+f"(d[93]), "+f"(d[94]), "+f"(d[95]),
      "+f"(d[96]), "+f"(d[97]), "+f"(d[98]), "+f"(d[99]), "+f"(d[100]), "+f"(d[101]), "+f"(d[102]), "+f"(d[103]),
      "+f"(d[104]), "+f"(d[105]), "+f"(d[106]), "+f"(d[107]), "+f"(d[108]), "+f"(d[109]), "+f"(d[110]), "+f"(d[111])
    : "l"(da), "l"(db), "r"(scale_d));
}
template <int O>
__device__ __forceinline__ void wgmma_rs_m64n96k16(float (&d)[112], const uint32_t (&a)[4], uint64_t db) {
  asm volatile(
    "wgmma.mma_async.sync.aligned.m64n96k16.f32.bf16.bf16 "
    "{%0, %1, %2, %3, %4, %5, %6, %7, %8, %9, %10, %11, %12, %13, %14, %15, "
    "%16, %17, %18, %19, %20, %21, %22, %23, %24, %25, %26, %27, %28, %29, %30, %31, "
    "%32, %33, %34, %35, %36, %37, %38, %39, %40, %41, %42, %43, %44, %45, %46, %47}, "
    "{%48, %49, %50, %51}, %52, 1, 1, 1, 0;\n"
    : "+f"(d[O + 0]), "+f"(d[O + 1]), "+f"(d[O + 2]), "+f"(d[O + 3]),
      "+f"(d[O + 4]), "+f"(d[O + 5]), "+f"(d[O + 6]), "+f"(d[O + 7]),
      "+f"(d[O + 8]), "+f"(d[O + 9]), "+f"(d[O + 10]), "+f"(d[O + 11]),
      "+f"(d[O + 12]), "+f"(d[O + 13]), "+f"(d[O + 14]), "+f"(d[O + 15]),
      "+f"(d[O + 16]), "+f"(d[O + 17]), "+f"(d[O + 18]), "+f"(d[O + 19]),
      "+f"(d[O + 20]), "+f"(d[O + 21]), "+f"(d[O + 22]), "+f"(d[O + 23]),
      "+f"(d[O + 24]), "+f"(d[O + 25]), "+f"(d[O + 26]), "+f"(d[O + 27]),
      "+f"(d[O + 28]), "+f"(d[O + 29]), "+f"(d[O + 30]), "+f"(d[O + 31]),
      "+f"(d[O + 32]), "+f"(d[O + 33]), "+f"(d[O + 34]), "+f"(d[O + 35]),
      "+f"(d[O + 36]), "+f"(d[O + 37]), "+f"(d[O + 38]), "+f"(d[O + 39]),
      "+f"(d[O + 40]), "+f"(d[O + 41]), "+f"(d[O + 42]), "+f"(d[O + 43]),
      "+f"(d[O + 44]), "+f"(d[O + 45]), "+f"(d[O + 46]), "+f"(d[O + 47])
    : "r"(a[0]), "r"(a[1]), "r"(a[2]), "r"(a[3]), "l"(db));
}
template <int O>
__device__ __forceinline__ void wgmma_rs_m64n64k16(float (&d)[112], const uint32_t (&a)[4], uint64_t db) {
  asm volatile(
    "wgmma.mma_async.sync.aligned.m64n64k16.f32.bf16.bf16 "
    "{%0, %1, %2, %3, %4, %5, %6, %7, %8, %9, %10, %11, %12, %13, %14, %15, "
    "%16, %17, %18, %19, %20, %21, %22, %23, %24, %25, %26, %27, %28, %29, %30, %31}, "
    "{%32, %33, %34, %35}, %36, 1, 1, 1, 0;\n"
    : "+f"(d[O + 0]), "+f"(d[O + 1]), "+f"(d[O + 2]), "+f"(d[O + 3]),
      "+f"(d[O + 4]), "+f"(d[O + 5]), "+f"(d[O + 6]), "+f"(d[O + 7]),
      "+f"(d[O + 8]), "+f"(d[O + 9]), "+f"(d[O + 10]), "+f"(d[O + 11]),
      "+f"(d[O + 12]), "+f"(d[O + 13]), "+f"(d[O + 14]), "+f"(d[O + 15]),
      "+f"(d[O + 16]), "+f"(d[O + 17]), "+f"(d[O + 18]), "+f"(d[O + 19]),
      "+f"(d[O + 20]), "+f"(d[O + 21]), "+f"(d[O + 22]), "+f"(d[O + 23]),
      "+f"(d[O + 24]), "+f"(d[O + 25]), "+f"(d[O + 26]), "+f"(d[O + 27]),
      "+f"(d[O + 28]), "+f"(d[O + 29]), "+f"(d[O + 30]), "+f"(d[O + 31])
    : "r"(a[0]), "r"(a[1]), "r"(a[2]), "r"(a[3]), "l"(db));
}

__device__ __forceinline__ uint32_t pack_bf16(float lo, float hi) {
  uint32_t r;
  asm("cvt.rn.bf16x2.f32 %0, %1, %2;" : "=r"(r) : "f"(hi), "f"(lo));
  return r;
}

__device__ __forceinline__ int perm32(int n) { return (n & ~30) | ((n & 6) << 2) | ((n >> 2) & 6); }

constexpr int SMEM_X = 0;
constexpr int SMEM_W = 2 * XS * X_SLICE;
constexpr int SMEM_Q = SMEM_W + WS * W_STAGE;
constexpr int Q_UNIT = 8 * BN * 4;
constexpr int SMEM_BAR = SMEM_Q + W_STAGE;
constexpr int B_FULLW = 0, B_FULLQ = 5, B_FULLX = 9, B_DONE = 19, B_W0 = 35, B_RAW0 = 36;
constexpr int SMEM_TL = SMEM_BAR + 512;
constexpr int SMEM_TOTAL = SMEM_TL;
constexpr int W_OFF = 128;
constexpr unsigned FLAG_FULL = NI * 7;

#define TL(i)
#define TLG(i)

__device__ __forceinline__ void store_acc(const float (&a)[112], __nv_bfloat16* p, int J0, int J1) {
#pragma unroll
  for (int J = J0; J < J1; J++) {
    uint4 v0, v1;
    v0.x = pack_bf16(a[16 * J + 0], a[16 * J + 1]);
    v0.y = pack_bf16(a[16 * J + 4], a[16 * J + 5]);
    v0.z = pack_bf16(a[16 * J + 8], a[16 * J + 9]);
    v0.w = pack_bf16(a[16 * J + 12], a[16 * J + 13]);
    v1.x = pack_bf16(a[16 * J + 2], a[16 * J + 3]);
    v1.y = pack_bf16(a[16 * J + 6], a[16 * J + 7]);
    v1.z = pack_bf16(a[16 * J + 10], a[16 * J + 11]);
    v1.w = pack_bf16(a[16 * J + 14], a[16 * J + 15]);
    *reinterpret_cast<uint4*>(p + 32 * J) = v0;
    *reinterpret_cast<uint4*>(p + 8 * F_DIM + 32 * J) = v1;
  }
}

struct Table {
  uint32_t lo[4], hi[4];
};
__device__ __forceinline__ uint32_t prmt(uint32_t a, uint32_t b, uint32_t s) {
  uint32_t r;
  asm("prmt.b32 %0, %1, %2, %3;" : "=r"(r) : "r"(a), "r"(b), "r"(s));
  return r;
}
__device__ __forceinline__ Table make_table(float lutv, float sc) {
  Table t;
#pragma unroll
  for (int i = 0; i < 4; i++) {
    const uint32_t a = pack_bf16(__shfl_sync(0xffffffffu, lutv, 4 * i) * sc, __shfl_sync(0xffffffffu, lutv, 4 * i + 1) * sc);
    const uint32_t b =
        pack_bf16(__shfl_sync(0xffffffffu, lutv, 4 * i + 2) * sc, __shfl_sync(0xffffffffu, lutv, 4 * i + 3) * sc);
    t.lo[i] = prmt(a, b, 0x6420);
    t.hi[i] = prmt(a, b, 0x7531);
  }
  return t;
}
__device__ __forceinline__ uint4 convert_unit(const int (&q)[8], const Table& t) {
  const uint32_t all = ((q[7] * 16 + q[6]) * 256 + (q[5] * 16 + q[4])) * 65536 + ((q[3] * 16 + q[2]) * 256 + (q[1] * 16 + q[0]));
  const uint32_t s7 = all & 0x77777777u;
  const uint32_t s2 = ((all >> 1) & 0x44444444u) | 0x32103210u;
  uint32_t o[4];
#pragma unroll
  for (int h = 0; h < 2; h++) {
    const uint32_t a = h ? s7 >> 16 : s7, b = h ? s2 >> 16 : s2;
    const uint32_t lo = prmt(prmt(t.lo[0], t.lo[1], a), prmt(t.lo[2], t.lo[3], a), b);
    const uint32_t hi = prmt(prmt(t.hi[0], t.hi[1], a), prmt(t.hi[2], t.hi[3], a), b);
    o[2 * h] = prmt(lo, hi, 0x5140);
    o[2 * h + 1] = prmt(lo, hi, 0x7362);
  }
  return make_uint4(o[0], o[1], o[2], o[3]);
}

constexpr int PU = 3;
#define HEAVY 0x3EEEAu
__host__ __device__ constexpr int popc(unsigned v) { return v ? (v & 1) + popc(v >> 1) : 0; }
__host__ __device__ constexpr bool heavy(int n) { return n >= 0 && ((HEAVY >> n) & 1); }
__host__ __device__ constexpr int unit_at(int n) { return PU + popc(HEAVY & ((1u << n) - 1)); }
__host__ __device__ constexpr int emit_slot(int u) {
  if (u < PU) return -1;
  for (int n = 0; n < 24; n++)
    if (heavy(n) && unit_at(n) == u) return n;
  return 99;
}
__host__ __device__ constexpr int end_kb(int e) { return e < 3 ? NR + e : NR + 7 - e; }
__host__ __device__ constexpr int w_ring(int m) { return m == 15 ? 4 : m & 3; }
__host__ __device__ constexpr int cmax(int a, int b) { return a > b ? a : b; }
__host__ __device__ constexpr int w_slot(int m) {
  return m == 15 ? cmax(emit_slot(15) + 3, 20) : cmax(2 * m - 5, emit_slot(m) + 3);
}
__host__ __device__ constexpr int q_slot(int u) {
  return u == 5 ? 2 : cmax(cmax(q_slot(u - 1) + 1, emit_slot(u) - 3), u < 8 ? 2 : emit_slot(u - 4) + 2);
}
__host__ __device__ constexpr int w_at(int n) {
  for (int m = 2; m < NKB; m++)
    if (w_slot(m) == n) return m;
  return -1;
}
__host__ __device__ constexpr int q_at(int n) {
  for (int u = 5; u < NKB; u++)
    if (q_slot(u) == n) return u;
  return -1;
}
constexpr bool schedule_ok() {
  if (popc(HEAVY) != NKB - PU || (HEAVY & 7) != 2 || (HEAVY >> 20)) return false;
  for (int m = 2; m < NKB; m++) {
    if (w_at(w_slot(m)) != m || (m != 14 && w_slot(m) >= 2 * NR)) return false;
    if (m < NR && w_slot(m) > 2 * m - 2) return false;
  }
  for (int u = 5; u < NKB; u++)
    if (q_slot(u) + 2 > emit_slot(u)) return false;
  return true;
}
static_assert(schedule_ok(), "bad schedule");
template <int V>
struct IC {
  static constexpr int value = V;
};
template <int I, int N, class F>
__device__ __forceinline__ void static_for(F&& f) {
  if constexpr (I < N) {
    f(IC<I>{});
    static_for<I + 1, N>(f);
  }
}

#define NCP 3
#define RSPLIT 5
#define STAG_L 70
#define PACE_INIT 550
#define PACE_X 950
#define PACE_Q2 1450
#define PACE_Q3 1950
#define PUB_AT 6
#define ST_GAP 150
#define LEAD 8

constexpr uint32_t sbase = 1024;

__global__ void __launch_bounds__(256, 1)
fused_kernel(const int* __restrict__ qw, const __nv_bfloat16* __restrict__ lut,
             const __nv_bfloat16* __restrict__ scales, __nv_bfloat16* __restrict__ out, uint8_t* scratch,
             unsigned flag_full,
             const __grid_constant__ CUtensorMap tm_x, const __grid_constant__ CUtensorMap tm_q) {
  extern __shared__ __align__(1024) uint8_t smem_raw[];
  constexpr uint32_t bars = sbase + SMEM_BAR;
  const int j = blockIdx.x >> 3, it = blockIdx.x & 7;
  constexpr uint32_t raw0 = sbase + SMEM_W + 2 * W_STAGE;
  uint32_t lut_raw = 0, sc_raw = 0;
  if (threadIdx.x < 224) {
    const unsigned t = threadIdx.x, row0 = (t >> 3) & 3, col = (t & ~31u) + (t & 7) * 4;
    const int* src = qw + (row0 * F_DIM + j * BN + col);
    const uint32_t dst = row0 * (BN * 4) + col * 4;
    lut_raw = ldg_u16(lut + (t & 15));
    sc_raw = ldg_u16(scales + (j * BN + perm32(t)));
    __syncwarp();
#pragma unroll
    for (int g = 0; g < NCP + 1; g++) {
      const unsigned row = g == 0 ? BK + it * 8 : (g - 1) * 8;
      const uint32_t d = dst + (g == 0 ? sbase + SMEM_Q + Q_UNIT : raw0 + (g - 1) * Q_UNIT);
      cp_async16(d, src + row * F_DIM);
      cp_async16(d + 4 * BN * 4, src + (row + 4) * F_DIM);
      cp_async_commit();
    }
  }
  const int warp = __shfl_sync(0xffffffffu, threadIdx.x >> 5, 0);
  const int wg = warp >> 2;
  int lane;
  asm volatile("mov.u32 %0, %%laneid;" : "=r"(lane));
  const unsigned t_start = clk32();
  auto pace = [&](unsigned t) {
    while (__any_sync(0xffffffffu, clk32() - t_start < t)) {}
  };

  uint8_t* const region = scratch + (size_t)j * REGION;
  uint8_t* const wp = region + (warp < 7 ? W_OFF + it * W_KC + (warp * 32 + lane) * 16 : lane * 4);
  unsigned* const fl = reinterpret_cast<unsigned*>(wp);
  Table tab;
  unsigned rb;
  const int xrow = it * BM + wg * 128;

  auto w_ptr = [&](int u) { return reinterpret_cast<uint4*>(wp + u * W_STAGE); };
  auto emit_unit = [&](uint4 w, int u) {
    st_strong128(w_ptr(u), w);
    rb = ld_strong(w_ptr(u));
  };
  auto publish = [&](int u) {
    asm volatile(
        "{\n.reg .pred P, Q;\n"
        "setp.ne.u32 P, %1, 0xffffffff;\n"
        "vote.sync.all.pred P, P, 0xffffffff;\n"
        "elect.sync _|Q, 0xffffffff;\n"
        "and.pred Q, Q, P;\n"
        "@Q red.relaxed.gpu.global.add.u32 [%0], 1;\n}"
        ::"l"(region + u * 4), "r"(rb) : "memory");
  };
  auto load_x = [&](int g, int n, int kb, int half) {
    const uint32_t bar = ring<XS>(bars + 8 * B_FULLX, n) + g * (8 * XS);
    mbar_expect_tx(bar, X_SLICE);
    tma_load_2d(sbase + SMEM_X + (n % XS) * X_SLICE + g * (XS * X_SLICE), &tm_x, kb * BK,
                it * BM + g * 128 + half * 64, bar);
  };
  auto load_q = [&](int u) {
    const uint32_t bar = ring<4>(bars + 8 * B_FULLQ, u);
    mbar_expect_tx(bar, Q_UNIT);
    tma_load_2d(sbase + SMEM_Q + (u & 3) * Q_UNIT, &tm_q, j * BN, u * BK + it * 8, bar);
  };

  unsigned ready = 0;
  auto load_w = [&](int m) {
    const uint32_t bar = bars + 8 * (B_FULLW + w_ring(m));
    mbar_expect_tx(bar, W_STAGE);
    bulk_load(sbase + SMEM_W + w_ring(m) * W_STAGE, region + W_OFF + m * W_STAGE, W_STAGE, bar);
  };
  auto wait_w = [&](int m) { mbar_wait(bars + 8 * (B_FULLW + w_ring(m)), m == 15 ? 0 : (m >> 2) & 1); };
  auto poll = [&]() { ready |= __ballot_sync(0xffffffffu, ld_strong(fl) >= flag_full); };
  auto wait_ready = [&](int kb) {
    int spins = 0;
    while (!((ready >> kb) & 1)) {
      poll();
      if (++spins > (1 << 22)) __trap();
    }
  };

  uint32_t qbase;
  asm volatile("mov.u32 %0, %1;" : "=r"(qbase) : "r"(sbase + SMEM_Q + warp * 128 + perm32(lane) * 4));
  auto lds_unit = [&](int (&q)[8], int u) {
    ring_wait<4>(bars + 8 * B_FULLQ, u);
#pragma unroll
    for (int i = 0; i < 8; i++) q[i] = lds32(qbase + (u & 3) * Q_UNIT + i * (BN * 4));
  };
  auto arrive_one = [&](uint32_t bar) {
    asm volatile("{\n.reg .pred P;\nelect.sync _|P, 0xffffffff;\n@P mbarrier.arrive.shared::cta.b64 _, [%0];\n}"
                 ::"r"(bar) : "memory");
  };

  if (warp == 7) {
    if (elect_one()) {
      mbar_init(bars + 8 * B_RAW0, RSPLIT - NCP);
      mbar_init(bars + 8 * B_RAW0 + 8, 8 - RSPLIT);
      asm volatile("fence.mbarrier_init.release.cluster;" ::: "memory");
    }
    __syncwarp();
    bar_arrive(4, (9 - NCP) * 32);
    if (elect_one()) {
      asm volatile("prefetch.tensormap [%0];" ::"l"(&tm_x) : "memory");
      asm volatile("prefetch.tensormap [%0];" ::"l"(&tm_q) : "memory");
    }
    TL(5);
    pace(PACE_INIT);
    if (elect_one()) {
#pragma unroll
      for (int i = 0; i < B_RAW0; i++) mbar_init(bars + 8 * i, i == B_W0 ? 7 : i >= B_DONE ? 4 : 1);
      asm volatile("fence.mbarrier_init.release.cluster;" ::: "memory");
    }
    __syncwarp();
    rb = ld_strong(fl);
    bar_arrive(0, 256);
    TL(4);
#pragma unroll
    for (int i = 0; i < 4; i++) tab.lo[i] = tab.hi[i] = 0;
    if (smem_u32(smem_raw) != sbase) __trap();
    if (elect_one()) {
      mbar_arrive(bars + 8 * B_FULLW);
      mbar_arrive(bars + 8 * B_FULLQ);
      mbar_arrive(bars + 8 * B_FULLQ + 8);
    }
    pace(PACE_X);
    if (elect_one()) {
      load_x(0, 0, 0, 0); load_x(1, 0, 0, 0); load_x(0, 1, 0, 1); load_x(1, 1, 0, 1);
    }
    pace(PACE_Q2);
    if (elect_one()) load_q(2);
    pace(PACE_Q3);
    ready = __ballot_sync(0xffffffffu, rb >= flag_full);
    rb = ld_strong(fl);
    if (elect_one()) {
      load_q(3);
      load_x(0, 2, 1, 0); load_x(1, 2, 1, 0); load_x(0, 3, 1, 1); load_x(1, 3, 1, 1);
    }
    ready |= __ballot_sync(0xffffffffu, rb >= flag_full);
    wait_ready(1);
    asm volatile("fence.proxy.async.global;" ::: "memory");
    if (elect_one()) {
      load_w(1);
      load_x(0, 4, 2, 0); load_x(1, 4, 2, 0);
    }
    TL(2);
    TL(3);
  } else {
    if (warp + NCP < 8) {
      bar_sync(4, (9 - NCP) * 32);
      pace(warp * STAG_L);
      if (elect_one()) {
        const int c = warp + NCP;
        const uint32_t bar = bars + 8 * B_RAW0 + (c < RSPLIT ? 0 : 8);
        mbar_expect_tx(bar, Q_UNIT);
#pragma unroll
        for (int i = 0; i < 8; i++)
          bulk_load(raw0 + (c * 8 + i) * (BN * 4), qw + (size_t)(c * 8 + i) * F_DIM + j * BN, BN * 4, bar);
      }
    }
    bar_sync(0, 256);
    pace(200);
    asm volatile("shl.b32 %0, %0, 16;\nshl.b32 %1, %1, 16;" : "+r"(lut_raw), "+r"(sc_raw));
    tab = make_table(__uint_as_float(lut_raw), __uint_as_float(sc_raw));
    if (__any_sync(0xffffffffu, lane > 31 && (tab.lo[0] ^ tab.lo[1] ^ tab.lo[2] ^ tab.lo[3] ^ tab.hi[0] ^ tab.hi[1] ^
                                              tab.hi[2] ^ tab.hi[3]) == 1))
      __trap();
    int r[2][8];
    auto lds_group = [&](auto G) {
      constexpr int g = decltype(G)::value, c = g > 0 ? g - 1 : 0;
      if constexpr (g <= NCP) {
        cp_async_wait<NCP - g>();
        __syncwarp();
      } else {
        if (c == NCP) mbar_wait(bars + 8 * B_RAW0, 0);
        if (c == RSPLIT) mbar_wait(bars + 8 * B_RAW0 + 8, 0);
      }
#pragma unroll
      for (int i = 0; i < 8; i++)
        r[g & 1][i] = lds32(qbase + (g == 0 ? Q_UNIT : raw0 - sbase - SMEM_Q + c * Q_UNIT) + i * (BN * 4));
    };
    lds_group(IC<0>{});
    TL(6);
    static_for<0, 9>([&](auto G) {
      constexpr int g = decltype(G)::value, c = g > 0 ? g - 1 : 0;
      if (g == PUB_AT) {
        publish(1);
        TL(3);
      }
      if (g == 0) {
        emit_unit(convert_unit(r[g & 1], tab), 1);
        __syncwarp();
        TL(2);
        if constexpr (g < 8) lds_group(IC<g + 1>{});
      } else {
        if constexpr (g < 8) lds_group(IC<g + 1>{});
        sts128(sbase + SMEM_W + c * W_KC + (warp * 32 + lane) * 16, convert_unit(r[g & 1], tab));
      }
    });
    asm volatile("fence.proxy.async.shared::cta;" ::: "memory");
    __syncwarp();
    arrive_one(bars + 8 * B_W0);
    TL(4);
    if (wg == 1) {
      lds_unit(r[0], 2);
      emit_unit(convert_unit(r[0], tab), 2);
    }
    TL(5);
  }

  float acc0[112], acc1[112];
  constexpr uint32_t DA_HI = (1u << 30) | (1024 >> 4), DB_HI = (128 >> 4);
  const uint32_t da0 = ((1u << 16) | ((sbase + SMEM_X) >> 4)) + wg * (XS * X_SLICE >> 4);
  constexpr uint32_t db0 = ((W_KC >> 4) << 16) | ((sbase + SMEM_W) >> 4);
  const uint32_t fullx = bars + 8 * B_FULLX + wg * (8 * XS), done = bars + 8 * B_DONE + wg * 64;
  const bool x_issuer = (warp & 3) == 3;

  auto mma = [&](float (&acc)[112], int n, int kb, int k0, int k1) {
    wgmma_fence();
#pragma unroll
    for (int k = k0; k < k1; k++)
      wgmma_m64n224k16(acc, make_desc(da0 + (n % XS) * (X_SLICE >> 4) + k * 2, DA_HI),
                       make_desc(db0 + w_ring(kb) * (W_STAGE >> 4) + k * (2 * W_KC >> 4), DB_HI), kb != 0 || k != 0);
    wgmma_commit();
  };
  auto release = [&](int n) {
    arrive_one(ring<8>(done, n));
    if (x_issuer) {
      ring_wait<8>(done, n);
      const int m = n + 4;
      if (elect_one())
        load_x(wg, m, m < 2 * NR ? m >> 1 : end_kb((m - 2 * NR) % ENDK), m < 2 * NR ? m & 1 : (m - 2 * NR) / ENDK);
    }
  };
  auto end_slot = [&](int n) {
    wgmma_wait<1>();
    release(n);
  };
  auto slot = [&](float (&acc)[112], auto N) {
    constexpr int n = decltype(N)::value;
    constexpr bool hv = heavy(n), pub = heavy(n - 1);
    ring_wait<XS>(fullx, n);
    constexpr int m = w_at(n);
    if (m >= 0 && warp == 7) rb = ld_strong(fl);
    mma(acc, n, n >> 1, 0, 4);
    end_slot(n);
    if (warp < 7) {
      constexpr int u = unit_at(n);
      int q[8];
      if (hv) lds_unit(q, u);
      if (pub) publish(u - 1);
      if (hv) emit_unit(convert_unit(q, tab), u);
    } else {
      constexpr int u = q_at(n);
      if (m >= 0 || u >= 0) ring_wait<8>(bars + 8 * B_DONE, n - 1);
      if (m >= 0) {
        ready |= __ballot_sync(0xffffffffu, rb >= flag_full);
        wait_ready(m);
        asm volatile("fence.proxy.async.global;" ::: "memory");
      }
      if ((m >= 0 || u >= 0) && elect_one()) {
        if (m >= 0) load_w(m);
        if (u >= 0) load_q(u);
      }
    }
  };

  mbar_wait(bars + 8 * B_W0, 0);
  mbar_wait(fullx, 0);
  TL(8); TLG(46);
  mma(acc0, 0, 0, 0, 4);
  mbar_wait(fullx + 8, 0);
  TL(9);
  mma(acc1, 1, 0, 0, 4);
  arrive_one(done);
  if (warp < 7) {
    if (wg == 0) {
      int q2[8];
      lds_unit(q2, 2);
      emit_unit(convert_unit(q2, tab), 2);
    } else {
      publish(2);
    }
    int q3[8];
    lds_unit(q3, 3);
    const uint4 w3 = convert_unit(q3, tab);
    if (wg == 0) publish(2);
    emit_unit(w3, 3);
  } else {
    if (elect_one()) load_q(4);
  }
  end_slot(1);

  static_for<1, NR>([&](auto R) {
    constexpr int r = decltype(R)::value;
    wait_w(r);
    TL(8 + 2 * r);
    slot(acc0, IC<2 * r>{});
    TL(9 + 2 * r);
    slot(acc1, IC<2 * r + 1>{});
  });

  __nv_bfloat16* op = out + (size_t)(xrow + (warp & 3) * 16 + (lane >> 2)) * F_DIM + j * BN + (lane & 3) * 8;
  TL(40); TLG(48);
  if (wg == 1) {
    wgmma_wait<0>();
    release(2 * NR);
    if (warp == 7) {
      wait_ready(14);
      asm volatile("fence.proxy.async.global;" ::: "memory");
      ring_wait<8>(bars + 8 * B_DONE, 2 * NR);
      if (elect_one()) load_w(14);
      unsigned old = 0;
      if (lane == 17) old = atomicAdd(fl, 1u);
      if (__shfl_sync(0xffffffffu, old, 17) == NI - 1) *fl = 0;
    }
    bar_sync(1, 256);
  }
#pragma unroll
  for (int e = 0; e < ENDK; e++) {
    wait_w(end_kb(e));
    ring_wait<XS>(fullx, 2 * NR + e);
    mma(acc0, 2 * NR + e, end_kb(e), 0, 4);
    if (e == ENDK - 1) bar_arrive(1 + wg, 256);
    wgmma_wait<1>();
    if (e > 0 || wg == 0) release(2 * NR + e);
  }
  wgmma_wait<0>();
  release(2 * NR + ENDK);
  TL(41);
  auto delay_to = [&](unsigned t0, unsigned t) {
    while (__any_sync(0xffffffffu, clk32() - t0 < t)) {}
  };
  {
    uint32_t af[4 * ENDK][4];
    const uint32_t abase = sbase + SMEM_X + wg * (XS * X_SLICE) + ((warp & 3) * 16 + (lane & 15)) * 128;
    float accp[112];
    const unsigned t0 = clk32();
#pragma unroll
    for (int J = 0; J < 7; J++) {
      if (J > 0) delay_to(t0, J * ST_GAP);
      store_acc(acc0, op, J, J + 1);
      if (J == 0) {
#pragma unroll
        for (int i = 0; i < 112; i++) asm volatile("add.rn.f32 %0, %1, 0f00000000;" : "=f"(accp[i]) : "f"(acc1[i]));
      }
      if (J >= 1 && J <= ENDK) {
        const int e = J - 1, n = 2 * NR + ENDK + e;
        ring_wait<XS>(fullx, n);
#pragma unroll
        for (int k = 0; k < 4; k++)
          asm volatile("ldmatrix.sync.aligned.m8n8.x4.shared.b16 {%0, %1, %2, %3}, [%4];"
                       : "=r"(af[4 * e + k][0]), "=r"(af[4 * e + k][1]), "=r"(af[4 * e + k][2]), "=r"(af[4 * e + k][3])
                       : "r"(abase + (n % XS) * X_SLICE + (((2 * k + (lane >> 4)) ^ (lane & 7)) << 4))
                       : "memory");
      }
    }
    TL(42);
    auto part = [&](auto P, int s0, int s1) {
      constexpr int p = decltype(P)::value;
      wgmma_fence();
#pragma unroll
      for (int st = s0; st < s1; st++) {
        const int kb = end_kb(st >> 2);
        const uint64_t db = make_desc(db0 + w_ring(kb) * (W_STAGE >> 4) + (st & 3) * (2 * W_KC >> 4) +
                                          (p == 0 ? 0 : 32 + 64 * p), DB_HI);
        if constexpr (p == 0) wgmma_rs_m64n96k16<0>(accp, af[st], db);
        else wgmma_rs_m64n64k16<16 + 32 * p>(accp, af[st], db);
      }
      wgmma_commit();
    };
    bar_sync(2 - wg, 256);
    TL(51);
    part(IC<0>{}, 0, 4 * ENDK);
    part(IC<1>{}, 0, LEAD);
    wgmma_wait<1>();
    if (wg == 1) store_acc(accp, op + 64 * F_DIM, 0, 3);
    part(IC<1>{}, LEAD, 4 * ENDK);
    part(IC<2>{}, 0, LEAD);
    wgmma_wait<1>();
    if (wg == 0) store_acc(accp, op + 64 * F_DIM, 0, 3);
    else store_acc(accp, op + 64 * F_DIM, 3, 5);
    part(IC<2>{}, LEAD, 4 * ENDK - 4);
    if (wg == 0) bar_arrive(1, 256);
    part(IC<2>{}, 4 * ENDK - 4, 4 * ENDK);
    if (wg == 0) store_acc(accp, op + 64 * F_DIM, 3, 5);
    wgmma_wait<0>();
    TL(43); TLG(47);
    store_acc(accp, op + 64 * F_DIM, 5, 7);
  }
  TL(44);
}

__global__ void __launch_bounds__(BN)
prefill_kernel(const int* __restrict__ qw, const __nv_bfloat16* __restrict__ lut,
               const __nv_bfloat16* __restrict__ scales, uint8_t* scratch) {
  const int j = blockIdx.x & 15, kc = blockIdx.x >> 4, f = j * BN + perm32(threadIdx.x);
  int q[8];
#pragma unroll
  for (int i = 0; i < 8; i++) q[i] = qw[(kc * 8 + i) * F_DIM + f];
  *reinterpret_cast<uint4*>(scratch + (size_t)j * REGION + W_OFF + kc * W_KC + threadIdx.x * 16) =
      convert_unit(q, make_table(__bfloat162float(lut[threadIdx.x & 15]), __bfloat162float(scales[f])));
}

typedef CUresult (*EncodeTiledFn)(CUtensorMap*, CUtensorMapDataType, cuuint32_t, void*, const cuuint64_t*,
                                  const cuuint64_t*, const cuuint32_t*, const cuuint32_t*, CUtensorMapInterleave,
                                  CUtensorMapSwizzle, CUtensorMapL2promotion, CUtensorMapFloatOOBfill);

}

extern "C" void kernel_launch(void* const* d_in, const int* in_sizes, int n_in, void* d_out, int out_size) {
  const __nv_bfloat16* x = (const __nv_bfloat16*)d_in[0];
  const int* qw = (const int*)d_in[1];
  const __nv_bfloat16* lut = (const __nv_bfloat16*)d_in[2];
  const __nv_bfloat16* scales = (const __nv_bfloat16*)d_in[3];
  __nv_bfloat16* out = (__nv_bfloat16*)d_out;

  static EncodeTiledFn enc = nullptr;
  static uint8_t* p_scr = nullptr;
  static bool coresident = false;
  if (!enc) {
    void* fn = nullptr;
    cudaDriverEntryPointQueryResult qr;
    cudaGetDriverEntryPoint("cuTensorMapEncodeTiled", &fn, cudaEnableDefault, &qr);
    enc = (EncodeTiledFn)fn;
    void* p = nullptr;
    cudaGetSymbolAddress(&p, g_scratch);
    p_scr = (uint8_t*)(((uintptr_t)p + REGION - 1) & ~(uintptr_t)(REGION - 1));
    cudaFuncSetAttribute(fused_kernel, cudaFuncAttributeMaxDynamicSharedMemorySize, SMEM_TOTAL);
    int dev = 0, sms = 0;
    cudaGetDevice(&dev);
    cudaDeviceGetAttribute(&sms, cudaDevAttrMultiProcessorCount, dev);
    coresident = sms >= NI * NJ;
  }
  CUtensorMap tm_x, tm_q;
  cuuint32_t estr[2] = {1, 1};
  {
    cuuint64_t gdim[2] = {(cuuint64_t)D_DIM, (cuuint64_t)S_DIM};
    cuuint64_t gstr[1] = {(cuuint64_t)D_DIM * 2};
    cuuint32_t box[2] = {(cuuint32_t)BK, 64};
    enc(&tm_x, CU_TENSOR_MAP_DATA_TYPE_BFLOAT16, 2, (void*)x, gdim, gstr, box, estr, CU_TENSOR_MAP_INTERLEAVE_NONE,
        CU_TENSOR_MAP_SWIZZLE_128B, CU_TENSOR_MAP_L2_PROMOTION_NONE, CU_TENSOR_MAP_FLOAT_OOB_FILL_NONE);
  }
  {
    cuuint64_t gdim[2] = {(cuuint64_t)F_DIM, (cuuint64_t)D_DIM};
    cuuint64_t gstr[1] = {(cuuint64_t)F_DIM * 4};
    cuuint32_t box[2] = {(cuuint32_t)BN, 8};
    enc(&tm_q, CU_TENSOR_MAP_DATA_TYPE_INT32, 2, (void*)qw, gdim, gstr, box, estr, CU_TENSOR_MAP_INTERLEAVE_NONE,
        CU_TENSOR_MAP_SWIZZLE_NONE, CU_TENSOR_MAP_L2_PROMOTION_NONE, CU_TENSOR_MAP_FLOAT_OOB_FILL_NONE);
  }
  if (!coresident) prefill_kernel<<<NJ * NKB * 8, BN, 0, cudaStreamPerThread>>>(qw, lut, scales, p_scr);
  fused_kernel<<<NI * NJ, 256, SMEM_TOTAL, cudaStreamPerThread>>>(qw, lut, scales, out, p_scr,
                                                                  coresident ? FLAG_FULL : 0u, tm_x, tm_q);
}
```
